```python
import torch

def _softmax(x, axis=-1):
    return torch.softmax(x, dim=axis)
def _gelu(x):
    return torch.nn.functional.gelu(x, approximate="tanh")
def _silu(x):
    return torch.nn.functional.silu(x)
def _sigmoid(x):
    return torch.sigmoid(x)
def _layernorm(x, axis=-1, eps=1e-5):
    m = x.mean(dim=axis, keepdim=True)
    v = x.var(dim=axis, keepdim=True, unbiased=False)
    return (x - m) / torch.sqrt(v + eps)
def _scatter_add(tgt, idx, src, axis=0):
    return tgt.clone().index_add_(axis, idx, src)
def _segment_sum(src, seg, n):
    out = torch.zeros((n,) + src.shape[1:], dtype=src.dtype)
    return out.index_add_(0, seg, src)
def _pad(x, pw):
    flat = tuple(v for pair in reversed(pw) for v in pair)
    return torch.nn.functional.pad(x, flat)

kernel_name = 'interleave_layers__sliding_block__moe_arch_mod__prompt'

def setup_inputs():

    _w = (lambda a: (lambda t: t.to(torch.bfloat16) if t.is_floating_point() else t)(torch.as_tensor(a)))
    def _A_setup():
        B, S, D = 1, 2048, 1024
        return {
            "x": _w((lambda *s: torch.randn(*s, dtype=torch.bfloat16) * 0.05)(B, S, D)),
            "wqkv": _w((lambda *s: torch.randn(*s, dtype=torch.bfloat16) * 0.05)(D, 3 * D)),
            "wo": _w((lambda *s: torch.randn(*s, dtype=torch.bfloat16) * 0.05)(D, D)),
        }
    _A_in = _A_setup()

    def _B_setup():
        B, S, D, F, C = 1, 2048, 1024, 3584, 1
        return {
            "x": _w((lambda *s: torch.randn(*s, dtype=torch.bfloat16) * 0.05)(B, S, D)),
            "w_r": _w((lambda *s: torch.randn(*s, dtype=torch.bfloat16) * 1.6)(D)),
            "w_gate": _w((lambda *s: torch.randn(*s, dtype=torch.bfloat16) * 0.1)(D, F)),
            "w_up": _w((lambda *s: torch.randn(*s, dtype=torch.bfloat16) * 0.1)(D, F)),
            "w_down": _w((lambda *s: torch.randn(*s, dtype=torch.bfloat16) * 0.1)(F, D)),
        }
    _B_in = _B_setup()

    return {
        "A_x": _A_in["x"],
        "A_wqkv": _A_in["wqkv"],
        "A_wo": _A_in["wo"],
        "B_x": _B_in["x"],
        "B_w_r": _B_in["w_r"],
        "B_w_gate": _B_in["w_gate"],
        "B_w_up": _B_in["w_up"],
        "B_w_down": _B_in["w_down"],
    }

def reference(A_x, A_wqkv, A_wo, B_x, B_w_r, B_w_gate, B_w_up, B_w_down):
    def _A_ref(x, wqkv, wo):
        B, S, D = x.shape
        H = 32; Dh = D // H; W = 256
        qkv = (lambda x, *d: x.permute(*d))((x @ wqkv).reshape(B, S, 3, H, Dh), 2, 0, 3, 1, 4)
        q, k, v = qkv[0], qkv[1], qkv[2]
        scores = torch.einsum("bhqd,bhkd->bhqk", q, k) * (Dh ** -0.5)
        idx = torch.arange(S)
        mask = (idx[:, None] - idx[None, :] >= 0) & (idx[:, None] - idx[None, :] < W)
        scores = torch.where(mask[None, None], scores, -1e9)
        p = _softmax(scores, axis=-1)
        o = torch.einsum("bhqk,bhkd->bhqd", p, v)
        return (lambda x, *d: x.permute(*d))(o, 0, 2, 1, 3).reshape(B, S, D) @ wo

    def _B_ref(x, w_r, w_gate, w_up, w_down):
        B, S, D = x.shape
        C = 1
        r = x @ w_r
        idx = torch.argsort(-r, axis=-1)[:, :C]
        idx_e = (lambda x, n, axis: torch.repeat_interleave(x, n, dim=axis))(idx.reshape(B, C, 1), D, axis=2)
        x_sel = (lambda x, i, axis: torch.take_along_dim(x, i, dim=axis))(x, idx_e, axis=1)
        g = _silu(x_sel @ w_gate)
        u = x_sel @ w_up
        y = (g * u) @ w_down
        r_sel = _sigmoid((lambda x, i, axis: torch.take_along_dim(x, i, dim=axis))(r, idx, axis=1))
        y = y * r_sel.reshape(B, C, 1)
        b_off = (torch.arange(B) * S).reshape(B, 1)
        flat_idx = (idx + b_off).reshape(B * C)
        zero = (x * 0.0).reshape(B * S, D)
        upd = _scatter_add(zero, flat_idx, y.reshape(B * C, D), axis=0)
        return x + upd.reshape(B, S, D)

    x = A_x
    x = x + _A_ref(_layernorm(x, axis=-1), A_wqkv, A_wo)
    x = x + _B_ref(_layernorm(x, axis=-1), B_w_r, B_w_gate, B_w_up, B_w_down)
    x = x + _A_ref(_layernorm(x, axis=-1), A_wqkv, A_wo)
    x = x + _B_ref(_layernorm(x, axis=-1), B_w_r, B_w_gate, B_w_up, B_w_down)
    return x
```

```cpp
#include <cuda_runtime.h>
#include <cuda_bf16.h>
#include <cuda.h>
#include <stdint.h>

namespace {

constexpr int SEQ = 2048, DM = 1024, FF = 3584;
constexpr float LN_EPS = 1e-5f;
typedef __nv_bfloat16 bf16;

__device__ __align__(1024) uint8_t g_kv[3 * 16 * 65536];
__device__ __align__(1024) uint8_t g_o[SEQ * DM * 2];
__device__ __align__(1024) bf16 g_x2[SEQ * DM];
__device__ unsigned g_epoch;
struct __align__(128) Flag { unsigned v[32]; };
__device__ Flag g_kvflag[3][16][3], g_oflag[8][2][16], g_xflag[16][8];
__device__ uint4 g_rowab[2][SEQ];
__device__ __align__(16) uint32_t g_cspart[4][3 * DM];
constexpr uint32_t SENT = 0xFFFFFFFFu;
__device__ uint4 g_part[2][8 * SEQ];
__device__ uint4 g_slot[2][16 * 8];
__device__ uint4 g_cand[2][16 * 128];
__device__ uint4 g_ypart[2][128 * DM / 4];
__device__ uint4 g_x2row[128 * 2];
__device__ __align__(16) uint32_t g_patch[8][3 * DM];
__device__ int g_sel[2];

#define PROFL(l, e)
#define PROF(e) PROFL(layer, e)
#define STEPT(i)
#define SPIN_LIMIT 4000000u
__device__ __forceinline__ uint32_t smem_u32(const void* p) { return (uint32_t)__cvta_generic_to_shared(p); }
__device__ __forceinline__ void mbar_init(uint32_t bar, uint32_t cnt) {
  asm volatile("mbarrier.init.shared::cta.b64 [%0], %1;" ::"r"(bar), "r"(cnt) : "memory");
}
#define ELECT "{\n.reg .pred e;\nelect.sync _|e, 0xffffffff;\n@e "
__device__ __forceinline__ void mbar_expect_tx(uint32_t bar, uint32_t bytes) {
  asm volatile(ELECT "mbarrier.arrive.expect_tx.shared::cta.b64 _, [%0], %1;\n}" ::"r"(bar), "r"(bytes) : "memory");
}
__device__ __forceinline__ void mbar_arrive(uint32_t bar) {
  asm volatile("mbarrier.arrive.shared::cta.b64 _, [%0];" ::"r"(bar) : "memory");
}
__device__ __forceinline__ void mbar_arrive_e(uint32_t bar) {
  asm volatile(ELECT "mbarrier.arrive.shared::cta.b64 _, [%0];\n}" ::"r"(bar) : "memory");
}
__device__ __forceinline__ uint32_t mapa(uint32_t addr, uint32_t cta) {
  uint32_t r; asm("mapa.shared::cluster.u32 %0, %1, %2;" : "=r"(r) : "r"(addr), "r"(cta)); return r;
}
__device__ __forceinline__ void mbar_arrive_cluster(uint32_t bar, uint32_t cta) {
  asm volatile("mbarrier.arrive.shared::cluster.b64 _, [%0];" ::"r"(mapa(bar, cta)) : "memory");
}
#define MBAR_WAIT_ASM(QUAL)                                                                                                \
  asm volatile("{\n.reg .pred p;\n.reg .u32 n;\nmov.u32 n, 0;\nWAIT_LOOP:\n.pragma \"nounroll\";\n"                         \
               "mbarrier.try_wait.parity" QUAL ".shared::cta.b64 p, [%0], %1;\n@p bra WAIT_DONE;\n"                        \
               "add.u32 n, n, 1;\nsetp.lt.u32 p, n, %2;\n@p bra WAIT_LOOP;\nWAIT_DONE:\n}" ::"r"(bar), "r"(parity), "n"(SPIN_LIMIT) : "memory")
__device__ __forceinline__ void mbar_wait(uint32_t bar, uint32_t parity) { MBAR_WAIT_ASM(""); }
__device__ __forceinline__ void mbar_wait_cluster(uint32_t bar, uint32_t parity) { MBAR_WAIT_ASM(".acquire.cluster"); }
__device__ __forceinline__ void st_async2(uint32_t addr, float a, float b, uint32_t bar) {
  asm volatile("st.async.weak.shared::cluster.mbarrier::complete_tx::bytes.v2.f32 [%0], {%1, %2}, [%3];"
               ::"r"(addr), "f"(a), "f"(b), "r"(bar) : "memory");
}
__device__ __forceinline__ uint64_t policy_evict_first() {
  uint64_t p; asm volatile("createpolicy.fractional.L2::evict_first.b64 %0, 1.0;" : "=l"(p)); return p;
}
__device__ __forceinline__ uint64_t policy_normal() {
  uint64_t p; asm volatile("createpolicy.fractional.L2::evict_normal.b64 %0, 1.0;" : "=l"(p)); return p;
}
__device__ __forceinline__ void tma_load2(uint32_t dst, const CUtensorMap* m, int c0, int c1, uint32_t bar) {
  asm volatile(ELECT "cp.async.bulk.tensor.2d.shared::cluster.global.mbarrier::complete_tx::bytes [%0], [%1, {%3, %4}], [%2];\n}"
               ::"r"(dst), "l"(m), "r"(bar), "r"(c0), "r"(c1) : "memory");
}
__device__ __forceinline__ void tma_load2_h(uint32_t dst, const CUtensorMap* m, int c0, int c1, uint32_t bar, uint64_t pol) {
  asm volatile(ELECT "cp.async.bulk.tensor.2d.shared::cluster.global.mbarrier::complete_tx::bytes.L2::cache_hint [%0], [%1, {%3, %4}], [%2], %5;\n}"
               ::"r"(dst), "l"(m), "r"(bar), "r"(c0), "r"(c1), "l"(pol) : "memory");
}
__device__ __forceinline__ void tma_load3(uint32_t dst, const CUtensorMap* m, int c0, int c1, int c2, uint32_t bar) {
  asm volatile(ELECT "cp.async.bulk.tensor.3d.shared::cluster.global.mbarrier::complete_tx::bytes [%0], [%1, {%3, %4, %5}], [%2];\n}"
               ::"r"(dst), "l"(m), "r"(bar), "r"(c0), "r"(c1), "r"(c2) : "memory");
}
__device__ __forceinline__ void tma_load3_h(uint32_t dst, const CUtensorMap* m, int c0, int c1, int c2, uint32_t bar, uint64_t pol) {
  asm volatile(ELECT "cp.async.bulk.tensor.3d.shared::cluster.global.mbarrier::complete_tx::bytes.L2::cache_hint [%0], [%1, {%3, %4, %5}], [%2], %6;\n}"
               ::"r"(dst), "l"(m), "r"(bar), "r"(c0), "r"(c1), "r"(c2), "l"(pol) : "memory");
}
__device__ __forceinline__ void tma_load3_mc(uint32_t dst, const CUtensorMap* m, int c0, int c1, int c2, uint32_t bar) {
  asm volatile(ELECT "cp.async.bulk.tensor.3d.shared::cluster.global.mbarrier::complete_tx::bytes.multicast::cluster [%0], [%1, {%3, %4, %5}], [%2], %6;\n}"
               ::"r"(dst), "l"(m), "r"(bar), "r"(c0), "r"(c1), "r"(c2), "h"((uint16_t)3) : "memory");
}
__device__ __forceinline__ void bulk_push(uint32_t dst, uint32_t src, uint32_t bytes, uint32_t bar) {
  asm volatile(ELECT "cp.async.bulk.shared::cluster.shared::cta.mbarrier::complete_tx::bytes [%0], [%1], %2, [%3];\n}"
               ::"r"(dst), "r"(src), "r"(bytes), "r"(bar) : "memory");
}
template <int N> __device__ __forceinline__ void regs_inc() { asm volatile("setmaxnreg.inc.sync.aligned.u32 %0;" ::"n"(N)); }
template <int N> __device__ __forceinline__ void regs_dec() { asm volatile("setmaxnreg.dec.sync.aligned.u32 %0;" ::"n"(N)); }
__device__ __forceinline__ void tma_store(const CUtensorMap* m, uint32_t src, int c0, int c1) {
  asm volatile(ELECT "cp.async.bulk.tensor.2d.global.shared::cta.bulk_group [%0, {%2, %3}], [%1];\n}"
               ::"l"(m), "r"(src), "r"(c0), "r"(c1) : "memory");
}
__device__ __forceinline__ void bulk_load(uint32_t dst, const void* src, uint32_t bytes, uint32_t bar) {
  asm volatile(ELECT "cp.async.bulk.shared::cluster.global.mbarrier::complete_tx::bytes [%0], [%1], %2, [%3];\n}"
               ::"r"(dst), "l"(src), "r"(bytes), "r"(bar) : "memory");
}
__device__ __forceinline__ void bulk_load_h(uint32_t dst, const void* src, uint32_t bytes, uint32_t bar, uint64_t pol) {
  asm volatile(ELECT "cp.async.bulk.shared::cluster.global.mbarrier::complete_tx::bytes.L2::cache_hint [%0], [%1], %2, [%3], %4;\n}"
               ::"r"(dst), "l"(src), "r"(bytes), "r"(bar), "l"(pol) : "memory");
}
__device__ __forceinline__ void bulk_store(void* dst, uint32_t src, uint32_t bytes) {
  asm volatile(ELECT "cp.async.bulk.global.shared::cta.bulk_group [%0], [%1], %2;\n}" ::"l"(dst), "r"(src), "r"(bytes) : "memory");
}
__device__ __forceinline__ void bulk_commit() { asm volatile("cp.async.bulk.commit_group;" ::: "memory"); }
__device__ __forceinline__ void bulk_wait_all() { asm volatile("cp.async.bulk.wait_group 0;" ::: "memory"); }
__device__ __forceinline__ void fence_async_smem() { asm volatile("fence.proxy.async.shared::cta;" ::: "memory"); }
__device__ __forceinline__ void fence_async_global() { asm volatile("fence.proxy.async.global;" ::: "memory"); }
__device__ __forceinline__ void fence_release() { asm volatile("fence.release.gpu;" ::: "memory"); }
__device__ __forceinline__ void l2_prefetch_line(const void* p) { asm volatile("prefetch.global.L2 [%0];" ::"l"(p) : "memory"); }
__device__ __forceinline__ void prefetch_tmap(const CUtensorMap* m) { asm volatile("prefetch.tensormap [%0];" ::"l"(m) : "memory"); }
__device__ __forceinline__ void named_bar(int id, int n) { asm volatile("bar.sync %0, %1;" ::"r"(id), "r"(n) : "memory"); }
__device__ __forceinline__ bool bar_red_or(int id, int n, bool v) {
  uint32_t r;
  asm volatile("{\n.reg .pred p, q;\nsetp.ne.u32 q, %3, 0;\nbarrier.cta.red.or.pred p, %1, %2, q;\nselp.u32 %0, 1, 0, p;\n}"
               : "=r"(r) : "r"(id), "r"(n), "r"((uint32_t)v) : "memory");
  return r != 0;
}
__device__ __forceinline__ void cluster_arrive() { asm volatile("barrier.cluster.arrive.relaxed.aligned;" ::: "memory"); }
__device__ __forceinline__ void cluster_wait() { asm volatile("barrier.cluster.wait.aligned;" ::: "memory"); }
__device__ __forceinline__ uint32_t cluster_rank() { uint32_t r; asm volatile("mov.u32 %0, %%cluster_ctarank;" : "=r"(r)); return r; }
__device__ __forceinline__ unsigned ld_relaxed(const unsigned* p) {
  unsigned v; asm volatile("ld.relaxed.gpu.global.u32 %0, [%1];" : "=r"(v) : "l"(p) : "memory"); return v;
}
__device__ __forceinline__ uint4 ld_relaxed4(const uint4* p) {
  uint4 v; asm volatile("ld.relaxed.gpu.global.v4.u32 {%0, %1, %2, %3}, [%4];" : "=r"(v.x), "=r"(v.y), "=r"(v.z), "=r"(v.w) : "l"(p) : "memory"); return v;
}
__device__ __forceinline__ void st_relaxed(unsigned* p, unsigned v) {
  asm volatile("st.relaxed.gpu.global.u32 [%0], %1;" ::"l"(p), "r"(v) : "memory");
}
__device__ __forceinline__ uint2 ld_relaxed2(const void* p) {
  uint2 v; asm volatile("ld.relaxed.gpu.global.v2.u32 {%0, %1}, [%2];" : "=r"(v.x), "=r"(v.y) : "l"(p) : "memory"); return v;
}
__device__ __forceinline__ void st_relaxed4(uint4* p, uint4 v) {
  asm volatile("st.relaxed.gpu.global.v4.u32 [%0], {%1, %2, %3, %4};" ::"l"(p), "r"(v.x), "r"(v.y), "r"(v.z), "r"(v.w) : "memory");
}
__device__ __forceinline__ bool valid4(uint4 v) { return v.x != SENT && v.y != SENT && v.z != SENT && v.w != SENT; }
__device__ __forceinline__ uint4 poll4(const uint4* p) {
  uint4 v;
  uint32_t spins = 0;
#pragma unroll 1
  do { v = ld_relaxed4(p); } while (!valid4(v) && ++spins < SPIN_LIMIT);
  return v;
}
__device__ __forceinline__ void set_flag(unsigned* p, unsigned tag) {
  asm volatile(ELECT "st.release.gpu.global.u32 [%0], %1;\n}" ::"l"(p), "r"(tag) : "memory");
}
__device__ __forceinline__ void poll_flag(const unsigned* p, unsigned tag) {
#pragma unroll 1
  for (uint32_t spins = 0; !__all_sync(0xffffffffu, ld_relaxed(p) == tag) && spins < SPIN_LIMIT; spins++) {}
  asm volatile("fence.acquire.gpu;" ::: "memory");
}
__device__ __forceinline__ uint32_t enc(float x) { return __float_as_uint(x + 0.0f) ^ 0x80000000u; }
__device__ __forceinline__ float dec(uint32_t u) { return __uint_as_float(u ^ 0x80000000u); }
__device__ __forceinline__ uint32_t f2u(float x) { uint32_t u = __float_as_uint(x); return u == SENT ? 0x7FFFFFFFu : u; }
__device__ __forceinline__ uint32_t nosent(uint32_t u) { return u == SENT ? 0x7FFF7FFFu : u; }
__device__ __forceinline__ uint32_t hadd_bf2(uint32_t a, uint32_t b) {
  uint32_t r; asm("add.rn.bf16x2 %0, %1, %2;" : "=r"(r) : "r"(a), "r"(b)); return r;
}
__device__ __forceinline__ uint32_t hsub_bf2(uint32_t a, uint32_t b) {
  uint32_t r; asm("sub.rn.bf16x2 %0, %1, %2;" : "=r"(r) : "r"(a), "r"(b)); return r;
}
__device__ __forceinline__ void wg_fence() { asm volatile("wgmma.fence.sync.aligned;" ::: "memory"); }
__device__ __forceinline__ void wg_commit() { asm volatile("wgmma.commit_group.sync.aligned;" ::: "memory"); }
template <int N> __device__ __forceinline__ void wg_wait() { asm volatile("wgmma.wait_group.sync.aligned %0;" ::"n"(N) : "memory"); }
template <int R> __device__ __forceinline__ void fence_regs(float* d) {
#pragma unroll
  for (int i = 0; i < R; i++) asm volatile("" : "+f"(d[i])::"memory");
}
template <int R> __device__ __forceinline__ void fence_regs_u(uint32_t* d) {
#pragma unroll
  for (int i = 0; i < R; i++) asm volatile("" : "+r"(d[i])::"memory");
}
__host__ __device__ constexpr uint32_t dlo(uint32_t addr, uint32_t lbo) { return ((addr & 0x3FFFF) >> 4) | ((lbo >> 4) << 16); }
constexpr uint32_t H128 = 0x40000040u, H64 = 0x80000020u;
__device__ __forceinline__ void stsm_x4(uint32_t addr, uint32_t r0, uint32_t r1, uint32_t r2, uint32_t r3) {
  asm volatile("stmatrix.sync.aligned.m8n8.x4.shared.b16 [%0], {%1, %2, %3, %4};"
               ::"r"(addr), "r"(r0), "r"(r1), "r"(r2), "r"(r3) : "memory");
}
__device__ __forceinline__ void ldsm_x4(uint32_t addr, uint32_t& r0, uint32_t& r1, uint32_t& r2, uint32_t& r3) {
  asm volatile("ldmatrix.sync.aligned.m8n8.x4.shared.b16 {%0, %1, %2, %3}, [%4];"
               : "=r"(r0), "=r"(r1), "=r"(r2), "=r"(r3) : "r"(addr) : "memory");
}
__device__ __forceinline__ void ldsm_x4_t(uint32_t addr, uint32_t& r0, uint32_t& r1, uint32_t& r2, uint32_t& r3) {
  asm volatile("ldmatrix.sync.aligned.m8n8.x4.trans.shared.b16 {%0, %1, %2, %3}, [%4];"
               : "=r"(r0), "=r"(r1), "=r"(r2), "=r"(r3) : "r"(addr) : "memory");
}
__device__ __forceinline__ void mma_16816(float* d, uint32_t a0, uint32_t a1, uint32_t a2, uint32_t a3, uint32_t b0, uint32_t b1) {
  asm volatile("mma.sync.aligned.m16n8k16.row.col.f32.bf16.bf16.f32 {%0, %1, %2, %3}, {%4, %5, %6, %7}, {%8, %9}, {%0, %1, %2, %3};"
               : "+f"(d[0]), "+f"(d[1]), "+f"(d[2]), "+f"(d[3]) : "r"(a0), "r"(a1), "r"(a2), "r"(a3), "r"(b0), "r"(b1));
}
__device__ __forceinline__ void spin_cycles(int n) {
  const int t0 = (int)clock();
#pragma unroll 1
  while ((int)clock() - t0 < n) {}
}
__device__ __forceinline__ uint32_t pack_bf16(float lo, float hi) {
  uint32_t r; asm("cvt.rn.bf16x2.f32 %0, %1, %2;" : "=r"(r) : "f"(hi), "f"(lo)); return r;
}
__device__ __forceinline__ float bf_lo(uint32_t v) { return __uint_as_float(v << 16); }
__device__ __forceinline__ float bf_hi(uint32_t v) { return __uint_as_float(v & 0xffff0000u); }
__device__ __forceinline__ float rbf(float x) { return __bfloat162float(__float2bfloat16_rn(x)); }
__device__ __forceinline__ float ex2(float x) { float y; asm("ex2.approx.ftz.f32 %0, %1;" : "=f"(y) : "f"(x)); return y; }
__device__ __forceinline__ uint32_t shl_clamp(uint32_t v, uint32_t n) {
  uint32_t r; asm("shl.b32 %0, %1, %2;" : "=r"(r) : "r"(v), "r"(n)); return r;
}
__device__ __forceinline__ float warp_sum(float v) {
#pragma unroll
  for (int o = 16; o > 0; o >>= 1) v += __shfl_xor_sync(0xffffffffu, v, o);
  return v;
}
__device__ __forceinline__ float ln_inv(float var) {
  float r;
  asm("sqrt.approx.ftz.f32 %0, %1;" : "=f"(r) : "f"(rbf(rbf(var) + LN_EPS)));
  asm("rcp.approx.ftz.f32 %0, %1;" : "=f"(r) : "f"(rbf(r)));
  return r;
}
__device__ __forceinline__ uint32_t ln_pair(uint32_t x, uint32_t mean2, float inv) {
  const uint32_t d = hsub_bf2(x, mean2);
  return pack_bf16(bf_lo(d) * inv, bf_hi(d) * inv);
}
__device__ __forceinline__ uint32_t add_ln_pair(uint32_t x, uint32_t mean2, float inv) { return hadd_bf2(x, ln_pair(x, mean2, inv)); }
__device__ __forceinline__ uint32_t router_key(float r_bf, int row) {
  uint32_t u = __float_as_uint(r_bf);
  u = (u & 0x80000000u) ? ~u : (u | 0x80000000u);
  return (u & 0xFFFF0000u) | (uint32_t)(SEQ - 1 - row);
}

template <uint32_t HA = 0x40000040u, uint32_t HB = 0x40000040u>
__device__ __forceinline__ void wg_ss192t(float* d, uint32_t da, uint32_t db, int scale_d) {
  asm volatile("{\n.reg .pred p;\n.reg .b64 dA, dB;\nmov.b64 dA, {%96, %99};\nmov.b64 dB, {%97, %100};\nsetp.ne.b32 p, %98, 0;\n"
    "wgmma.mma_async.sync.aligned.m64n192k16.f32.bf16.bf16 "
    "{%0, %1, %2, %3, %4, %5, %6, %7, %8, %9, %10, %11, %12, %13, %14, %15, "
    "%16, %17, %18, %19, %20, %21, %22, %23, %24, %25, %26, %27, %28, %29, %30, %31, "
    "%32, %33, %34, %35, %36, %37, %38, %39, %40, %41, %42, %43, %44, %45, %46, %47, "
    "%48, %49, %50, %51, %52, %53, %54, %55, %56, %57, %58, %59, %60, %61, %62, %63, "
    "%64, %65, %66, %67, %68, %69, %70, %71, %72, %73, %74, %75, %76, %77, %78, %79, "
    "%80, %81, %82, %83, %84, %85, %86, %87, %88, %89, %90, %91, %92, %93, %94, %95}, "
    "dA, dB, p, 1, 1, 0, 1;\n}\n"
    : "+f"(d[0]), "+f"(d[1]), "+f"(d[2]), "+f"(d[3]), "+f"(d[4]), "+f"(d[5]), "+f"(d[6]), "+f"(d[7]),
      "+f"(d[8]), "+f"(d[9]), "+f"(d[10]), "+f"(d[11]), "+f"(d[12]), "+f"(d[13]), "+f"(d[14]), "+f"(d[15]),
      "+f"(d[16]), "+f"(d[17]), "+f"(d[18]), "+f"(d[19]), "+f"(d[20]), "+f"(d[21]), "+f"(d[22]), "+f"(d[23]),
      "+f"(d[24]), "+f"(d[25]), "+f"(d[26]), "+f"(d[27]), "+f"(d[28]), "+f"(d[29]), "+f"(d[30]), "+f"(d[31]),
      "+f"(d[32]), "+f"(d[33]), "+f"(d[34]), "+f"(d[35]), "+f"(d[36]), "+f"(d[37]), "+f"(d[38]), "+f"(d[39]),
      "+f"(d[40]), "+f"(d[41]), "+f"(d[42]), "+f"(d[43]), "+f"(d[44]), "+f"(d[45]), "+f"(d[46]), "+f"(d[47]),
      "+f"(d[48]), "+f"(d[49]), "+f"(d[50]), "+f"(d[51]), "+f"(d[52]), "+f"(d[53]), "+f"(d[54]), "+f"(d[55]),
      "+f"(d[56]), "+f"(d[57]), "+f"(d[58]), "+f"(d[59]), "+f"(d[60]), "+f"(d[61]), "+f"(d[62]), "+f"(d[63]),
      "+f"(d[64]), "+f"(d[65]), "+f"(d[66]), "+f"(d[67]), "+f"(d[68]), "+f"(d[69]), "+f"(d[70]), "+f"(d[71]),
      "+f"(d[72]), "+f"(d[73]), "+f"(d[74]), "+f"(d[75]), "+f"(d[76]), "+f"(d[77]), "+f"(d[78]), "+f"(d[79]),
      "+f"(d[80]), "+f"(d[81]), "+f"(d[82]), "+f"(d[83]), "+f"(d[84]), "+f"(d[85]), "+f"(d[86]), "+f"(d[87]),
      "+f"(d[88]), "+f"(d[89]), "+f"(d[90]), "+f"(d[91]), "+f"(d[92]), "+f"(d[93]), "+f"(d[94]), "+f"(d[95])
    : "r"(da), "r"(db), "r"(scale_d), "n"(HA), "n"(HB));
}
template <uint32_t HA = 0x40000040u, uint32_t HB = 0x40000040u>
__device__ __forceinline__ void wg_ss128t(float* d, uint32_t da, uint32_t db, int scale_d) {
  asm volatile("{\n.reg .pred p;\n.reg .b64 dA, dB;\nmov.b64 dA, {%64, %67};\nmov.b64 dB, {%65, %68};\nsetp.ne.b32 p, %66, 0;\n"
    "wgmma.mma_async.sync.aligned.m64n128k16.f32.bf16.bf16 "
    "{%0, %1, %2, %3, %4, %5, %6, %7, %8, %9, %10, %11, %12, %13, %14, %15, "
    "%16, %17, %18, %19, %20, %21, %22, %23, %24, %25, %26, %27, %28, %29, %30, %31, "
    "%32, %33, %34, %35, %36, %37, %38, %39, %40, %41, %42, %43, %44, %45, %46, %47, "
    "%48, %49, %50, %51, %52, %53, %54, %55, %56, %57, %58, %59, %60, %61, %62, %63}, "
    "dA, dB, p, 1, 1, 0, 1;\n}\n"
    : "+f"(d[0]), "+f"(d[1]), "+f"(d[2]), "+f"(d[3]), "+f"(d[4]), "+f"(d[5]), "+f"(d[6]), "+f"(d[7]),
      "+f"(d[8]), "+f"(d[9]), "+f"(d[10]), "+f"(d[11]), "+f"(d[12]), "+f"(d[13]), "+f"(d[14]), "+f"(d[15]),
      "+f"(d[16]), "+f"(d[17]), "+f"(d[18]), "+f"(d[19]), "+f"(d[20]), "+f"(d[21]), "+f"(d[22]), "+f"(d[23]),
      "+f"(d[24]), "+f"(d[25]), "+f"(d[26]), "+f"(d[27]), "+f"(d[28]), "+f"(d[29]), "+f"(d[30]), "+f"(d[31]),
      "+f"(d[32]), "+f"(d[33]), "+f"(d[34]), "+f"(d[35]), "+f"(d[36]), "+f"(d[37]), "+f"(d[38]), "+f"(d[39]),
      "+f"(d[40]), "+f"(d[41]), "+f"(d[42]), "+f"(d[43]), "+f"(d[44]), "+f"(d[45]), "+f"(d[46]), "+f"(d[47]),
      "+f"(d[48]), "+f"(d[49]), "+f"(d[50]), "+f"(d[51]), "+f"(d[52]), "+f"(d[53]), "+f"(d[54]), "+f"(d[55]),
      "+f"(d[56]), "+f"(d[57]), "+f"(d[58]), "+f"(d[59]), "+f"(d[60]), "+f"(d[61]), "+f"(d[62]), "+f"(d[63])
    : "r"(da), "r"(db), "r"(scale_d), "n"(HA), "n"(HB));
}
template <uint32_t HB = 0x40000040u>
__device__ __forceinline__ void wg_rs64(float* d, uint32_t a0, uint32_t a1, uint32_t a2, uint32_t a3, uint32_t db, int scale_d) {
  asm volatile("{\n.reg .pred p;\n.reg .b64 dB;\nmov.b64 dB, {%36, %38};\nsetp.ne.b32 p, %37, 0;\n"
    "wgmma.mma_async.sync.aligned.m64n64k16.f32.bf16.bf16 "
    "{%0, %1, %2, %3, %4, %5, %6, %7, %8, %9, %10, %11, %12, %13, %14, %15, "
    "%16, %17, %18, %19, %20, %21, %22, %23, %24, %25, %26, %27, %28, %29, %30, %31}, "
    "{%32, %33, %34, %35}, dB, p, 1, 1, 0;\n}\n"
    : "+f"(d[0]), "+f"(d[1]), "+f"(d[2]), "+f"(d[3]), "+f"(d[4]), "+f"(d[5]), "+f"(d[6]), "+f"(d[7]),
      "+f"(d[8]), "+f"(d[9]), "+f"(d[10]), "+f"(d[11]), "+f"(d[12]), "+f"(d[13]), "+f"(d[14]), "+f"(d[15]),
      "+f"(d[16]), "+f"(d[17]), "+f"(d[18]), "+f"(d[19]), "+f"(d[20]), "+f"(d[21]), "+f"(d[22]), "+f"(d[23]),
      "+f"(d[24]), "+f"(d[25]), "+f"(d[26]), "+f"(d[27]), "+f"(d[28]), "+f"(d[29]), "+f"(d[30]), "+f"(d[31])
    : "r"(a0), "r"(a1), "r"(a2), "r"(a3), "r"(db), "r"(scale_d), "n"(HB));
}
template <uint32_t HB = 0x40000040u>
__device__ __forceinline__ void wg_rs64_z(float* d, uint32_t a0, uint32_t a1, uint32_t a2, uint32_t a3, uint32_t db) {
  asm volatile("{\n.reg .pred p;\n.reg .b64 dB;\nmov.b64 dB, {%36, %37};\nsetp.ne.b32 p, 0, 0;\n"
    "wgmma.mma_async.sync.aligned.m64n64k16.f32.bf16.bf16 "
    "{%0, %1, %2, %3, %4, %5, %6, %7, %8, %9, %10, %11, %12, %13, %14, %15, "
    "%16, %17, %18, %19, %20, %21, %22, %23, %24, %25, %26, %27, %28, %29, %30, %31}, "
    "{%32, %33, %34, %35}, dB, p, 1, 1, 0;\n}\n"
    : "=f"(d[0]), "=f"(d[1]), "=f"(d[2]), "=f"(d[3]), "=f"(d[4]), "=f"(d[5]), "=f"(d[6]), "=f"(d[7]),
      "=f"(d[8]), "=f"(d[9]), "=f"(d[10]), "=f"(d[11]), "=f"(d[12]), "=f"(d[13]), "=f"(d[14]), "=f"(d[15]),
      "=f"(d[16]), "=f"(d[17]), "=f"(d[18]), "=f"(d[19]), "=f"(d[20]), "=f"(d[21]), "=f"(d[22]), "=f"(d[23]),
      "=f"(d[24]), "=f"(d[25]), "=f"(d[26]), "=f"(d[27]), "=f"(d[28]), "=f"(d[29]), "=f"(d[30]), "=f"(d[31])
    : "r"(a0), "r"(a1), "r"(a2), "r"(a3), "r"(db), "n"(HB));
}
template <uint32_t HB = 0x40000040u>
__device__ __forceinline__ void wg_rs32(float* d, uint32_t a0, uint32_t a1, uint32_t a2, uint32_t a3, uint32_t db, int scale_d) {
  asm volatile("{\n.reg .pred p;\n.reg .b64 dB;\nmov.b64 dB, {%20, %22};\nsetp.ne.b32 p, %21, 0;\n"
    "wgmma.mma_async.sync.aligned.m64n32k16.f32.bf16.bf16 "
    "{%0, %1, %2, %3, %4, %5, %6, %7, %8, %9, %10, %11, %12, %13, %14, %15}, "
    "{%16, %17, %18, %19}, dB, p, 1, 1, 0;\n}\n"
    : "+f"(d[0]), "+f"(d[1]), "+f"(d[2]), "+f"(d[3]), "+f"(d[4]), "+f"(d[5]), "+f"(d[6]), "+f"(d[7]),
      "+f"(d[8]), "+f"(d[9]), "+f"(d[10]), "+f"(d[11]), "+f"(d[12]), "+f"(d[13]), "+f"(d[14]), "+f"(d[15])
    : "r"(a0), "r"(a1), "r"(a2), "r"(a3), "r"(db), "r"(scale_d), "n"(HB));
}
template <uint32_t HB = 0x40000040u>
__device__ __forceinline__ void wg_rs32_z(float* d, uint32_t a0, uint32_t a1, uint32_t a2, uint32_t a3, uint32_t db) {
  asm volatile("{\n.reg .pred p;\n.reg .b64 dB;\nmov.b64 dB, {%20, %21};\nsetp.ne.b32 p, 0, 0;\n"
    "wgmma.mma_async.sync.aligned.m64n32k16.f32.bf16.bf16 "
    "{%0, %1, %2, %3, %4, %5, %6, %7, %8, %9, %10, %11, %12, %13, %14, %15}, "
    "{%16, %17, %18, %19}, dB, p, 1, 1, 0;\n}\n"
    : "=f"(d[0]), "=f"(d[1]), "=f"(d[2]), "=f"(d[3]), "=f"(d[4]), "=f"(d[5]), "=f"(d[6]), "=f"(d[7]),
      "=f"(d[8]), "=f"(d[9]), "=f"(d[10]), "=f"(d[11]), "=f"(d[12]), "=f"(d[13]), "=f"(d[14]), "=f"(d[15])
    : "r"(a0), "r"(a1), "r"(a2), "r"(a3), "r"(db), "n"(HB));
}
template <uint32_t HB = 0x40000040u>
__device__ __forceinline__ void wg_rs40t(float* d, uint32_t a0, uint32_t a1, uint32_t a2, uint32_t a3, uint32_t db, int scale_d) {
  asm volatile("{\n.reg .pred p;\n.reg .b64 dB;\nmov.b64 dB, {%24, %26};\nsetp.ne.b32 p, %25, 0;\n"
    "wgmma.mma_async.sync.aligned.m64n40k16.f32.bf16.bf16 "
    "{%0, %1, %2, %3, %4, %5, %6, %7, %8, %9, %10, %11, %12, %13, %14, %15, "
    "%16, %17, %18, %19}, "
    "{%20, %21, %22, %23}, dB, p, 1, 1, 1;\n}\n"
    : "+f"(d[0]), "+f"(d[1]), "+f"(d[2]), "+f"(d[3]), "+f"(d[4]), "+f"(d[5]), "+f"(d[6]), "+f"(d[7]),
      "+f"(d[8]), "+f"(d[9]), "+f"(d[10]), "+f"(d[11]), "+f"(d[12]), "+f"(d[13]), "+f"(d[14]), "+f"(d[15]),
      "+f"(d[16]), "+f"(d[17]), "+f"(d[18]), "+f"(d[19])
    : "r"(a0), "r"(a1), "r"(a2), "r"(a3), "r"(db), "r"(scale_d), "n"(HB));
}
template <uint32_t HB = 0x40000040u>
__device__ __forceinline__ void wg_rs40t_z(float* d, uint32_t a0, uint32_t a1, uint32_t a2, uint32_t a3, uint32_t db) {
  asm volatile("{\n.reg .pred p;\n.reg .b64 dB;\nmov.b64 dB, {%24, %25};\nsetp.ne.b32 p, 0, 0;\n"
    "wgmma.mma_async.sync.aligned.m64n40k16.f32.bf16.bf16 "
    "{%0, %1, %2, %3, %4, %5, %6, %7, %8, %9, %10, %11, %12, %13, %14, %15, "
    "%16, %17, %18, %19}, "
    "{%20, %21, %22, %23}, dB, p, 1, 1, 1;\n}\n"
    : "=f"(d[0]), "=f"(d[1]), "=f"(d[2]), "=f"(d[3]), "=f"(d[4]), "=f"(d[5]), "=f"(d[6]), "=f"(d[7]),
      "=f"(d[8]), "=f"(d[9]), "=f"(d[10]), "=f"(d[11]), "=f"(d[12]), "=f"(d[13]), "=f"(d[14]), "=f"(d[15]),
      "=f"(d[16]), "=f"(d[17]), "=f"(d[18]), "=f"(d[19])
    : "r"(a0), "r"(a1), "r"(a2), "r"(a3), "r"(db), "n"(HB));
}

constexpr uint32_t SOFF = 1024;
constexpr int STG = 57344, SL_W = 32768, SL_HD = 12288, SL_F = 3 * STG, AT_ST = 131072;
constexpr int OFF_ONES = 4 * STG;
constexpr int OFF_PATCH = OFF_ONES + 1024;
constexpr int OFF_CS = OFF_PATCH + 768;
constexpr int OFF_BAR = OFF_CS + 768;
constexpr int OFF_MISC = OFF_BAR + 384;
constexpr int SMEM_BYTES = OFF_MISC + 128;
enum { B_FULL = 0, B_EMPTY = 3, B_HALO = 6, B_CS = 9, B_KVREADY, B_QDONE = B_KVREADY + 2, B_QREADY, B_OST, B_ADONE = B_OST + 2,
       B_QFREE, B_WS, B_CHAIN, B_WFULL = B_CHAIN + 2, B_WEMPTY = B_WFULL + 4, B_GU = B_WEMPTY + 4, B_GUFREE = B_GU + 2, B_RES, B_DN,
       B_HX, B_RST, B_PUSHED, B_WGO, B_COUNT = B_WGO + 2 };
static_assert(B_COUNT <= 48, "barrier area");
__host__ __device__ constexpr int bar_count(int i) {
  return i >= B_EMPTY && i < B_HALO ? 17 : i == B_CS ? 4 : i == B_QFREE ? 2
       : i == B_KVREADY || i == B_KVREADY + 1 || i == B_QREADY || i == B_ADONE ? 8 : i == B_OST + 1 ? 32
       : i == B_QDONE || i == B_OST || i == B_GUFREE || (i >= B_WEMPTY && i < B_GU) ? 16 : i == B_RST ? 6 : 1;
}
enum { M_KEY = 0, M_MEAN, M_INV, M_WSUM, M_TAG, M_SEL0, M_XQ = 8, M_CNT = 12, M_KEYS = 16 };
constexpr int FFN_PIECE = 14336;
constexpr int T_XS = 163840, T_HP = T_XS + 1024;
constexpr int HELP_GR = 8;
constexpr float LSUM_MIN = 5.421010862427522e-20f, LSUM_MAX = 1.8446744073709552e19f;
constexpr float SM_C = 0.17677669529663687f * 1.4426950408889634f;
constexpr uint32_t VSTEP = 64u - (64u << 16);
#define FFN_POL policy_evict_first()
#define D_SPLIT 0
#define D_LATE 0
#define PF_MODE 0
#define WG_FLIP 384
#define GU_PACE 1500
#define DELAY_P 600
#define DELAY_S 300
#define DELAY_Y 700
__host__ __device__ constexpr int wo_off(int st) { return st < 3 ? 65536 + st * 32768 : 32768; }

struct Params {
  CUtensorMap mapA[2], mapW, mapWo, mapRes[2], mapXst[2], mapG, mapU, mapD;
  const bf16 *wqkv, *wo, *w_r, *w_g, *w_u, *w_d;
  bf16* out;
  int helper_first;
};

template <int N> __device__ __forceinline__ void exp_pack(const float* s, uint32_t* p) {
#pragma unroll
  for (int b = 0; b < N; b++) {
    p[2 * b] = pack_bf16(ex2(s[4 * b]), ex2(s[4 * b + 1]));
    p[2 * b + 1] = pack_bf16(ex2(s[4 * b + 2]), ex2(s[4 * b + 3]));
  }
}
template <int KIND> __device__ __forceinline__ void edge16(const float* sd, const float* st, uint32_t* pd, uint32_t* pt, int dl, uint32_t mt) {
  if (KIND == 0) { exp_pack<2>(sd, pd); pt[0] = pt[1] = pt[2] = pt[3] = 0; }
  else if (KIND == 1) { exp_pack<2>(st, pt); pd[0] = pd[1] = pd[2] = pd[3] = 0; }
  else {
    const uint32_t a = pack_bf16(ex2(dl >= 0 ? sd[0] : st[0]), ex2(dl >= 1 ? sd[1] : st[1]));
    const uint32_t c = pack_bf16(ex2(dl >= 0 ? sd[6] : st[6]), ex2(dl >= 1 ? sd[7] : st[7]));
    pd[0] = a & ~mt; pt[0] = a & mt; pd[3] = c & ~mt; pt[3] = c & mt;
    pd[1] = pack_bf16(ex2(sd[2]), ex2(sd[3])); pt[1] = 0;
    pt[2] = pack_bf16(ex2(st[4]), ex2(st[5])); pd[2] = 0;
  }
}
__device__ __forceinline__ void mix_exp(const float* sm, const float* sd, const float* st, uint32_t* p, int rel, int dl, uint32_t mt) {
  uint32_t *pd = p + 8, *pt = p + 16;
  if (rel > 1) { edge16<0>(sd, st, pd, pt, dl, mt); edge16<0>(sd + 8, st + 8, pd + 4, pt + 4, dl, mt); }
  else if (rel == 1) { edge16<0>(sd, st, pd, pt, dl, mt); edge16<2>(sd + 8, st + 8, pd + 4, pt + 4, dl, mt); }
  else if (rel == 0) { edge16<2>(sd, st, pd, pt, dl, mt); edge16<1>(sd + 8, st + 8, pd + 4, pt + 4, dl, mt); }
  else { edge16<1>(sd, st, pd, pt, dl, mt); edge16<1>(sd + 8, st + 8, pd + 4, pt + 4, dl, mt); }
  exp_pack<4>(sm, p);
}
__device__ __forceinline__ void qk64(float* s, const uint32_t* qf, uint32_t kd) {
  wg_rs64_z<H64>(s, qf[0], qf[1], qf[2], qf[3], kd);
  wg_rs64<H64>(s, qf[4], qf[5], qf[6], qf[7], kd + 2, 1);
}
__device__ __forceinline__ void qk32x3(float* a, float* b, float* c, const uint32_t* qf, uint32_t ka, uint32_t kb, uint32_t kc) {
  wg_rs32_z<H64>(a, qf[0], qf[1], qf[2], qf[3], ka); wg_rs32_z<H64>(b, qf[0], qf[1], qf[2], qf[3], kb); wg_rs32_z<H64>(c, qf[0], qf[1], qf[2], qf[3], kc);
  wg_rs32<H64>(a, qf[4], qf[5], qf[6], qf[7], ka + 2, 1); wg_rs32<H64>(b, qf[4], qf[5], qf[6], qf[7], kb + 2, 1); wg_rs32<H64>(c, qf[4], qf[5], qf[6], qf[7], kc + 2, 1);
}
__device__ __forceinline__ void pv32(float* o, const uint32_t* p, uint32_t vd) {
  wg_rs40t<H64>(o, p[0], p[1], p[2], p[3], vd, 1);
  wg_rs40t<H64>(o, p[4], p[5], p[6], p[7], vd + VSTEP, 1);
}

__device__ __forceinline__ int fresh_tid() { int r; asm volatile("mov.u32 %0, %%tid.x;" : "=r"(r)); return r ^ WG_FLIP; }
__device__ __forceinline__ int fresh_bid() { int r; asm volatile("mov.u32 %0, %%ctaid.x;" : "=r"(r)); return r; }
#define PHASE_IDS                                                                                                              \
  const uint32_t sbase = smem_u32(smem);                                                                                       \
  const int tid = fresh_tid(), bid = fresh_bid();                                                                              \
  const int warp = __shfl_sync(0xffffffffu, tid >> 5, 0), lane = tid & 31;                                                     \
  const int rank = bid & 1, cl = bid >> 1, rb = bid & 7, hp = bid >> 3;                  \
  const int mb = 2 * rb + (hp >> 3), nb = hp & 7;                                            \
  const int wg = warp >> 2, wi = warp & 3, g = lane >> 2, q = lane & 3;                                                        \
  const int mi = lane >> 3, srow = wi * 16 + (mi & 1) * 8 + (lane & 7);      \
  auto bar = [&](int i) { return sbase + OFF_BAR + 8 * i; };                                                                   \
  volatile uint32_t* s_misc = (volatile uint32_t*)(smem + OFF_MISC);                                                           \
  auto load_w = [&](int s, int kt) {                           \
    tma_load3_mc(sbase + s * STG + SL_W + rank * SL_HD, &P.mapW, hp * 64, kt * 64 + rank * 32, 0, bar(B_FULL + s));            \
  };                                                                                                                           \
  auto load_a = [&](int s, int kt, int layer) { mbar_expect_tx(bar(B_FULL + s), STG); tma_load2(sbase + s * STG, &P.mapA[layer], kt * 64, rb * 256, bar(B_FULL + s)); }; \
  auto load_stage = [&](int k) {        \
    const int st = k & 3;                                                                                                      \
    mbar_expect_tx(bar(B_WFULL + st), 32768);                                                                                  \
    bulk_load(sbase + wo_off(st), g_o + (size_t)(mb * 16 + k) * 16384, 16384, bar(B_WFULL + st));                              \
    tma_load3_mc(sbase + wo_off(st) + 16384 + rank * 8192, &P.mapWo, nb * 128 + rank * 64, (k >> 3) * 32, (k & 7) * 2, bar(B_WFULL + st)); \
  };                                                                                                                           \
  (void)load_stage; (void)cl; (void)mb; (void)nb; (void)wg; (void)g; (void)q; (void)srow; (void)s_misc; (void)load_w; (void)load_a;

__global__ void __launch_bounds__(512, 1) mega_kernel(const __grid_constant__ Params P) {
  extern __shared__ __align__(1024) uint8_t smem[];
  if ((int)blockIdx.x < P.helper_first) {
    PHASE_IDS
    if (warp == 0) {
      if (lane == 0) {
        prefetch_tmap(&P.mapA[0]); prefetch_tmap(&P.mapW);
#pragma unroll
        for (int i = 0; i < 3; i++) mbar_init(bar(B_FULL + i), 1);
        asm volatile("fence.mbarrier_init.release.cluster;" ::: "memory");
      }
      __syncwarp();
      load_a(0, 0, 0);
    } else if (tid == 32) {
#pragma unroll
      for (int i = 3; i < B_COUNT; i++) mbar_init(bar(i), bar_count(i));
      asm volatile("fence.mbarrier_init.release.cluster;" ::: "memory");
    } else if (warp == 8) {
      ((uint4*)(smem + OFF_ONES))[lane] = make_uint4(0x3F803F80u, 0x3F803F80u, 0x3F803F80u, 0x3F803F80u);
      ((uint4*)(smem + OFF_ONES))[lane + 32] = make_uint4(0x3F803F80u, 0x3F803F80u, 0x3F803F80u, 0x3F803F80u);
    }
    __syncwarp();
    cluster_arrive(); cluster_wait();
    if (warp == 0) {
#pragma unroll 1
      for (int i = 0; i < 3; i++) { load_w(i, i); if (i) load_a(i, i, 0); }
      PROFL(0, 1);
    } else if (warp == 1) {
      if (lane < 16) g_rowab[0][rb * 256 + hp * 16 + lane] = make_uint4(0, 0, 0, 0);
      if (lane == 0) { s_misc[M_TAG] = ld_relaxed(&g_epoch) + 1; s_misc[M_SEL0] = 0xFFFFFFFFu; s_misc[M_CNT] = 0; }
    } else if (warp == 2) {
      const int f = lane >> 1;
      Flag* fl = f < 3 ? &g_kvflag[rb >> 1][hp][f] : f < 5 ? &g_oflag[rb][f & 1][hp] : &g_xflag[mb][nb];
      if (f < 6 && (f >= 3 || (rank == 1 && rb < 7))) ((uint4*)fl)[lane & 1] = make_uint4(0, 0, 0, 0);
    } else if (tid == 96) {
      if ((sbase & 0x3FFFF) != SOFF) __trap();
#pragma unroll 1
      for (int i = 1; i < 11; i++) prefetch_tmap(&P.mapA[0] + i);
    }
    __syncwarp();
    if (wg < 2) named_bar(7, 256);
  } else {
    const uint32_t sbase = smem_u32(smem);
    const int tid = threadIdx.x, warp = __shfl_sync(0xffffffffu, tid >> 5, 0), lane = tid & 31;
    const int hid = blockIdx.x - P.helper_first;
    constexpr int GR = HELP_GR, NG = 36 / GR, GB = GR * 6144, NGRP = 256 / GR;
    const uint32_t hfull = sbase + NG * GB, hempty = hfull + 8 * NG;
    if (tid == 0) {
      for (int i = 0; i < NG; i++) { mbar_init(hfull + 8 * i, 1); mbar_init(hempty + 8 * i, 12); }
      asm volatile("fence.mbarrier_init.release.cluster;" ::: "memory");
    }
    __syncthreads();
    const uint8_t* wsrc = (const uint8_t*)P.wqkv + (size_t)hid * 256 * 6144;
    if (warp == 12) {
#pragma unroll 1
      for (int gI = 0; gI < NGRP; gI++) {
        const int sl = gI % NG;
        if (gI >= NG) mbar_wait(hempty + 8 * sl, ((gI / NG) & 1) ^ 1);
        mbar_expect_tx(hfull + 8 * sl, GB);
        bulk_load(sbase + sl * GB, wsrc + (size_t)gI * GB, GB, hfull + 8 * sl);
      }
    } else if (warp < 12) {
      float cs8[8] = {0, 0, 0, 0, 0, 0, 0, 0};
#pragma unroll 1
      for (int gI = 0; gI < NGRP; gI++) {
        const int sl = gI % NG;
        mbar_wait(hfull + 8 * sl, (gI / NG) & 1);
#pragma unroll
        for (int i = 0; i < GR; i++) {
          const uint4 v = *(const uint4*)(smem + sl * GB + i * 6144 + tid * 16);
          cs8[0] += bf_lo(v.x); cs8[1] += bf_hi(v.x); cs8[2] += bf_lo(v.y); cs8[3] += bf_hi(v.y);
          cs8[4] += bf_lo(v.z); cs8[5] += bf_hi(v.z); cs8[6] += bf_lo(v.w); cs8[7] += bf_hi(v.w);
        }
        __syncwarp();
        if (lane == 0) mbar_arrive(hempty + 8 * sl);
      }
      uint4* dst = (uint4*)&g_cspart[hid][tid * 8];
      st_relaxed4(dst, make_uint4(enc(cs8[0]), enc(cs8[1]), enc(cs8[2]), enc(cs8[3])));
      st_relaxed4(dst + 1, make_uint4(enc(cs8[4]), enc(cs8[5]), enc(cs8[6]), enc(cs8[7])));
    }
    return;
  }

#pragma unroll 1
  for (unsigned pass_v = 0;;) {
    const unsigned pass = __shfl_sync(0xffffffffu, pass_v, 0);
    if (__shfl_sync(0xffffffffu, fresh_tid() >> 8, 0)) {
      if (pass > 0) {
        const unsigned layer = pass - 1;
        uint32_t xr[32];
        {
          PHASE_IDS
          if (warp == 8) {
            poll_flag(&g_oflag[rb][0][lane & 15].v[layer], s_misc[M_TAG]);
            __syncwarp();
            fence_async_global();
            mbar_wait(bar(B_ADONE), layer);
            PROF(15);
#pragma unroll 1
            for (int k = 0; k < 3; k++) {
              if (k == 2) mbar_wait(bar(B_OST + 1), layer);
              load_stage(k);
            }
            mbar_arrive_e(bar(B_WGO));
          }
          float acc[64];
#pragma unroll
          for (int i = 0; i < 64; i++) acc[i] = 0.f;
          const uint32_t da0 = dlo(SOFF, 16) + (wg - 2) * 256;
          constexpr uint32_t db0 = dlo(SOFF + 16384, 8192);
#pragma unroll 1
          for (int k4 = 0; k4 < 4; k4++) {
#pragma unroll
            for (int st = 0; st < 4; st++) {
              mbar_wait(bar(B_WFULL + st), k4 & 1);
              wg_fence();
#pragma unroll
              for (int kk = 0; kk < 4; kk++)
                wg_ss128t<H64, H128>(acc, da0 + (wo_off(st) >> 4) + (kk >> 1) * 512 + (kk & 1) * 2, db0 + (wo_off(st) >> 4) + kk * 128, 1);
              wg_commit();
              if (st == 0 && k4 == 0 && warp == 9) PROF(10);
              if (st & 1) STEPT(24 + k4 * 2 + (st >> 1));
              wg_wait<1>();
              if (lane < 2 && (st == 0 ? k4 > 0 : (st < 3 || k4 < 3))) mbar_arrive_cluster(bar(B_WEMPTY + ((st + 3) & 3)), lane);
            }
          }
          mbar_wait(bar(B_RES), layer);
          const uint32_t zoff = (wg - 2) * 16384;
          const int prow = (int)s_misc[M_SEL0] - (mb * 128 + (wg - 2) * 64);
          if (prow >> 4 == wi) {
            if (lane < 16) *(uint4*)(smem + zoff + (lane >> 3) * 8192 + prow * 128 + (((lane & 7) ^ (prow & 7)) << 4)) = poll4(&g_x2row[(nb * 16 + lane) * 2]);
            __syncwarp();
          }
#pragma unroll
          for (int j = 0; j < 8; j++)
            ldsm_x4(sbase + zoff + srow * 128 + (j >> 2) * 8192 + ((((2 * j + (mi >> 1)) & 7) ^ (srow & 7)) << 4), xr[4 * j], xr[4 * j + 1], xr[4 * j + 2], xr[4 * j + 3]);
          mbar_wait(bar(B_RST), layer);
          wg_wait<0>();
          fence_regs<64>(acc);
          if (warp == 9) PROF(11);
#pragma unroll
          for (int j = 0; j < 32; j++) xr[j] = hadd_bf2(xr[j], pack_bf16(acc[2 * j], acc[2 * j + 1]));
        }
        PHASE_IDS
        const uint32_t tag = s_misc[M_TAG];
        const int grow = mb * 128 + (warp - 8) * 16 + g;
        {
          float d[6][4];
#pragma unroll
          for (int i = 0; i < 6; i++) d[i][0] = d[i][1] = d[i][2] = d[i][3] = 0.f;
          const uint4* tab = (const uint4*)(smem + OFF_PATCH + (g == 1 ? q * 64 : (g == 0 ? 256 : 320)));
#pragma unroll
          for (int j2 = 0; j2 < 4; j2++) {
            const uint4 w = tab[j2];
#pragma unroll
            for (int jj = 0; jj < 2; jj++) {
              const uint32_t* a = &xr[8 * j2 + 4 * jj];
              mma_16816(d[jj], a[0], a[1], a[2], a[3], jj ? w.z : w.x, jj ? w.w : w.y);
              mma_16816(d[2 + jj], a[0], a[1], a[2], a[3], a[0], a[2]);
              mma_16816(d[4 + jj], a[0], a[1], a[2], a[3], a[1], a[3]);
            }
          }
          const float sq0 = __shfl_sync(0xffffffffu, (g & 1) ? d[2][1] + d[3][1] : d[2][0] + d[3][0], g * 4 + (g >> 1));
          const float sq1 = __shfl_sync(0xffffffffu, (g & 1) ? d[4][3] + d[5][3] : d[4][2] + d[5][2], g * 4 + (g >> 1));
          uint4* dst = &g_part[layer][nb * SEQ + grow];
          if (q == 0) {
            st_relaxed4(dst, make_uint4(__float_as_uint(d[0][0] + d[1][0]), __float_as_uint(sq0), __float_as_uint(d[0][1] + d[1][1]), tag));
            st_relaxed4(dst + 8, make_uint4(__float_as_uint(d[0][2] + d[1][2]), __float_as_uint(sq1), __float_as_uint(d[0][3] + d[1][3]), tag));
          }
        }
        if (warp == 9) PROF(12);
        if (D_LATE) asm volatile("bar.arrive 11, 288;" ::: "memory");
        spin_cycles(DELAY_P);
        {
          const uint4* src = &g_part[layer][2 * q * SEQ + grow];
          uint4 pp[4];
          uint32_t spins = 0;
#pragma unroll 1
          do {
            pp[0] = ld_relaxed4(src); pp[1] = ld_relaxed4(src + SEQ); pp[2] = ld_relaxed4(src + 8); pp[3] = ld_relaxed4(src + SEQ + 8);
          } while (!__all_sync(0xffffffffu, pp[0].w == tag && pp[1].w == tag && pp[2].w == tag && pp[3].w == tag) && ++spins < SPIN_LIMIT);
          if (warp == 9) PROF(13);
          const int rr = q >> 1;
          float s3[3];
#pragma unroll
          for (int c = 0; c < 3; c++) {
            const float lo = __uint_as_float(c == 0 ? pp[0].x : c == 1 ? pp[0].y : pp[0].z) + __uint_as_float(c == 0 ? pp[1].x : c == 1 ? pp[1].y : pp[1].z);
            const float hi = __uint_as_float(c == 0 ? pp[2].x : c == 1 ? pp[2].y : pp[2].z) + __uint_as_float(c == 0 ? pp[3].x : c == 1 ? pp[3].y : pp[3].z);
            s3[c] = (rr ? hi : lo) + __shfl_xor_sync(0xffffffffu, rr ? lo : hi, 2);
            s3[c] += __shfl_xor_sync(0xffffffffu, s3[c], 1);
          }
          const float mu = s3[0] * (1.f / DM), var = fmaxf(fmaf(-mu, mu, s3[1] * (1.f / DM)), 0.f);
          const float mn = rbf(mu), iv = ln_inv(var);
          const uint32_t ky = router_key(rbf((s3[2] - mn * __uint_as_float(s_misc[M_WSUM])) * iv), grow + 8 * rr);
          const uint32_t wbest = __reduce_max_sync(0xffffffffu, ky);
          s_misc[M_KEYS + warp - 8] = wbest;
          named_bar(5, 256);
          if (__reduce_max_sync(0xffffffffu, s_misc[M_KEYS + (lane & 7)]) == wbest) {
            if (nb == 0 && ky == wbest && (q & 1) == 0) st_relaxed4(&g_slot[layer][mb * 8], make_uint4(ky, __float_as_uint(mn), __float_as_uint(iv), tag));
            const int r = ~wbest & 15;
            if ((r & 7) == g) {
#pragma unroll
              for (int j = 0; j < 4; j++) {
                const uint32_t* a = &xr[8 * j];
                st_relaxed4(&g_cand[layer][mb * 128 + nb * 16 + q * 4 + j],
                            r < 8 ? make_uint4(nosent(a[0]), nosent(a[2]), nosent(a[4]), nosent(a[6])) : make_uint4(nosent(a[1]), nosent(a[3]), nosent(a[5]), nosent(a[7])));
              }
            }
            __syncwarp();
          }
          if (warp == 9) PROF(14);
          asm volatile("bar.arrive 6, 288;" ::: "memory");
          if (layer == 0 && (q & 1) == 0 && warp - 8 == nb) {
            const float mu2 = mu + (mu - mn) * iv, inv2 = ln_inv(var * (1.f + iv) * (1.f + iv));
            st_relaxed4(&g_rowab[1][grow + 8 * rr], make_uint4(__float_as_uint(inv2), __float_as_uint(rbf(mu2) * inv2), tag, 0));
          }
          const float mo = __shfl_xor_sync(0xffffffffu, mn, 2), io = __shfl_xor_sync(0xffffffffu, iv, 2);
          const uint32_t m0 = pack_bf16(rr ? mo : mn, rr ? mo : mn), m1 = pack_bf16(rr ? mn : mo, rr ? mn : mo);
          const float i0 = rr ? io : iv, i1 = rr ? iv : io;
#pragma unroll
          for (int j = 0; j < 8; j++)
            stsm_x4(sbase + (wg - 2) * 16384 + srow * 128 + (j >> 2) * 8192 + ((((2 * j + (mi >> 1)) & 7) ^ (srow & 7)) << 4), add_ln_pair(xr[4 * j], m0, i0),
                    add_ln_pair(xr[4 * j + 1], m1, i1), add_ln_pair(xr[4 * j + 2], m0, i0), add_ln_pair(xr[4 * j + 3], m1, i1));
          fence_async_smem();
          if (warp == 15) {
            named_bar(8, 256);
#pragma unroll 1
            for (int j = 0; j < 4; j++) tma_store(&P.mapXst[layer], sbase + (j & 1) * 16384 + (j >> 1) * 8192, nb * 128 + (j >> 1) * 64, mb * 128 + (j & 1) * 64);
            bulk_commit();
            bulk_wait_all();
            set_flag(&g_xflag[mb][nb].v[layer], tag);
            PROF(17);
          } else {
            asm volatile("bar.arrive 8, 256;" ::: "memory");
          }
        }
        uint32_t wd[64];
        mbar_wait(bar(B_DN), layer);
#pragma unroll
        for (int j = 0; j < 16; j++) {
          const uint32_t row = sbase + wo_off(0) + ((warp - 8) * 2 + (j >> 3)) * 3584 + min(lane, 27) * 128;
          ldsm_x4_t(row + (((j & 7) ^ ((row >> 7) & 7)) << 4), wd[4 * j], wd[4 * j + 1], wd[4 * j + 2], wd[4 * j + 3]);
        }
        fence_regs_u<64>(wd);
        asm volatile("bar.arrive 10, 288;" ::: "memory");
        mbar_wait_cluster(bar(B_HX), layer);
        uint32_t hf[4];
        {
          const float2* hpart = (const float2*)(smem + T_HP) + min(lane, 27);
          float gs[2] = {0.f, 0.f}, us[2] = {0.f, 0.f};
#pragma unroll
          for (int j = 0; j < 16; j++) { const float2 v = hpart[j * 28]; gs[j & 1] += v.x; us[j & 1] += v.y; }
          const float gb = rbf(gs[0] + gs[1]), ub = rbf(us[0] + us[1]);
          const float hv = lane < 28 ? rbf(__fdividef(gb, 1.f + __expf(-gb))) * ub : 0.f;
          const uint32_t hp2 = pack_bf16(hv, __shfl_down_sync(0xffffffffu, hv, 1));
#pragma unroll
          for (int j = 0; j < 4; j++) hf[j] = __shfl_sync(0xffffffffu, hp2, 8 * j + 2 * q);
        }
        if (warp == 9) PROF(19);
        float y[4][4];
#pragma unroll
        for (int i = 0; i < 4; i++) y[i][0] = y[i][1] = y[i][2] = y[i][3] = 0.f;
#pragma unroll
        for (int j = 0; j < 8; j++) {
          const uint32_t a0 = g == j ? hf[0] : 0u, a1 = g == j ? hf[1] : 0u, a2 = g == j ? hf[2] : 0u, a3 = g == j ? hf[3] : 0u;
          mma_16816(y[0], a0, 0u, a1, 0u, wd[4 * j], wd[4 * j + 1]);
          mma_16816(y[1], a2, 0u, a3, 0u, wd[4 * j + 2], wd[4 * j + 3]);
          mma_16816(y[2], a0, 0u, a1, 0u, wd[32 + 4 * j], wd[33 + 4 * j]);
          mma_16816(y[3], a2, 0u, a3, 0u, wd[34 + 4 * j], wd[35 + 4 * j]);
        }
        {
          const float u0 = y[0][0] + y[1][0], u1 = y[0][1] + y[1][1], v0 = y[2][0] + y[3][0], v1 = y[2][1] + y[3][1];
          const int odd = lane & 1;
          const float t0 = __shfl_xor_sync(0xffffffffu, odd ? u0 : v0, 1), t1 = __shfl_xor_sync(0xffffffffu, odd ? u1 : v1, 1);
          st_relaxed4(&g_ypart[layer][bid * 256 + (warp - 8) * 32 + odd * 16 + (lane >> 1)],
                      odd ? make_uint4(f2u(t0), f2u(t1), f2u(v0), f2u(v1)) : make_uint4(f2u(u0), f2u(u1), f2u(t0), f2u(t1)));
        }
        if (warp == 9) PROF(20);
        asm volatile("bar.arrive 9, 512;" ::: "memory");
        if (pass == 2) { cluster_arrive(); cluster_wait(); return; }
      }
      const unsigned layer = pass;
      regs_inc<224>();
      float acc[2][96];
      {
        PHASE_IDS
        const uint32_t da0 = dlo(SOFF, 16) + (wg - 2) * 512;
        constexpr uint32_t db0 = dlo(SOFF + SL_W, 4096);
#pragma unroll
        for (int i = 0; i < 96; i++) acc[0][i] = acc[1][i] = 0.f;
        int s = 0, u = 0;
#pragma unroll 1
        for (int i = 0; i < 16; i++) {
          const uint32_t da = da0 + s * (STG >> 4), db = db0 + s * (STG >> 4);
          mbar_wait(bar(B_FULL + s), (u + (s ? layer : 0)) & 1);
          if (warp == 9) STEPT(i);
          wg_fence();
#pragma unroll
          for (int kk = 0; kk < 4; kk++) {
            wg_ss192t(acc[0], da + kk * 2, db + (kk >> 1) * (SL_HD >> 4) + (kk & 1) * 128, 1);
            wg_ss192t(acc[1], da + 1024 + kk * 2, db + (kk >> 1) * (SL_HD >> 4) + (kk & 1) * 128, 1);
          }
          wg_commit();
          wg_wait<1>();
          if (lane < 2 && i > 0 && i < 14) mbar_arrive_cluster(bar(B_EMPTY + (s == 0 ? 2 : s - 1)), lane);
          if (++s == 3) { s = 0; u++; }
        }
      }
      PHASE_IDS
      mbar_wait(bar(B_CS), layer);
      float pa[2][2], pb[2][2];
      {
        const uint32_t tag = s_misc[M_TAG];
        const uint4* src = &g_rowab[layer][rb * 256 + (wg - 2 + (lane >> 4) * 2) * 64 + wi * 16 + (lane & 15)];
        uint4 v;
        uint32_t spins = 0;
#pragma unroll 1
        do { v = ld_relaxed4(src); } while (!__all_sync(0xffffffffu, v.z == tag) && ++spins < SPIN_LIMIT);
#pragma unroll
        for (int j = 0; j < 4; j++) {
          pa[j >> 1][j & 1] = __uint_as_float(__shfl_sync(0xffffffffu, v.x, g + 8 * j));
          pb[j >> 1][j & 1] = __uint_as_float(__shfl_sync(0xffffffffu, v.y, g + 8 * j));
        }
      }
      const int prow = (int)s_misc[M_SEL0] - rb * 256;
      const bool patch = ((prow - (wg - 2) * 64 - wi * 16) & ~0x8F) == 0;
      const float* cs = (const float*)(smem + OFF_CS);
      auto finish = [&](int m, int b, float2 c, uint32_t* dst) {
        dst[0] = pack_bf16(acc[m][4 * b] * pa[m][0] - c.x * pb[m][0], acc[m][4 * b + 1] * pa[m][0] - c.y * pb[m][0]);
        dst[1] = pack_bf16(acc[m][4 * b + 2] * pa[m][1] - c.x * pb[m][1], acc[m][4 * b + 3] * pa[m][1] - c.y * pb[m][1]);
      };
      wg_wait<0>();
      fence_regs<96>(acc[0]); fence_regs<96>(acc[1]);
      if (warp != 9) STEPT(1);
      if (lane < 2) mbar_arrive_cluster(bar(B_QDONE), lane);
      if (warp == 9) PROF(2);
#pragma unroll
      for (int h = 0; h < 2; h++) {
        const uint32_t dst = sbase + (h * 8 + 2 + wg) * 8192 + srow * 64;
#pragma unroll
        for (int jj = 0; jj < 4; jj++) {
          const int b = 8 + (jj >> 1) * 8 + h * 4 + (jj & 1) * 2;
          const float2 c0 = *(const float2*)&cs[8 * b + 2 * q], c1 = *(const float2*)&cs[8 * b + 8 + 2 * q];
          uint32_t r[2][4];
#pragma unroll
          for (int m = 0; m < 2; m++) { finish(m, b, c0, r[m]); finish(m, b + 1, c1, r[m] + 2); }
          if (h == 0 && jj == 0) named_bar(5, 256);
#pragma unroll
          for (int m = 0; m < 2; m++)
            stsm_x4(dst + m * 16384 + (jj >> 1) * 4096 + ((((jj & 1) * 2 + (mi >> 1)) ^ ((srow >> 1) & 3)) << 4), r[m][0], r[m][1], r[m][2], r[m][3]);
        }
        if (patch) {
          __syncwarp();
          if (lane < 8)
            *(uint4*)(smem + (h * 8 + 4 + (prow >> 6)) * 8192 + g * 4096 + (prow & 63) * 64 + ((q ^ ((prow >> 1) & 3)) << 4)) =
                *(const uint4*)(smem + OFF_PATCH + 128 + g * 128 + h * 64 + q * 16);
        }
        fence_async_smem();
        __syncwarp();
        mbar_arrive_e(bar(B_KVREADY + h));
        if (warp != 9) STEPT(2 + h);
      }
#pragma unroll
      for (int j = 0; j < 4; j++) { pa[j >> 1][j & 1] *= SM_C; pb[j >> 1][j & 1] *= SM_C; }
#pragma unroll
      for (int jj = 0; jj < 4; jj++) {
        const float2 c0 = *(const float2*)&cs[16 * jj + 2 * q], c1 = *(const float2*)&cs[16 * jj + 8 + 2 * q];
#pragma unroll
        for (int m = 0; m < 2; m++) {
          uint32_t r[4];
          finish(m, 2 * jj, c0, r); finish(m, 2 * jj + 1, c1, r + 2);
          *(uint4*)(smem + AT_ST + ((jj >> 1) * 16 + warp - 8 + 8 * m) * 1024 + (jj & 1) * 512 + lane * 16) = make_uint4(r[0], r[1], r[2], r[3]);
        }
      }
      __syncwarp();
      if (patch) {
        *(uint32_t*)(smem + AT_ST + ((lane >> 4) * 16 + (prow >> 4)) * 1024 + (mi & 1) * 512 + ((prow & 7) * 4 + q) * 16 + ((g & 1) * 2 + ((prow >> 3) & 1)) * 4) =
            *(const uint32_t*)(smem + OFF_PATCH + lane * 4);
        __syncwarp();
      }
      if (warp == 9) PROF(3);
      mbar_arrive_e(bar(B_QREADY));
      regs_dec<128>();
    } else {
      if (pass > 0) {
        const unsigned layer = pass - 1;
        uint32_t gu[56];
        {
          PHASE_IDS
          const uint32_t tag = s_misc[M_TAG];
          mbar_wait(bar(B_GU + 1), layer);
#pragma unroll
          for (int j = 0; j < 14; j++)
            ldsm_x4_t(sbase + (mi & 1) * 2 * FFN_PIECE + (warp * 32 + (mi >> 1) * 8 + (lane & 7)) * 112 + (j >> 1) * 16 + (j & 1) * 1792,
                      gu[4 * j], gu[4 * j + 1], gu[4 * j + 2], gu[4 * j + 3]);
          fence_regs_u<56>(gu);
          if (lane < 2) mbar_arrive_cluster(bar(B_GUFREE), lane);
          __syncwarp();
          if (warp == 0) {
            mbar_wait(bar(B_GUFREE), layer);
            mbar_wait(bar(B_WGO), layer);
            fence_async_global();
#pragma unroll 1
            for (int k = 3; k < 16; k++) {
              if (k == 8) { mbar_wait(bar(B_WGO + 1), layer); fence_async_global(); mbar_expect_tx(bar(B_RES), 32768); }
              if (k >= 4) mbar_wait(bar(B_WEMPTY + (k & 3)), ((k >> 2) - 1 + ((k & 2) ? layer : 0)) & 1);
              load_stage(k);
              if (k >= 8 && k < 12) tma_load2(sbase + (k - 8) * 8192, &P.mapRes[layer], nb * 128 + (k & 1) * 64, mb * 128 + ((k >> 1) & 1) * 64, bar(B_RES));
            }
            mbar_wait(bar(B_WEMPTY + 1), 1);
            if (D_LATE) named_bar(11, 288);
            mbar_expect_tx(bar(B_DN), 4 * FFN_PIECE);
            tma_load3_h(sbase + wo_off(0), &P.mapD, 0, bid * 28, 0, bar(B_DN), FFN_POL);
            if (!D_SPLIT) tma_load3_h(sbase + wo_off(0) + 2 * FFN_PIECE, &P.mapD, 0, bid * 28, 8, bar(B_DN), FFN_POL);
            named_bar(6, 288);
            if (D_SPLIT) tma_load3_h(sbase + wo_off(0) + 2 * FFN_PIECE, &P.mapD, 0, bid * 28, 8, bar(B_DN), FFN_POL);
            if (DELAY_S > 0) spin_cycles(DELAY_S);
            uint4 c;
            uint32_t spins = 0;
#pragma unroll 1
            do { c = ld_relaxed4(&g_slot[layer][(lane & 15) * 8]); } while (!__all_sync(0xffffffffu, c.w == tag) && ++spins < SPIN_LIMIT);
            const uint32_t best = __reduce_max_sync(0xffffffffu, c.x);
            const int src = (SEQ - 1 - (int)(best & 0xFFFFu)) >> 7;
            const float sel_m = __uint_as_float(__shfl_sync(0xffffffffu, c.y, src)), sel_inv = __uint_as_float(__shfl_sync(0xffffffffu, c.z, src));
            PROF(16);
            const uint4* xsel = &g_cand[layer][src * 128];
            uint4 u0, u1;
            uint32_t u2;
            spins = 0;
#pragma unroll 1
            do {
              u0 = ld_relaxed4(xsel + rank * 64 + lane); u1 = ld_relaxed4(xsel + rank * 64 + 32 + lane);
              u2 = ld_relaxed((const uint32_t*)(xsel + (bid >> 4) * 16 + q * 4) + (bid & 15));
            } while (!__all_sync(0xffffffffu, valid4(u0) && valid4(u1) && u2 != SENT) && ++spins < SPIN_LIMIT);
            const uint32_t m2 = pack_bf16(sel_m, sel_m);
            uint4* xs = (uint4*)(smem + T_XS) + lane;
            xs[0] = make_uint4(ln_pair(u0.x, m2, sel_inv), ln_pair(u0.y, m2, sel_inv), ln_pair(u0.z, m2, sel_inv), ln_pair(u0.w, m2, sel_inv));
            xs[32] = make_uint4(ln_pair(u1.x, m2, sel_inv), ln_pair(u1.y, m2, sel_inv), ln_pair(u1.z, m2, sel_inv), ln_pair(u1.w, m2, sel_inv));
            s_misc[M_KEY] = best; s_misc[M_MEAN] = __float_as_uint(sel_m); s_misc[M_INV] = __float_as_uint(sel_inv);
            s_misc[M_XQ + q] = u2;
          } else if (warp == 1) {
            mbar_expect_tx(bar(B_HX), 3584);
            mbar_wait(bar(B_OST + 1), layer);
            set_flag(&g_oflag[rb][1][hp].v[layer], tag);
            poll_flag(&g_oflag[rb][1][lane & 15].v[layer], tag);
            __syncwarp();
            mbar_arrive_e(bar(B_WGO + 1));
          } else {
            const uint4 sent = make_uint4(SENT, SENT, SENT, SENT), zero = make_uint4(0, 0, 0, 0);
            const int t = tid - 64;
            g_ypart[layer][bid * 256 + t] = sent;
            if (t < 64) g_ypart[layer][bid * 256 + 192 + t] = sent;
            else g_part[layer][nb * SEQ + mb * 128 + t - 64] = zero;
            if (t < 16) g_cand[layer][mb * 128 + nb * 16 + t] = sent;
            else if (t < 18) { if (nb == 0) g_slot[layer][mb * 8 + t - 16] = zero; }
            else if (t < 20) { if (layer == 0) g_x2row[bid * 2 + t - 18] = sent; }
            if (layer == 0) g_patch[rb][(t >> 6) * DM + hp * 64 + (t & 63)] = SENT;
            if (warp == 7) {
              uint32_t* tab = (uint32_t*)(smem + OFF_PATCH);
#pragma unroll
              for (int j = 0; j < 2; j++) { const int w = lane + 32 * j; tab[(w & 3) * 16 + (w >> 2)] = ((const uint32_t*)P.w_r)[nb * 64 + w]; }
              tab[64 + lane] = lane < 16 ? 0x3F803F80u : 0u;
              float tot = 0.f;
#pragma unroll 1
              for (int j = 0; j < 4; j++) {
                const uint4 u = ((const uint4*)P.w_r)[lane + 32 * j];
                tot += bf_lo(u.x) + bf_hi(u.x) + bf_lo(u.y) + bf_hi(u.y) + bf_lo(u.z) + bf_hi(u.z) + bf_lo(u.w) + bf_hi(u.w);
              }
              s_misc[M_WSUM] = __float_as_uint(warp_sum(tot));
            }
            fence_release();
            __syncwarp();
            mbar_arrive_e(bar(B_RST));
            if ((PF_MODE & 8) && layer == 0) {
              l2_prefetch_line((const uint8_t*)P.wqkv + (size_t)(bid * 384 + t) * 128);
              l2_prefetch_line((const uint8_t*)P.wqkv + (size_t)(bid * 384 + 192 + t) * 128);
            }
          }
        }
        PHASE_IDS
        mbar_wait(bar(B_GU), layer);
        named_bar(7, 256);
        if (warp == 2) PROF(18);
        const uint32_t wa = sbase + SL_F + (mi & 1) * 2 * FFN_PIECE + (warp * 32 + (mi >> 1) * 8 + (lane & 7)) * 112;
        const uint4* xs = (const uint4*)(smem + T_XS) + wg * 16 + q * 4 + wi;
        const uint4 xa = xs[0], xb = xs[32];
        const uint32_t hdst = sbase + T_HP + ((rank * 8 + warp) * 28 + g) * 8;
#pragma unroll
        for (int j = 0; j < 7; j++) {
          float d[4] = {0.f, 0.f, 0.f, 0.f};
          const uint32_t* r = &gu[j * 8];
          uint32_t a[8];
          ldsm_x4_t(wa + j * 16, a[0], a[1], a[2], a[3]);
          ldsm_x4_t(wa + j * 16 + 1792, a[4], a[5], a[6], a[7]);
          mma_16816(d, r[0], r[1], r[2], r[3], xb.x, xb.y);
          mma_16816(d, r[4], r[5], r[6], r[7], xb.z, xb.w);
          mma_16816(d, a[0], a[1], a[2], a[3], xa.x, xa.y);
          mma_16816(d, a[4], a[5], a[6], a[7], xa.z, xa.w);
          const int own = 8 * j + g >= 28;
          if (q == 0) st_async2(mapa(hdst + (8 * j - 28 * own) * 8, own), d[0], d[2], mapa(bar(B_HX), own));
        }
        __syncwarp();
      }
      regs_dec<32>();
      if (pass > 0) {
        const unsigned layer = pass - 1;
        PHASE_IDS
        const uint32_t tag = s_misc[M_TAG], bkey = s_misc[M_KEY];
        const int sel = SEQ - 1 - (int)(bkey & 0xFFFFu);
        if (warp == 3) {
          if (layer == 1) {
            if (lane < 24) ((uint4*)g_cspart)[bid * 24 + lane] = make_uint4(0, 0, 0, 0);
          } else s_misc[M_SEL0] = sel;
          if (bid == 0 && lane == 0) g_sel[layer] = sel;
        } else if (warp == 0) {
          named_bar(10, 288);
          if (layer == 0) {
            poll_flag(&g_xflag[2 * rb + (lane & 1)][(lane >> 1) & 7].v[0], tag);
            __syncwarp();
            fence_async_global();
#pragma unroll 1
            for (int i = 0; i < 3; i++) {
              if (i == 2) named_bar(9, 512);
              if (i != 1) {
                fence_async_smem();
                if (lane < 2) mbar_arrive_cluster(bar(B_QFREE), lane);
                mbar_wait(bar(B_QFREE), i >> 1);
              }
              load_w(i, i); load_a(i, i, 1);
              if (i == 0) PROFL(1, 1);
            }
          }
        }
        __syncwarp();
        if (warp != 0 || layer == 1) named_bar(9, 512);
        if (wg == 1) {
          spin_cycles(DELAY_Y);
          const uint4* src = &g_ypart[layer][((tid - 128) >> 1) * 256 + bid * 2 + (tid & 1)];
          const unsigned* xf = &g_xflag[sel >> 7][bid >> 4].v[layer];
          uint4 v, w;
          uint32_t f, spins = 0;
#pragma unroll 1
          do { v = ld_relaxed4(src); w = ld_relaxed4(src + 64 * 256); f = ld_relaxed(xf); } while (!__all_sync(0xffffffffu, valid4(v) && valid4(w) && f == tag) && ++spins < SPIN_LIMIT);
          float a[4] = {__uint_as_float(v.x) + __uint_as_float(w.x), __uint_as_float(v.y) + __uint_as_float(w.y),
                        __uint_as_float(v.z) + __uint_as_float(w.z), __uint_as_float(v.w) + __uint_as_float(w.w)};
          const bool b1 = lane & 2, b2 = lane & 4;
          float c0 = (b1 ? a[1] : a[0]) + __shfl_xor_sync(0xffffffffu, b1 ? a[0] : a[1], 2);
          float c1 = (b1 ? a[3] : a[2]) + __shfl_xor_sync(0xffffffffu, b1 ? a[2] : a[3], 2);
          float y = (b2 ? c1 : c0) + __shfl_xor_sync(0xffffffffu, b2 ? c0 : c1, 4);
          y += __shfl_xor_sync(0xffffffffu, y, 8);
          y += __shfl_xor_sync(0xffffffffu, y, 16);
          float* red = (float*)(smem + OFF_PATCH);
          red[wi * 8 + (lane & 1) * 4 + ((lane >> 1) & 3)] = y;
          named_bar(2, 128);
          if (warp == 4) {
            PROF(21);
            asm volatile("fence.acquire.gpu;" ::: "memory");
            const float sel_m = __uint_as_float(s_misc[M_MEAN]), sel_inv = __uint_as_float(s_misc[M_INV]);
            y = (red[lane & 7] + red[8 + (lane & 7)]) + (red[16 + (lane & 7)] + red[24 + (lane & 7)]);
            const uint32_t xw = s_misc[M_XQ + ((lane & 7) >> 1)];
            const float x = (lane & 1) ? bf_hi(xw) : bf_lo(xw);
            const float xn = rbf(rbf(x - sel_m) * sel_inv);
            uint32_t u = bkey & 0xFFFF0000u;
            u = (u & 0x80000000u) ? (u & 0x7FFFFFFFu) : (~u & 0xFFFF0000u);
            const float sg = rbf(__fdividef(1.f, 1.f + __expf(-__uint_as_float(u))));
            const float res = x + rbf(xn + rbf(rbf(y) * sg));
            const uint32_t pr = nosent(pack_bf16(res, __shfl_down_sync(0xffffffffu, res, 1)));
            if (lane < 8 && (lane & 1) == 0)
              st_relaxed((layer == 0 ? (uint32_t*)&g_x2row[bid * 2] : (uint32_t*)(P.out + (size_t)sel * DM + bid * 8)) + (lane >> 1), pr);
            PROF(22);
          }
        }
        if (pass == 2) {
          if (bid == 0 && tid == 128) g_epoch = tag;
          __syncwarp();
          cluster_arrive(); cluster_wait();
          return;
        }
      }
      const unsigned layer = pass;
      PHASE_IDS
      const uint32_t tag = s_misc[M_TAG];
      if (wg == 0) {
        if (warp == 0) {
          int s = 0, u = 0;
#pragma unroll 1
          for (int i = 3; i < 16; i++) {
            if (layer == 1) mbar_arrive_e(bar(B_EMPTY + s));
            mbar_wait(bar(B_EMPTY + s), (u + (s ? 0 : layer)) & 1);
            load_w(s, i);
            load_a(s, i, layer);
            if (++s == 3) { s = 0; u++; }
          }
        } else if (warp == 1) {
          if (layer == 0) {
            float shift = 0.f, sum = 0.f, sq = 0.f;
            const int r = hp * 16 + (lane >> 1);
#pragma unroll 1
            for (int i = 0; i < 16; i++) {
              mbar_wait(bar(B_FULL + i % 3), (i / 3) & 1);
              const uint8_t* base = smem + (i % 3) * STG + r * 128;
#pragma unroll 1
              for (int j0 = 0; j0 < 4; j0 += 2) {
                uint4 v[2];
#pragma unroll
                for (int j = 0; j < 2; j++) v[j] = *(const uint4*)(base + ((((lane & 1) * 4 + j0 + j) ^ (r & 7)) << 4));
                if (i == 0 && j0 == 0) shift = __shfl_sync(0xffffffffu, bf_lo(v[0].x), lane & ~1);
#pragma unroll
                for (int j = 0; j < 2; j++) {
                  const uint32_t w[4] = {v[j].x, v[j].y, v[j].z, v[j].w};
#pragma unroll
                  for (int c = 0; c < 4; c++) {
                    const float d0 = bf_lo(w[c]) - shift, d1 = bf_hi(w[c]) - shift;
                    sum += d0 + d1; sq = fmaf(d0, d0, fmaf(d1, d1, sq));
                  }
                }
              }
              __syncwarp();
              if (i < 13) mbar_arrive_e(bar(B_EMPTY + i % 3));
            }
            sum += __shfl_xor_sync(0xffffffffu, sum, 1); sq += __shfl_xor_sync(0xffffffffu, sq, 1);
            const float dm = sum * (1.f / DM), var = fmaxf(sq * (1.f / DM) - dm * dm, 0.f), mean = shift + dm;
            const float inv = ln_inv(var);
            if ((lane & 1) == 0) st_relaxed4(&g_rowab[0][rb * 256 + r], make_uint4(__float_as_uint(inv), __float_as_uint(rbf(mean) * inv), tag, 0));
          }
          if (rb == 0) {
            mbar_wait(bar(B_QDONE), layer);
#pragma unroll 1
            for (int j = lane; j < 512; j += 32) ((uint4*)(smem + 65536))[j] = make_uint4(0, 0, 0, 0);
            fence_async_smem();
            __syncwarp();
            if (lane < 3) mbar_arrive(bar(B_HALO + lane));
          }
        } else if (warp == 3) {
          if (layer == 1) named_bar(12, 160);
          else { mbar_wait(bar(B_FULL), 0); mbar_wait(bar(B_FULL), 1); }
          fence_async_smem();
          mbar_expect_tx(bar(B_GU), 4 * FFN_PIECE);
#pragma unroll 1
          for (int j = 0; j < 4; j++) {
            tma_load2_h(sbase + SL_F + j * FFN_PIECE, &P.mapG + (j >> 1), cl * 56, rank * 512 + (j & 1) * 128, bar(B_GU), FFN_POL);
            spin_cycles(GU_PACE);
          }
          PROF(27);
        } else if (PF_MODE & 7) {
          mbar_wait(bar(B_FULL), 0); mbar_wait(bar(B_FULL), 1);
          if (PF_MODE & 1) {
#pragma unroll 1
            for (int j = 0; j < 16; j++) {
              const size_t off = (size_t)(rank * 512 + 256 + (j & 7) * 32 + lane) * (FF * 2) + cl * 112;
              const uint8_t* w = (const uint8_t*)(j < 8 ? P.w_g : P.w_u) + off;
              l2_prefetch_line(w); l2_prefetch_line(w + 111);
              spin_cycles(300);
            }
          }
          if (PF_MODE & 2) {
#pragma unroll 1
            for (int j = 0; j < 14; j++) { l2_prefetch_line((const uint8_t*)P.w_d + (size_t)bid * 57344 + (j * 32 + lane) * 128); spin_cycles(300); }
          }
          if (PF_MODE & 4) {
#pragma unroll 1
            for (int j = 0; j < 4; j++) l2_prefetch_line((const uint8_t*)P.wo + (size_t)bid * 16384 + (j * 32 + lane) * 128);
          }
        }
        __syncwarp();
        const int n = warp - 1, off = n == 0 ? 16384 : (n == 1 ? 0 : 65536), len = n == 2 ? 32768 : 16384;
        if (warp == 0) {
          if (rank == 0) {
            mbar_wait(bar(B_QDONE), layer);
#pragma unroll 1
            for (int j = 0; j < 3; j++) {
              const int o = j == 0 ? 16384 : (j == 1 ? 0 : 65536);
              mbar_wait(bar(B_KVREADY + (j >> 1)), layer);
              bulk_push(mapa(sbase + o, 1), sbase + 32768 + o, j == 2 ? 32768 : 16384, mapa(bar(B_HALO + j), 1));
            }
          }
        } else if (rank == 1) {
          mbar_expect_tx(bar(B_HALO + n), len);
          if (rb < 7) {
            mbar_wait(bar(B_KVREADY + (n >> 1)), layer);
            if (n > 0) mbar_wait(bar(B_CHAIN + n - 1), layer);
            bulk_store(g_kv + (size_t)((rb >> 1) * 16 + hp) * 65536 + (off >> (n >> 1)), sbase + 32768 + off, len);
            bulk_commit();
            bulk_wait_all();
            if (n < 2) mbar_arrive_e(bar(B_CHAIN + n));
            set_flag(&g_kvflag[rb >> 1][hp][n].v[layer], tag);
            if (n == 0) PROF(4);
          }
        } else if (rb > 0 && n < 2) {
          mbar_wait(bar(B_KVREADY + 1), layer);
          poll_flag(&g_kvflag[(rb - 1) >> 1][hp][n].v[layer], tag);
          fence_async_global();
          mbar_expect_tx(bar(B_HALO + n), 16384);
          bulk_load_h(sbase + off, g_kv + (size_t)(((rb - 1) >> 1) * 16 + hp) * 65536 + off, 16384, bar(B_HALO + n), policy_evict_first());
          if (n == 0) PROF(5);
        }
      } else {
        const int t = tid - 128, go = (t >> 5) * DM + hp * 64 + (t & 31) * 2;
        if (layer == 0) {
#pragma unroll 1
          for (int u = 0; u < 5; u++) mbar_wait(bar(B_FULL + 2), u & 1);
          if (warp < 7) {
            uint2 v[4];
            uint32_t spins = 0;
#pragma unroll 1
            do {
#pragma unroll
              for (int j = 0; j < 4; j++) v[j] = ld_relaxed2(&g_cspart[j][go]);
            } while (!__all_sync(0xffffffffu, v[0].x && v[0].y && v[1].x && v[1].y && v[2].x && v[2].y && v[3].x && v[3].y) && ++spins < SPIN_LIMIT);
            ((float2*)(smem + OFF_CS))[t] = make_float2((dec(v[0].x) + dec(v[1].x)) + (dec(v[2].x) + dec(v[3].x)), (dec(v[0].y) + dec(v[1].y)) + (dec(v[2].y) + dec(v[3].y)));
          }
        } else {
          if (warp == 5) {
            mbar_expect_tx(bar(B_WS), 4 * SL_HD);
#pragma unroll 1
            for (int j = 0; j < 4; j++) tma_load3(sbase + SL_F + j * SL_HD, &P.mapW, hp * 64, rb * 128 + j * 32, 0, bar(B_WS));
          }
          const uint4 v = poll4(&g_x2row[t * 2]);
          __syncwarp();
          PROF(23);
          if (t >> 4 == rb) ((uint4*)(smem + SL_F + 4 * SL_HD))[t & 15] = v;
          float* red = (float*)(smem + SL_F + 4 * SL_HD + 256);
          const float e[8] = {bf_lo(v.x), bf_hi(v.x), bf_lo(v.y), bf_hi(v.y), bf_lo(v.z), bf_hi(v.z), bf_lo(v.w), bf_hi(v.w)};
          red[wi] = warp_sum(((e[0] + e[1]) + (e[2] + e[3])) + ((e[4] + e[5]) + (e[6] + e[7])));
          named_bar(2, 128);
          const float mean = ((red[0] + red[1]) + (red[2] + red[3])) * (1.f / DM);
          float qq = 0.f;
#pragma unroll
          for (int c = 0; c < 8; c++) qq = fmaf(e[c] - mean, e[c] - mean, qq);
          red[4 + wi] = warp_sum(qq);
          mbar_wait(bar(B_WS), 0);
          if (warp < 7) {
            const uint8_t* wa = smem + SL_F + mi * SL_HD + wi * 4096;
            const uint32_t* xs = (const uint32_t*)(smem + SL_F + 4 * SL_HD) + mi * 16;
            float d[8] = {0.f, 0.f, 0.f, 0.f, 0.f, 0.f, 0.f, 0.f};
#pragma unroll 1
            for (int j = 0; j < 32; j += 2) {
              const uint4 w0 = *(const uint4*)(wa + j * 128 + (((lane ^ j) & 7) << 4)), w1 = *(const uint4*)(wa + j * 128 + 128 + (((lane ^ (j + 1)) & 7) << 4));
              const uint32_t xx = xs[j >> 1];
              const float x0 = bf_lo(xx), x1 = bf_hi(xx);
              d[0] += x0 * bf_lo(w0.x); d[1] += x0 * bf_hi(w0.x); d[2] += x0 * bf_lo(w0.y); d[3] += x0 * bf_hi(w0.y);
              d[4] += x0 * bf_lo(w0.z); d[5] += x0 * bf_hi(w0.z); d[6] += x0 * bf_lo(w0.w); d[7] += x0 * bf_hi(w0.w);
              d[0] += x1 * bf_lo(w1.x); d[1] += x1 * bf_hi(w1.x); d[2] += x1 * bf_lo(w1.y); d[3] += x1 * bf_hi(w1.y);
              d[4] += x1 * bf_lo(w1.z); d[5] += x1 * bf_hi(w1.z); d[6] += x1 * bf_lo(w1.w); d[7] += x1 * bf_hi(w1.w);
            }
#pragma unroll
            for (int c = 0; c < 4; c++) d[c] = ((mi & 2) ? d[c + 4] : d[c]) + __shfl_xor_sync(0xffffffffu, (mi & 2) ? d[c] : d[c + 4], 16);
#pragma unroll
            for (int c = 0; c < 2; c++) d[c] = ((mi & 1) ? d[c + 2] : d[c]) + __shfl_xor_sync(0xffffffffu, (mi & 1) ? d[c] : d[c + 2], 8);
            uint32_t* dst = &g_patch[rb][wi * DM + hp * 64 + (lane & 7) * 8 + mi * 2];
            st_relaxed(dst, f2u(d[0])); st_relaxed(dst + 1, f2u(d[1]));
          }
          named_bar(2, 128);
          const float inv = ln_inv(((red[4] + red[5]) + (red[6] + red[7])) * (1.f / DM));
          asm volatile("bar.arrive 12, 160;" ::"f"(inv) : "memory");
          PROF(24);
          if ((int)s_misc[M_SEL0] >> 8 == rb && warp < 7) {
            float s0 = 0.f, s1 = 0.f;
#pragma unroll 1
            for (int hf = 0; hf < 8; hf += 4) {
              uint2 w[4];
              uint32_t spins = 0;
#pragma unroll 1
              do {
#pragma unroll
                for (int j = 0; j < 4; j++) w[j] = ld_relaxed2(&g_patch[hf + j][go]);
              } while (!__all_sync(0xffffffffu, valid4(make_uint4(w[0].x, w[0].y, w[1].x, w[1].y)) && valid4(make_uint4(w[2].x, w[2].y, w[3].x, w[3].y))) && ++spins < SPIN_LIMIT);
              s0 += (__uint_as_float(w[0].x) + __uint_as_float(w[1].x)) + (__uint_as_float(w[2].x) + __uint_as_float(w[3].x));
              s1 += (__uint_as_float(w[0].y) + __uint_as_float(w[1].y)) + (__uint_as_float(w[2].y) + __uint_as_float(w[3].y));
            }
            const float2 c = ((const float2*)(smem + OFF_CS))[t];
            const float a = warp == 4 ? inv * SM_C : inv, b = rbf(mean) * a;
            ((uint32_t*)(smem + OFF_PATCH))[t] = pack_bf16(s0 * a - c.x * b, s1 * a - c.y * b);
            PROF(25);
          }
        }
        __syncwarp();
        mbar_arrive_e(bar(B_CS));
      }
      __syncwarp();
      mbar_wait(bar(B_QREADY), layer);
      named_bar(1 + (fresh_tid() >> 7), 128);
      regs_inc<128>();
    }
    const unsigned layer = pass;
    {
      PHASE_IDS
      mbar_wait(bar(B_QREADY), layer);
      if (warp != 9) STEPT(7);
      auto kdesc = [&](int h, int b) { return dlo(SOFF, 16) + (rb == 0 && b < 4 ? 4096 : h * 4096 + b * 512); };
      auto vdesc = [&](int h, int b) { return rb == 0 && b < 4 ? dlo(SOFF + 65536, 4096) : dlo(SOFF + 4096, OFF_ONES - 4096) + (h * 8 + b) * 8 * VSTEP; };
      auto load_q = [&](uint32_t* qf, int h) {
        *(uint4*)&qf[0] = *(const uint4*)(smem + AT_ST + (h * 16 + warp) * 1024 + lane * 16);
        *(uint4*)&qf[4] = *(const uint4*)(smem + AT_ST + (h * 16 + warp) * 1024 + 512 + lane * 16);
      };
      auto store_o = [&](const float* o, int h) {
        const float i0 = __fdividef(1.f, o[16]), i1 = __fdividef(1.f, o[18]);
#pragma unroll
        for (int j = 0; j < 2; j++)
          stsm_x4(sbase + AT_ST + (h * 4 + wg) * 4096 + srow * 64 + (((2 * j + (mi >> 1)) ^ ((srow >> 1) & 3)) << 4),
                  pack_bf16(o[8 * j] * i0, o[8 * j + 1] * i0), pack_bf16(o[8 * j + 2] * i1, o[8 * j + 3] * i1),
                  pack_bf16(o[8 * j + 4] * i0, o[8 * j + 5] * i0), pack_bf16(o[8 * j + 6] * i1, o[8 * j + 7] * i1));
        fence_async_smem();
        __syncwarp();
        bulk_store(g_o + (size_t)((((rb * 2 + (wg >> 1)) * 2 + h) * 16 + hp) * 8 + (warp & 7)) * 1024, sbase + AT_ST + (h * 16 + warp) * 1024, 1024);
        bulk_commit();
      };
      auto leave_head0 = [&]() {
        bulk_wait_all();
        mbar_arrive_e(bar(B_OST));
        uint32_t n = 0;
        asm volatile(ELECT "atom.relaxed.cta.shared::cta.inc.u32 %0, [%1], 15;\n}" : "+r"(n) : "r"(sbase + OFF_MISC + 4 * M_CNT) : "memory");
        if (__any_sync(0xffffffffu, n == 15)) {
          mbar_wait(bar(B_OST), layer);
          if (rank == 0) mbar_wait(bar(B_PUSHED), layer);
          mbar_expect_tx(bar(B_GU + 1), 4 * FFN_PIECE);
#pragma unroll 1
          for (int j = 0; j < 4; j++) tma_load2_h(sbase + j * FFN_PIECE, &P.mapG + (j >> 1), cl * 56, rank * 512 + 256 + (j & 1) * 128, bar(B_GU + 1), FFN_POL);
          PROF(26);
        }
      };
      int redo = 0;
      {
        const int dl = g - 2 * q;
        const uint32_t mt = shl_clamp(0xFFFFFFFFu, max(16 * dl + 16, 0));
        uint32_t qf[8];
        float s[32];
        load_q(qf, 0);
        if (wg == 0) mbar_wait(bar(B_HALO), layer);
        wg_fence();
        qk64(s, qf, kdesc(0, wg + 3));
        wg_commit();
        wg_wait<0>();
        fence_regs<32>(s);
#pragma unroll 1
        for (int h = 0; h < 2; h++) {
          float o[20];
          uint32_t p1[16], p2[16], p3[24], p4[24];
          if (warp != 9) STEPT(8 + h * 8);
          exp_pack<8>(s, p1);
          fence_regs_u<16>(p1);
          if (wg == 1) mbar_wait(bar(B_HALO + 2 * h), layer);
          {
            float s2[32];
            const uint32_t vd = vdesc(h, wg + 3);
            wg_fence();
            qk64(s2, qf, kdesc(h, wg + 2));
            wg_commit();
            wg_rs40t_z<H64>(o, p1[0], p1[1], p1[2], p1[3], vd);
            wg_rs40t<H64>(o, p1[4], p1[5], p1[6], p1[7], vd + VSTEP, 1);
            pv32(o, p1 + 8, vd + 2 * VSTEP);
            wg_commit();
            if (h == 1 && !redo) leave_head0();
            wg_wait<1>();
            fence_regs<32>(s2);
            if (warp != 9) STEPT(9 + h * 8);
            exp_pack<8>(s2, p2);
            fence_regs_u<16>(p2);
            wg_wait<0>();
            fence_regs<20>(o);
          }
          mbar_wait(bar(B_HALO + (h ? 2 : wg < 2)), layer);
          if (h == 0 && rank == 1 && tid == 0) mbar_arrive_cluster(bar(B_PUSHED), 0);
          const uint32_t km = kdesc(h, wg + 1), kd = kdesc(h, wg + 4), kt = kdesc(h, wg);
          const uint32_t vm = vdesc(h, wg + 1), vd = vdesc(h, wg + 4), vt = vdesc(h, wg);
          {
            float sm[16], sd[16], st[16];
            wg_fence();
            qk32x3(sm, sd, st, qf, km, kd, kt);
            pv32(o, p2, vdesc(h, wg + 2)); pv32(o, p2 + 8, vdesc(h, wg + 2) + 2 * VSTEP);
            wg_commit();
            wg_wait<0>();
            fence_regs<16>(sm); fence_regs<16>(sd); fence_regs<16>(st); fence_regs<20>(o);
            if (warp != 9) STEPT(10 + h * 8);
            mix_exp(sm, sd, st, p3, wi, dl, mt);
            fence_regs_u<24>(p3);
          }
          {
            float sm[16], sd[16], st[16];
            wg_fence();
            qk32x3(sm, sd, st, qf, km + 128, kd + 128, kt + 128);
            pv32(o, p3, vm); pv32(o, p3 + 8, vd); pv32(o, p3 + 16, vt);
            wg_commit();
            if (h == 0 && warp == 14 && rank == 0 && rb > 0) {
              poll_flag(&g_kvflag[(rb - 1) >> 1][hp][2].v[layer], s_misc[M_TAG]);
              fence_async_global();
              mbar_expect_tx(bar(B_HALO + 2), 32768);
              bulk_load_h(sbase + 65536, g_kv + (size_t)(((rb - 1) >> 1) * 16 + hp) * 65536 + 32768, 32768, bar(B_HALO + 2), policy_evict_first());
            }
            wg_wait<0>();
            fence_regs<16>(sm); fence_regs<16>(sd); fence_regs<16>(st); fence_regs<20>(o);
            if (warp != 9) STEPT(11 + h * 8);
            load_q(qf, 1);
            mix_exp(sm, sd, st, p4, wi - 2, dl, mt);
            fence_regs_u<24>(p4);
          }
          if (wg == 0) mbar_wait(bar(B_HALO + 2), layer);
          wg_fence();
          pv32(o, p4, vm + 2 * VSTEP); pv32(o, p4 + 8, vd + 2 * VSTEP); pv32(o, p4 + 16, vt + 2 * VSTEP);
          wg_commit();
          qk64(s, qf, kdesc(1, wg + 3));
          wg_commit();
          wg_wait<1>();
          fence_regs<20>(o);
          if (warp != 9) STEPT(12 + h * 8);
          const bool unsafe = !(o[16] >= LSUM_MIN && o[16] <= LSUM_MAX && o[18] >= LSUM_MIN && o[18] <= LSUM_MAX);
          if (__any_sync(0xffffffffu, unsafe)) redo |= 1 << h;
          else store_o(o, h);
          wg_wait<0>();
          fence_regs<32>(s);
        }
      }
      if (warp != 9) STEPT(13 + 8);
      if (bar_red_or(1 + wg, 128, redo)) {
#pragma unroll 1
        for (int h = 0; h < 2; h++) {
          if (!bar_red_or(1 + wg, 128, redo >> h & 1)) continue;
          uint32_t qf[8], p[16];
          float o[20], m0 = -INFINITY, m1 = -INFINITY;
          load_q(qf, h);
#pragma unroll
          for (int i = 0; i < 20; i++) o[i] = 0.f;
#pragma unroll 1
          for (int j = 0; j <= (rb == 0 ? wg : 4); j++) {
            const int b = wg + 4 - j;
            float s[32];
            wg_fence();
            qk64(s, qf, kdesc(h, b));
            wg_commit();
            wg_wait<0>();
            fence_regs<32>(s);
            float mx0 = m0, mx1 = m1;
#pragma unroll
            for (int c = 0; c < 8; c++) {
#pragma unroll
              for (int i = 0; i < 4; i++) {
                const int diff = j * 64 + (16 * wi + g + (i >> 1) * 8) - (8 * c + 2 * q + (i & 1));
                if (diff < 0 || diff > 255) s[4 * c + i] = -INFINITY;
              }
              mx0 = fmaxf(mx0, fmaxf(s[4 * c], s[4 * c + 1]));
              mx1 = fmaxf(mx1, fmaxf(s[4 * c + 2], s[4 * c + 3]));
            }
            mx0 = fmaxf(mx0, __shfl_xor_sync(0xffffffffu, mx0, 1)); mx1 = fmaxf(mx1, __shfl_xor_sync(0xffffffffu, mx1, 1));
            mx0 = fmaxf(mx0, __shfl_xor_sync(0xffffffffu, mx0, 2)); mx1 = fmaxf(mx1, __shfl_xor_sync(0xffffffffu, mx1, 2));
            const float r0 = j == 0 ? 0.f : ex2(m0 - mx0), r1 = j == 0 ? 0.f : ex2(m1 - mx1);
            m0 = mx0; m1 = mx1;
#pragma unroll
            for (int i = 0; i < 5; i++) { o[4 * i] *= r0; o[4 * i + 1] *= r0; o[4 * i + 2] *= r1; o[4 * i + 3] *= r1; }
#pragma unroll
            for (int c = 0; c < 8; c++) { s[4 * c] -= m0; s[4 * c + 1] -= m0; s[4 * c + 2] -= m1; s[4 * c + 3] -= m1; }
            exp_pack<8>(s, p);
            fence_regs<20>(o); fence_regs_u<16>(p);
            wg_fence();
            pv32(o, p, vdesc(h, b)); pv32(o, p + 8, vdesc(h, b) + 2 * VSTEP);
            wg_commit();
            wg_wait<0>();
            fence_regs<20>(o);
          }
          named_bar(1 + wg, 128);
          if (redo >> h & 1) {
            store_o(o, h);
            if (h == 0) leave_head0();
          }
          __syncwarp();
        }
      }
      if (wi == 0) PROF(6 + wg);
      if (wi == 3 && lane < 2) mbar_arrive_cluster(bar(B_ADONE), lane);
      bulk_wait_all();
      __syncwarp();
      if (lane < 2) mbar_arrive_cluster(bar(B_OST + 1), lane);
      __syncwarp();
      if (warp == 14) {
        mbar_wait(bar(B_OST), layer);
        set_flag(&g_oflag[rb][0][hp].v[layer], s_misc[M_TAG]);
        PROF(28);
      }
    }
    pass_v = pass + 1;
  }
}

}

typedef CUresult (*EncodeFn)(CUtensorMap*, CUtensorMapDataType, cuuint32_t, void*, const cuuint64_t*, const cuuint64_t*,
                             const cuuint32_t*, const cuuint32_t*, CUtensorMapInterleave, CUtensorMapSwizzle,
                             CUtensorMapL2promotion, CUtensorMapFloatOOBfill);
static EncodeFn g_encode = nullptr;
struct Dim { uint64_t size, stride; uint32_t box; };
template <int N> static CUtensorMap make_map(const void* ptr, const Dim (&d)[N], int swizzle) {
  CUtensorMap m;
  cuuint64_t dims[N], strides[N];
  cuuint32_t box[N], es[N];
  for (int i = 0; i < N; i++) { dims[i] = d[i].size; strides[i] = d[i].stride; box[i] = d[i].box; es[i] = 1; }
  g_encode(&m, CU_TENSOR_MAP_DATA_TYPE_BFLOAT16, N, const_cast<void*>(ptr), dims, strides + 1, box, es, CU_TENSOR_MAP_INTERLEAVE_NONE,
           swizzle == 128 ? CU_TENSOR_MAP_SWIZZLE_128B : (swizzle == 64 ? CU_TENSOR_MAP_SWIZZLE_64B : CU_TENSOR_MAP_SWIZZLE_NONE),
           swizzle ? CU_TENSOR_MAP_L2_PROMOTION_L2_256B : CU_TENSOR_MAP_L2_PROMOTION_L2_128B, CU_TENSOR_MAP_FLOAT_OOB_FILL_NONE);
  return m;
}
static CUtensorMap map2(const void* ptr, uint64_t inner, uint64_t outer, uint32_t bi, uint32_t bo, int swizzle) {
  const Dim d[2] = {{inner, 0, bi}, {outer, inner * 2, bo}};
  return make_map(ptr, d, swizzle);
}
template <class T> static void* sym_addr(T& sym) { void* p = nullptr; cudaGetSymbolAddress(&p, sym); return p; }

static Params h_p, h_p_helper;
static const void* h_key[9];
static bool h_helpers_fit = true;

static cudaLaunchConfig_t launch_cfg(int grid, cudaLaunchAttribute* at) {
  cudaLaunchConfig_t cfg = {};
  cfg.gridDim = dim3(grid); cfg.blockDim = dim3(512); cfg.dynamicSmemBytes = SMEM_BYTES; cfg.stream = cudaStreamPerThread;
  at[0].id = cudaLaunchAttributeClusterDimension;
  at[0].val.clusterDim.x = 2; at[0].val.clusterDim.y = 1; at[0].val.clusterDim.z = 1;
  cfg.attrs = at; cfg.numAttrs = 1;
  return cfg;
}

extern "C" void kernel_launch(void* const* d_in, const int* in_sizes, int n_in, void* d_out, int out_size) {
  const bf16* x = (const bf16*)d_in[0];
  const bf16* wqkv = (const bf16*)d_in[1];
  const bf16* wo = (const bf16*)d_in[2];
  cudaLaunchAttribute at[1];
  bool fresh = g_encode != nullptr && h_key[8] == d_out;
  for (int i = 0; i < 8; i++) fresh = fresh && h_key[i] == d_in[i];
  if (!fresh) {
    if (!g_encode) {
      void* fn = nullptr;
      cudaDriverEntryPointQueryResult st;
      cudaGetDriverEntryPoint("cuTensorMapEncodeTiled", &fn, cudaEnableDefault, &st);
      g_encode = (EncodeFn)fn;
      cudaFuncSetAttribute(mega_kernel, cudaFuncAttributeMaxDynamicSharedMemorySize, SMEM_BYTES);
      cudaLaunchConfig_t cfg = launch_cfg(132, at);
      int nclusters = 0;
      if (cudaOccupancyMaxActiveClusters(&nclusters, mega_kernel, &cfg) != cudaSuccess) { nclusters = 0; (void)cudaGetLastError(); }
      h_helpers_fit = nclusters >= 66;
    }
    bf16* x1 = (bf16*)sym_addr(g_x2);
    Params& p = h_p;
    p.wqkv = wqkv; p.wo = wo; p.w_r = (const bf16*)d_in[4]; p.w_g = (const bf16*)d_in[5]; p.w_u = (const bf16*)d_in[6]; p.w_d = (const bf16*)d_in[7];
    p.out = (bf16*)d_out;
    p.mapA[0] = map2(x, DM, SEQ, 64, 256, 128);
    p.mapA[1] = map2(x1, DM, SEQ, 64, 256, 128);
    { const Dim d[3] = {{DM, 0, 64}, {DM, 3 * DM * 2, 32}, {3, DM * 2, 3}}; p.mapW = make_map(wqkv, d, 128); }
    { const Dim d[3] = {{DM, 0, 64}, {64, DM * 2, 32}, {16, 64 * DM * 2, 2}}; p.mapWo = make_map(wo, d, 128); }
    p.mapRes[0] = map2(x, DM, SEQ, 64, 64, 128);
    p.mapRes[1] = p.mapXst[0] = map2(x1, DM, SEQ, 64, 64, 128);
    p.mapXst[1] = map2(d_out, DM, SEQ, 64, 64, 128);
    p.mapG = map2(p.w_g, FF, DM, 56, 128, 0);
    p.mapU = map2(p.w_u, FF, DM, 56, 128, 0);
    { const Dim d[3] = {{64, 0, 64}, {FF, DM * 2, 28}, {DM / 64, 128, 8}}; p.mapD = make_map(p.w_d, d, 128); }
    p.helper_first = 128;
    h_p_helper = p;
    h_p_helper.helper_first = 0;
    for (int i = 0; i < 8; i++) h_key[i] = d_in[i];
    h_key[8] = d_out;
  }
  if (!h_helpers_fit) {
    void* ah[] = {&h_p_helper};
    cudaLaunchConfig_t cfg = launch_cfg(4, at);
    cudaLaunchKernelExC(&cfg, (const void*)mega_kernel, ah);
  }
  void* a0[] = {&h_p};
  cudaLaunchConfig_t cfg = launch_cfg(h_helpers_fit ? 132 : 128, at);
  cudaLaunchKernelExC(&cfg, (const void*)mega_kernel, a0);
}
```

```cpp
#include <cuda_runtime.h>
#include <cuda_bf16.h>
#include <cuda.h>
#include <stdint.h>

namespace {

constexpr int SEQ = 2048, DM = 1024, FF = 3584;
constexpr float LN_EPS = 1e-5f;
typedef __nv_bfloat16 bf16;

__device__ __align__(1024) uint8_t g_kv[3 * 16 * 65536];
__device__ __align__(1024) uint8_t g_o[SEQ * DM * 2];
__device__ __align__(1024) bf16 g_x1[SEQ * DM];
__device__ unsigned g_epoch;
struct __align__(128) Flag { unsigned v[32]; };
__device__ Flag g_kvflag[3][16][3], g_oflag[8][2][16], g_xflag[16][8];
__device__ uint4 g_rowab[2][SEQ];
__device__ __align__(16) uint32_t g_cspart[4][3 * DM];
constexpr uint32_t SENT = 0xFFFFFFFFu;
__device__ uint4 g_part[2][8 * SEQ];
__device__ uint4 g_slot[2][16 * 8];
__device__ uint4 g_cand[2][16 * 128];
__device__ uint4 g_ypart[2][128 * DM / 4];
__device__ uint4 g_x2row[128 * 2];
__device__ __align__(16) uint32_t g_patch[8][3 * DM];
__device__ float2 g_rowln[8][SEQ];
__device__ int g_sel[2];

#define PROFL(l, e)
#define PROF(e) PROFL(layer, e)
#define STEPT(i)
#define SPIN_LIMIT 4000000u
__device__ __forceinline__ uint32_t smem_u32(const void* p) { return (uint32_t)__cvta_generic_to_shared(p); }
__device__ __forceinline__ void mbar_init(uint32_t bar, uint32_t cnt) {
  asm volatile("mbarrier.init.shared::cta.b64 [%0], %1;" ::"r"(bar), "r"(cnt) : "memory");
}
#define ELECT "{\n.reg .pred e;\nelect.sync _|e, 0xffffffff;\n@e "
__device__ __forceinline__ void mbar_expect_tx(uint32_t bar, uint32_t bytes) {
  asm volatile(ELECT "mbarrier.arrive.expect_tx.shared::cta.b64 _, [%0], %1;\n}" ::"r"(bar), "r"(bytes) : "memory");
}
__device__ __forceinline__ void mbar_arrive(uint32_t bar) {
  asm volatile("mbarrier.arrive.shared::cta.b64 _, [%0];" ::"r"(bar) : "memory");
}
__device__ __forceinline__ void mbar_arrive_e(uint32_t bar) {
  asm volatile(ELECT "mbarrier.arrive.shared::cta.b64 _, [%0];\n}" ::"r"(bar) : "memory");
}
__device__ __forceinline__ uint32_t mapa(uint32_t addr, uint32_t cta) {
  uint32_t r; asm("mapa.shared::cluster.u32 %0, %1, %2;" : "=r"(r) : "r"(addr), "r"(cta)); return r;
}
__device__ __forceinline__ void mbar_arrive_cluster(uint32_t bar, uint32_t cta) {
  asm volatile("mbarrier.arrive.shared::cluster.b64 _, [%0];" ::"r"(mapa(bar, cta)) : "memory");
}
#define MBAR_WAIT_ASM(QUAL)                                                                                                \
  asm volatile("{\n.reg .pred p;\n.reg .u32 n;\nmov.u32 n, 0;\nWAIT_LOOP:\n.pragma \"nounroll\";\n"                         \
               "mbarrier.try_wait.parity" QUAL ".shared::cta.b64 p, [%0], %1;\n@p bra WAIT_DONE;\n"                        \
               "add.u32 n, n, 1;\nsetp.lt.u32 p, n, %2;\n@p bra WAIT_LOOP;\nWAIT_DONE:\n}" ::"r"(bar), "r"(parity), "n"(SPIN_LIMIT) : "memory")
__device__ __forceinline__ void mbar_wait(uint32_t bar, uint32_t parity) { MBAR_WAIT_ASM(""); }
__device__ __forceinline__ void mbar_wait_cluster(uint32_t bar, uint32_t parity) { MBAR_WAIT_ASM(".acquire.cluster"); }
__device__ __forceinline__ bool mbar_wait_brief(uint32_t bar, uint32_t parity) {
  uint32_t ok;
  asm volatile("{\n.reg .pred p;\nmbarrier.try_wait.parity.shared::cta.b64 p, [%1], %2, 1000;\nselp.u32 %0, 1, 0, p;\n}"
               : "=r"(ok) : "r"(bar), "r"(parity) : "memory");
  return __all_sync(0xffffffffu, ok);
}
__device__ __forceinline__ void st_async2(uint32_t addr, float a, float b, uint32_t bar) {
  asm volatile("st.async.weak.shared::cluster.mbarrier::complete_tx::bytes.v2.f32 [%0], {%1, %2}, [%3];"
               ::"r"(addr), "f"(a), "f"(b), "r"(bar) : "memory");
}
__device__ __forceinline__ uint64_t policy_evict_first() {
  uint64_t p; asm volatile("createpolicy.fractional.L2::evict_first.b64 %0, 1.0;" : "=l"(p)); return p;
}
__device__ __forceinline__ uint64_t policy_normal() {
  uint64_t p; asm volatile("createpolicy.fractional.L2::evict_normal.b64 %0, 1.0;" : "=l"(p)); return p;
}
__device__ __forceinline__ void tma_load2(uint32_t dst, const CUtensorMap* m, int c0, int c1, uint32_t bar) {
  asm volatile(ELECT "cp.async.bulk.tensor.2d.shared::cluster.global.mbarrier::complete_tx::bytes [%0], [%1, {%3, %4}], [%2];\n}"
               ::"r"(dst), "l"(m), "r"(bar), "r"(c0), "r"(c1) : "memory");
}
__device__ __forceinline__ void tma_load2_h(uint32_t dst, const CUtensorMap* m, int c0, int c1, uint32_t bar, uint64_t pol) {
  asm volatile(ELECT "cp.async.bulk.tensor.2d.shared::cluster.global.mbarrier::complete_tx::bytes.L2::cache_hint [%0], [%1, {%3, %4}], [%2], %5;\n}"
               ::"r"(dst), "l"(m), "r"(bar), "r"(c0), "r"(c1), "l"(pol) : "memory");
}
__device__ __forceinline__ void tma_load3(uint32_t dst, const CUtensorMap* m, int c0, int c1, int c2, uint32_t bar) {
  asm volatile(ELECT "cp.async.bulk.tensor.3d.shared::cluster.global.mbarrier::complete_tx::bytes [%0], [%1, {%3, %4, %5}], [%2];\n}"
               ::"r"(dst), "l"(m), "r"(bar), "r"(c0), "r"(c1), "r"(c2) : "memory");
}
__device__ __forceinline__ void tma_load3_h(uint32_t dst, const CUtensorMap* m, int c0, int c1, int c2, uint32_t bar, uint64_t pol) {
  asm volatile(ELECT "cp.async.bulk.tensor.3d.shared::cluster.global.mbarrier::complete_tx::bytes.L2::cache_hint [%0], [%1, {%3, %4, %5}], [%2], %6;\n}"
               ::"r"(dst), "l"(m), "r"(bar), "r"(c0), "r"(c1), "r"(c2), "l"(pol) : "memory");
}
__device__ __forceinline__ void tma_load3_mc(uint32_t dst, const CUtensorMap* m, int c0, int c1, int c2, uint32_t bar) {
  asm volatile(ELECT "cp.async.bulk.tensor.3d.shared::cluster.global.mbarrier::complete_tx::bytes.multicast::cluster [%0], [%1, {%3, %4, %5}], [%2], %6;\n}"
               ::"r"(dst), "l"(m), "r"(bar), "r"(c0), "r"(c1), "r"(c2), "h"((uint16_t)3) : "memory");
}
__device__ __forceinline__ void bulk_push(uint32_t dst, uint32_t src, uint32_t bytes, uint32_t bar) {
  asm volatile(ELECT "cp.async.bulk.shared::cluster.shared::cta.mbarrier::complete_tx::bytes [%0], [%1], %2, [%3];\n}"
               ::"r"(dst), "r"(src), "r"(bytes), "r"(bar) : "memory");
}
template <int N> __device__ __forceinline__ void regs_inc() { asm volatile("setmaxnreg.inc.sync.aligned.u32 %0;" ::"n"(N)); }
template <int N> __device__ __forceinline__ void regs_dec() { asm volatile("setmaxnreg.dec.sync.aligned.u32 %0;" ::"n"(N)); }
__device__ __forceinline__ void tma_prefetch2(const CUtensorMap* m, int c0, int c1) {
  asm volatile(ELECT "cp.async.bulk.prefetch.tensor.2d.L2.global [%0, {%1, %2}];\n}" ::"l"(m), "r"(c0), "r"(c1) : "memory");
}
__device__ __forceinline__ void bulk_prefetch(const void* p, uint32_t bytes) {
  asm volatile(ELECT "cp.async.bulk.prefetch.L2.global [%0], %1;\n}" ::"l"(p), "r"(bytes) : "memory");
}
__device__ __forceinline__ void tma_store(const CUtensorMap* m, uint32_t src, int c0, int c1) {
  asm volatile(ELECT "cp.async.bulk.tensor.2d.global.shared::cta.bulk_group [%0, {%2, %3}], [%1];\n}"
               ::"l"(m), "r"(src), "r"(c0), "r"(c1) : "memory");
}
__device__ __forceinline__ void bulk_load(uint32_t dst, const void* src, uint32_t bytes, uint32_t bar) {
  asm volatile(ELECT "cp.async.bulk.shared::cluster.global.mbarrier::complete_tx::bytes [%0], [%1], %2, [%3];\n}"
               ::"r"(dst), "l"(src), "r"(bytes), "r"(bar) : "memory");
}
__device__ __forceinline__ void bulk_load_h(uint32_t dst, const void* src, uint32_t bytes, uint32_t bar, uint64_t pol) {
  asm volatile(ELECT "cp.async.bulk.shared::cluster.global.mbarrier::complete_tx::bytes.L2::cache_hint [%0], [%1], %2, [%3], %4;\n}"
               ::"r"(dst), "l"(src), "r"(bytes), "r"(bar), "l"(pol) : "memory");
}
__device__ __forceinline__ void bulk_store(void* dst, uint32_t src, uint32_t bytes) {
  asm volatile(ELECT "cp.async.bulk.global.shared::cta.bulk_group [%0], [%1], %2;\n}" ::"l"(dst), "r"(src), "r"(bytes) : "memory");
}
__device__ __forceinline__ void bulk_commit() { asm volatile("cp.async.bulk.commit_group;" ::: "memory"); }
__device__ __forceinline__ void bulk_wait_all() { asm volatile("cp.async.bulk.wait_group 0;" ::: "memory"); }
__device__ __forceinline__ void fence_async_smem() { asm volatile("fence.proxy.async.shared::cta;" ::: "memory"); }
__device__ __forceinline__ void fence_async_global() { asm volatile("fence.proxy.async.global;" ::: "memory"); }
__device__ __forceinline__ void fence_release() { asm volatile("fence.release.gpu;" ::: "memory"); }
__device__ __forceinline__ void l2_prefetch_line(const void* p) { asm volatile("prefetch.global.L2 [%0];" ::"l"(p) : "memory"); }
__device__ __forceinline__ void prefetch_tmap(const CUtensorMap* m) { asm volatile("prefetch.tensormap [%0];" ::"l"(m) : "memory"); }
__device__ __forceinline__ void named_bar(int id, int n) { asm volatile("bar.sync %0, %1;" ::"r"(id), "r"(n) : "memory"); }
__device__ __forceinline__ bool bar_red_or(int id, int n, bool v) {
  uint32_t r;
  asm volatile("{\n.reg .pred p, q;\nsetp.ne.u32 q, %3, 0;\nbarrier.cta.red.or.pred p, %1, %2, q;\nselp.u32 %0, 1, 0, p;\n}"
               : "=r"(r) : "r"(id), "r"(n), "r"((uint32_t)v) : "memory");
  return r != 0;
}
__device__ __forceinline__ void cluster_arrive() { asm volatile("barrier.cluster.arrive.relaxed.aligned;" ::: "memory"); }
__device__ __forceinline__ void cluster_wait() { asm volatile("barrier.cluster.wait.aligned;" ::: "memory"); }
__device__ __forceinline__ uint32_t cluster_rank() { uint32_t r; asm volatile("mov.u32 %0, %%cluster_ctarank;" : "=r"(r)); return r; }
__device__ __forceinline__ unsigned ld_relaxed(const unsigned* p) {
  unsigned v; asm volatile("ld.relaxed.gpu.global.u32 %0, [%1];" : "=r"(v) : "l"(p) : "memory"); return v;
}
__device__ __forceinline__ uint4 ld_relaxed4(const uint4* p) {
  uint4 v; asm volatile("ld.relaxed.gpu.global.v4.u32 {%0, %1, %2, %3}, [%4];" : "=r"(v.x), "=r"(v.y), "=r"(v.z), "=r"(v.w) : "l"(p) : "memory"); return v;
}
__device__ __forceinline__ void st_relaxed(unsigned* p, unsigned v) {
  asm volatile("st.relaxed.gpu.global.u32 [%0], %1;" ::"l"(p), "r"(v) : "memory");
}
__device__ __forceinline__ uint2 ld_relaxed2(const void* p) {
  uint2 v; asm volatile("ld.relaxed.gpu.global.v2.u32 {%0, %1}, [%2];" : "=r"(v.x), "=r"(v.y) : "l"(p) : "memory"); return v;
}
__device__ __forceinline__ void st_relaxed4(uint4* p, uint4 v) {
  asm volatile("st.relaxed.gpu.global.v4.u32 [%0], {%1, %2, %3, %4};" ::"l"(p), "r"(v.x), "r"(v.y), "r"(v.z), "r"(v.w) : "memory");
}
__device__ __forceinline__ bool valid4(uint4 v) { return v.x != SENT && v.y != SENT && v.z != SENT && v.w != SENT; }
__device__ __forceinline__ uint4 poll4(const uint4* p) {
  uint4 v;
  uint32_t spins = 0;
#pragma unroll 1
  do { v = ld_relaxed4(p); } while (!valid4(v) && ++spins < SPIN_LIMIT);
  return v;
}
__device__ __forceinline__ void set_flag(unsigned* p, unsigned tag) {
  asm volatile(ELECT "st.release.gpu.global.u32 [%0], %1;\n}" ::"l"(p), "r"(tag) : "memory");
}
__device__ __forceinline__ void poll_flag(const unsigned* p, unsigned tag) {
#pragma unroll 1
  for (uint32_t spins = 0; !__all_sync(0xffffffffu, ld_relaxed(p) == tag) && spins < SPIN_LIMIT; spins++) {}
  asm volatile("fence.acquire.gpu;" ::: "memory");
}
__device__ __forceinline__ uint32_t enc(float x) { return __float_as_uint(x + 0.0f) ^ 0x80000000u; }
__device__ __forceinline__ float dec(uint32_t u) { return __uint_as_float(u ^ 0x80000000u); }
__device__ __forceinline__ uint32_t f2u(float x) { uint32_t u = __float_as_uint(x); return u == SENT ? 0x7FFFFFFFu : u; }
__device__ __forceinline__ uint32_t nosent(uint32_t u) { return u == SENT ? 0x7FFF7FFFu : u; }
__device__ __forceinline__ uint32_t hadd_bf2(uint32_t a, uint32_t b) {
  uint32_t r; asm("add.rn.bf16x2 %0, %1, %2;" : "=r"(r) : "r"(a), "r"(b)); return r;
}
__device__ __forceinline__ uint32_t hsub_bf2(uint32_t a, uint32_t b) {
  uint32_t r; asm("sub.rn.bf16x2 %0, %1, %2;" : "=r"(r) : "r"(a), "r"(b)); return r;
}
__device__ __forceinline__ void wg_fence() { asm volatile("wgmma.fence.sync.aligned;" ::: "memory"); }
__device__ __forceinline__ void wg_commit() { asm volatile("wgmma.commit_group.sync.aligned;" ::: "memory"); }
template <int N> __device__ __forceinline__ void wg_wait() { asm volatile("wgmma.wait_group.sync.aligned %0;" ::"n"(N) : "memory"); }
template <int R> __device__ __forceinline__ void fence_regs(float* d) {
#pragma unroll
  for (int i = 0; i < R; i++) asm volatile("" : "+f"(d[i])::"memory");
}
template <int R> __device__ __forceinline__ void fence_regs_u(uint32_t* d) {
#pragma unroll
  for (int i = 0; i < R; i++) asm volatile("" : "+r"(d[i])::"memory");
}
__host__ __device__ constexpr uint32_t dlo(uint32_t addr, uint32_t lbo) { return ((addr & 0x3FFFF) >> 4) | ((lbo >> 4) << 16); }
constexpr uint32_t H128 = 0x40000040u, H64 = 0x80000020u;
__device__ __forceinline__ void stsm_x4(uint32_t addr, uint32_t r0, uint32_t r1, uint32_t r2, uint32_t r3) {
  asm volatile("stmatrix.sync.aligned.m8n8.x4.shared.b16 [%0], {%1, %2, %3, %4};"
               ::"r"(addr), "r"(r0), "r"(r1), "r"(r2), "r"(r3) : "memory");
}
__device__ __forceinline__ void ldsm_x4(uint32_t addr, uint32_t& r0, uint32_t& r1, uint32_t& r2, uint32_t& r3) {
  asm volatile("ldmatrix.sync.aligned.m8n8.x4.shared.b16 {%0, %1, %2, %3}, [%4];"
               : "=r"(r0), "=r"(r1), "=r"(r2), "=r"(r3) : "r"(addr) : "memory");
}
__device__ __forceinline__ void ldsm_x4_t(uint32_t addr, uint32_t& r0, uint32_t& r1, uint32_t& r2, uint32_t& r3) {
  asm volatile("ldmatrix.sync.aligned.m8n8.x4.trans.shared.b16 {%0, %1, %2, %3}, [%4];"
               : "=r"(r0), "=r"(r1), "=r"(r2), "=r"(r3) : "r"(addr) : "memory");
}
__device__ __forceinline__ void mma_16816(float* d, uint32_t a0, uint32_t a1, uint32_t a2, uint32_t a3, uint32_t b0, uint32_t b1) {
  asm volatile("mma.sync.aligned.m16n8k16.row.col.f32.bf16.bf16.f32 {%0, %1, %2, %3}, {%4, %5, %6, %7}, {%8, %9}, {%0, %1, %2, %3};"
               : "+f"(d[0]), "+f"(d[1]), "+f"(d[2]), "+f"(d[3]) : "r"(a0), "r"(a1), "r"(a2), "r"(a3), "r"(b0), "r"(b1));
}
__device__ __forceinline__ void spin_cycles(int n) {
  const int t0 = (int)clock();
#pragma unroll 1
  while ((int)clock() - t0 < n) {}
}
__device__ __forceinline__ uint32_t pack_bf16(float lo, float hi) {
  uint32_t r; asm("cvt.rn.bf16x2.f32 %0, %1, %2;" : "=r"(r) : "f"(hi), "f"(lo)); return r;
}
__device__ __forceinline__ float bf_lo(uint32_t v) { return __uint_as_float(v << 16); }
__device__ __forceinline__ float bf_hi(uint32_t v) { return __uint_as_float(v & 0xffff0000u); }
__device__ __forceinline__ float rbf(float x) { return __bfloat162float(__float2bfloat16_rn(x)); }
__device__ __forceinline__ float ex2(float x) { float y; asm("ex2.approx.ftz.f32 %0, %1;" : "=f"(y) : "f"(x)); return y; }
__device__ __forceinline__ uint32_t shl_clamp(uint32_t v, uint32_t n) {
  uint32_t r; asm("shl.b32 %0, %1, %2;" : "=r"(r) : "r"(v), "r"(n)); return r;
}
__device__ __forceinline__ float warp_sum(float v) {
#pragma unroll
  for (int o = 16; o > 0; o >>= 1) v += __shfl_xor_sync(0xffffffffu, v, o);
  return v;
}
__device__ __forceinline__ float ln_inv(float var) {
  float r;
  asm("sqrt.approx.ftz.f32 %0, %1;" : "=f"(r) : "f"(rbf(rbf(var) + LN_EPS)));
  asm("rcp.approx.ftz.f32 %0, %1;" : "=f"(r) : "f"(rbf(r)));
  return r;
}
__device__ __forceinline__ uint32_t ln_pair(uint32_t x, uint32_t mean2, float inv) {
  const uint32_t d = hsub_bf2(x, mean2);
  return pack_bf16(bf_lo(d) * inv, bf_hi(d) * inv);
}
__device__ __forceinline__ uint32_t add_ln_pair(uint32_t x, uint32_t mean2, float inv) { return hadd_bf2(x, ln_pair(x, mean2, inv)); }
__device__ __forceinline__ uint32_t router_key(float r_bf, int row) {
  uint32_t u = __float_as_uint(r_bf);
  u = (u & 0x80000000u) ? ~u : (u | 0x80000000u);
  return (u & 0xFFFF0000u) | 0x8000u | (uint32_t)(SEQ - 1 - row);
}

template <uint32_t HA = 0x40000040u, uint32_t HB = 0x40000040u>
__device__ __forceinline__ void wg_ss192t(float* d, uint32_t da, uint32_t db, int scale_d) {
  asm volatile("{\n.reg .pred p;\n.reg .b64 dA, dB;\nmov.b64 dA, {%96, %99};\nmov.b64 dB, {%97, %100};\nsetp.ne.b32 p, %98, 0;\n"
    "wgmma.mma_async.sync.aligned.m64n192k16.f32.bf16.bf16 "
    "{%0, %1, %2, %3, %4, %5, %6, %7, %8, %9, %10, %11, %12, %13, %14, %15, "
    "%16, %17, %18, %19, %20, %21, %22, %23, %24, %25, %26, %27, %28, %29, %30, %31, "
    "%32, %33, %34, %35, %36, %37, %38, %39, %40, %41, %42, %43, %44, %45, %46, %47, "
    "%48, %49, %50, %51, %52, %53, %54, %55, %56, %57, %58, %59, %60, %61, %62, %63, "
    "%64, %65, %66, %67, %68, %69, %70, %71, %72, %73, %74, %75, %76, %77, %78, %79, "
    "%80, %81, %82, %83, %84, %85, %86, %87, %88, %89, %90, %91, %92, %93, %94, %95}, "
    "dA, dB, p, 1, 1, 0, 1;\n}\n"
    : "+f"(d[0]), "+f"(d[1]), "+f"(d[2]), "+f"(d[3]), "+f"(d[4]), "+f"(d[5]), "+f"(d[6]), "+f"(d[7]),
      "+f"(d[8]), "+f"(d[9]), "+f"(d[10]), "+f"(d[11]), "+f"(d[12]), "+f"(d[13]), "+f"(d[14]), "+f"(d[15]),
      "+f"(d[16]), "+f"(d[17]), "+f"(d[18]), "+f"(d[19]), "+f"(d[20]), "+f"(d[21]), "+f"(d[22]), "+f"(d[23]),
      "+f"(d[24]), "+f"(d[25]), "+f"(d[26]), "+f"(d[27]), "+f"(d[28]), "+f"(d[29]), "+f"(d[30]), "+f"(d[31]),
      "+f"(d[32]), "+f"(d[33]), "+f"(d[34]), "+f"(d[35]), "+f"(d[36]), "+f"(d[37]), "+f"(d[38]), "+f"(d[39]),
      "+f"(d[40]), "+f"(d[41]), "+f"(d[42]), "+f"(d[43]), "+f"(d[44]), "+f"(d[45]), "+f"(d[46]), "+f"(d[47]),
      "+f"(d[48]), "+f"(d[49]), "+f"(d[50]), "+f"(d[51]), "+f"(d[52]), "+f"(d[53]), "+f"(d[54]), "+f"(d[55]),
      "+f"(d[56]), "+f"(d[57]), "+f"(d[58]), "+f"(d[59]), "+f"(d[60]), "+f"(d[61]), "+f"(d[62]), "+f"(d[63]),
      "+f"(d[64]), "+f"(d[65]), "+f"(d[66]), "+f"(d[67]), "+f"(d[68]), "+f"(d[69]), "+f"(d[70]), "+f"(d[71]),
      "+f"(d[72]), "+f"(d[73]), "+f"(d[74]), "+f"(d[75]), "+f"(d[76]), "+f"(d[77]), "+f"(d[78]), "+f"(d[79]),
      "+f"(d[80]), "+f"(d[81]), "+f"(d[82]), "+f"(d[83]), "+f"(d[84]), "+f"(d[85]), "+f"(d[86]), "+f"(d[87]),
      "+f"(d[88]), "+f"(d[89]), "+f"(d[90]), "+f"(d[91]), "+f"(d[92]), "+f"(d[93]), "+f"(d[94]), "+f"(d[95])
    : "r"(da), "r"(db), "r"(scale_d), "n"(HA), "n"(HB));
}
template <uint32_t HA = 0x40000040u, uint32_t HB = 0x40000040u>
__device__ __forceinline__ void wg_ss128t(float* d, uint32_t da, uint32_t db, int scale_d) {
  asm volatile("{\n.reg .pred p;\n.reg .b64 dA, dB;\nmov.b64 dA, {%64, %67};\nmov.b64 dB, {%65, %68};\nsetp.ne.b32 p, %66, 0;\n"
    "wgmma.mma_async.sync.aligned.m64n128k16.f32.bf16.bf16 "
    "{%0, %1, %2, %3, %4, %5, %6, %7, %8, %9, %10, %11, %12, %13, %14, %15, "
    "%16, %17, %18, %19, %20, %21, %22, %23, %24, %25, %26, %27, %28, %29, %30, %31, "
    "%32, %33, %34, %35, %36, %37, %38, %39, %40, %41, %42, %43, %44, %45, %46, %47, "
    "%48, %49, %50, %51, %52, %53, %54, %55, %56, %57, %58, %59, %60, %61, %62, %63}, "
    "dA, dB, p, 1, 1, 0, 1;\n}\n"
    : "+f"(d[0]), "+f"(d[1]), "+f"(d[2]), "+f"(d[3]), "+f"(d[4]), "+f"(d[5]), "+f"(d[6]), "+f"(d[7]),
      "+f"(d[8]), "+f"(d[9]), "+f"(d[10]), "+f"(d[11]), "+f"(d[12]), "+f"(d[13]), "+f"(d[14]), "+f"(d[15]),
      "+f"(d[16]), "+f"(d[17]), "+f"(d[18]), "+f"(d[19]), "+f"(d[20]), "+f"(d[21]), "+f"(d[22]), "+f"(d[23]),
      "+f"(d[24]), "+f"(d[25]), "+f"(d[26]), "+f"(d[27]), "+f"(d[28]), "+f"(d[29]), "+f"(d[30]), "+f"(d[31]),
      "+f"(d[32]), "+f"(d[33]), "+f"(d[34]), "+f"(d[35]), "+f"(d[36]), "+f"(d[37]), "+f"(d[38]), "+f"(d[39]),
      "+f"(d[40]), "+f"(d[41]), "+f"(d[42]), "+f"(d[43]), "+f"(d[44]), "+f"(d[45]), "+f"(d[46]), "+f"(d[47]),
      "+f"(d[48]), "+f"(d[49]), "+f"(d[50]), "+f"(d[51]), "+f"(d[52]), "+f"(d[53]), "+f"(d[54]), "+f"(d[55]),
      "+f"(d[56]), "+f"(d[57]), "+f"(d[58]), "+f"(d[59]), "+f"(d[60]), "+f"(d[61]), "+f"(d[62]), "+f"(d[63])
    : "r"(da), "r"(db), "r"(scale_d), "n"(HA), "n"(HB));
}
template <uint32_t HB = 0x40000040u>
__device__ __forceinline__ void wg_rs64(float* d, uint32_t a0, uint32_t a1, uint32_t a2, uint32_t a3, uint32_t db, int scale_d) {
  asm volatile("{\n.reg .pred p;\n.reg .b64 dB;\nmov.b64 dB, {%36, %38};\nsetp.ne.b32 p, %37, 0;\n"
    "wgmma.mma_async.sync.aligned.m64n64k16.f32.bf16.bf16 "
    "{%0, %1, %2, %3, %4, %5, %6, %7, %8, %9, %10, %11, %12, %13, %14, %15, "
    "%16, %17, %18, %19, %20, %21, %22, %23, %24, %25, %26, %27, %28, %29, %30, %31}, "
    "{%32, %33, %34, %35}, dB, p, 1, 1, 0;\n}\n"
    : "+f"(d[0]), "+f"(d[1]), "+f"(d[2]), "+f"(d[3]), "+f"(d[4]), "+f"(d[5]), "+f"(d[6]), "+f"(d[7]),
      "+f"(d[8]), "+f"(d[9]), "+f"(d[10]), "+f"(d[11]), "+f"(d[12]), "+f"(d[13]), "+f"(d[14]), "+f"(d[15]),
      "+f"(d[16]), "+f"(d[17]), "+f"(d[18]), "+f"(d[19]), "+f"(d[20]), "+f"(d[21]), "+f"(d[22]), "+f"(d[23]),
      "+f"(d[24]), "+f"(d[25]), "+f"(d[26]), "+f"(d[27]), "+f"(d[28]), "+f"(d[29]), "+f"(d[30]), "+f"(d[31])
    : "r"(a0), "r"(a1), "r"(a2), "r"(a3), "r"(db), "r"(scale_d), "n"(HB));
}
template <uint32_t HB = 0x40000040u>
__device__ __forceinline__ void wg_rs64_z(float* d, uint32_t a0, uint32_t a1, uint32_t a2, uint32_t a3, uint32_t db) {
  asm volatile("{\n.reg .pred p;\n.reg .b64 dB;\nmov.b64 dB, {%36, %37};\nsetp.ne.b32 p, 0, 0;\n"
    "wgmma.mma_async.sync.aligned.m64n64k16.f32.bf16.bf16 "
    "{%0, %1, %2, %3, %4, %5, %6, %7, %8, %9, %10, %11, %12, %13, %14, %15, "
    "%16, %17, %18, %19, %20, %21, %22, %23, %24, %25, %26, %27, %28, %29, %30, %31}, "
    "{%32, %33, %34, %35}, dB, p, 1, 1, 0;\n}\n"
    : "=f"(d[0]), "=f"(d[1]), "=f"(d[2]), "=f"(d[3]), "=f"(d[4]), "=f"(d[5]), "=f"(d[6]), "=f"(d[7]),
      "=f"(d[8]), "=f"(d[9]), "=f"(d[10]), "=f"(d[11]), "=f"(d[12]), "=f"(d[13]), "=f"(d[14]), "=f"(d[15]),
      "=f"(d[16]), "=f"(d[17]), "=f"(d[18]), "=f"(d[19]), "=f"(d[20]), "=f"(d[21]), "=f"(d[22]), "=f"(d[23]),
      "=f"(d[24]), "=f"(d[25]), "=f"(d[26]), "=f"(d[27]), "=f"(d[28]), "=f"(d[29]), "=f"(d[30]), "=f"(d[31])
    : "r"(a0), "r"(a1), "r"(a2), "r"(a3), "r"(db), "n"(HB));
}
template <uint32_t HB = 0x40000040u>
__device__ __forceinline__ void wg_rs32(float* d, uint32_t a0, uint32_t a1, uint32_t a2, uint32_t a3, uint32_t db, int scale_d) {
  asm volatile("{\n.reg .pred p;\n.reg .b64 dB;\nmov.b64 dB, {%20, %22};\nsetp.ne.b32 p, %21, 0;\n"
    "wgmma.mma_async.sync.aligned.m64n32k16.f32.bf16.bf16 "
    "{%0, %1, %2, %3, %4, %5, %6, %7, %8, %9, %10, %11, %12, %13, %14, %15}, "
    "{%16, %17, %18, %19}, dB, p, 1, 1, 0;\n}\n"
    : "+f"(d[0]), "+f"(d[1]), "+f"(d[2]), "+f"(d[3]), "+f"(d[4]), "+f"(d[5]), "+f"(d[6]), "+f"(d[7]),
      "+f"(d[8]), "+f"(d[9]), "+f"(d[10]), "+f"(d[11]), "+f"(d[12]), "+f"(d[13]), "+f"(d[14]), "+f"(d[15])
    : "r"(a0), "r"(a1), "r"(a2), "r"(a3), "r"(db), "r"(scale_d), "n"(HB));
}
template <uint32_t HB = 0x40000040u>
__device__ __forceinline__ void wg_rs32_z(float* d, uint32_t a0, uint32_t a1, uint32_t a2, uint32_t a3, uint32_t db) {
  asm volatile("{\n.reg .pred p;\n.reg .b64 dB;\nmov.b64 dB, {%20, %21};\nsetp.ne.b32 p, 0, 0;\n"
    "wgmma.mma_async.sync.aligned.m64n32k16.f32.bf16.bf16 "
    "{%0, %1, %2, %3, %4, %5, %6, %7, %8, %9, %10, %11, %12, %13, %14, %15}, "
    "{%16, %17, %18, %19}, dB, p, 1, 1, 0;\n}\n"
    : "=f"(d[0]), "=f"(d[1]), "=f"(d[2]), "=f"(d[3]), "=f"(d[4]), "=f"(d[5]), "=f"(d[6]), "=f"(d[7]),
      "=f"(d[8]), "=f"(d[9]), "=f"(d[10]), "=f"(d[11]), "=f"(d[12]), "=f"(d[13]), "=f"(d[14]), "=f"(d[15])
    : "r"(a0), "r"(a1), "r"(a2), "r"(a3), "r"(db), "n"(HB));
}
template <uint32_t HB = 0x40000040u>
__device__ __forceinline__ void wg_rs40t(float* d, uint32_t a0, uint32_t a1, uint32_t a2, uint32_t a3, uint32_t db, int scale_d) {
  asm volatile("{\n.reg .pred p;\n.reg .b64 dB;\nmov.b64 dB, {%24, %26};\nsetp.ne.b32 p, %25, 0;\n"
    "wgmma.mma_async.sync.aligned.m64n40k16.f32.bf16.bf16 "
    "{%0, %1, %2, %3, %4, %5, %6, %7, %8, %9, %10, %11, %12, %13, %14, %15, "
    "%16, %17, %18, %19}, "
    "{%20, %21, %22, %23}, dB, p, 1, 1, 1;\n}\n"
    : "+f"(d[0]), "+f"(d[1]), "+f"(d[2]), "+f"(d[3]), "+f"(d[4]), "+f"(d[5]), "+f"(d[6]), "+f"(d[7]),
      "+f"(d[8]), "+f"(d[9]), "+f"(d[10]), "+f"(d[11]), "+f"(d[12]), "+f"(d[13]), "+f"(d[14]), "+f"(d[15]),
      "+f"(d[16]), "+f"(d[17]), "+f"(d[18]), "+f"(d[19])
    : "r"(a0), "r"(a1), "r"(a2), "r"(a3), "r"(db), "r"(scale_d), "n"(HB));
}
template <uint32_t HB = 0x40000040u>
__device__ __forceinline__ void wg_rs40t_z(float* d, uint32_t a0, uint32_t a1, uint32_t a2, uint32_t a3, uint32_t db) {
  asm volatile("{\n.reg .pred p;\n.reg .b64 dB;\nmov.b64 dB, {%24, %25};\nsetp.ne.b32 p, 0, 0;\n"
    "wgmma.mma_async.sync.aligned.m64n40k16.f32.bf16.bf16 "
    "{%0, %1, %2, %3, %4, %5, %6, %7, %8, %9, %10, %11, %12, %13, %14, %15, "
    "%16, %17, %18, %19}, "
    "{%20, %21, %22, %23}, dB, p, 1, 1, 1;\n}\n"
    : "=f"(d[0]), "=f"(d[1]), "=f"(d[2]), "=f"(d[3]), "=f"(d[4]), "=f"(d[5]), "=f"(d[6]), "=f"(d[7]),
      "=f"(d[8]), "=f"(d[9]), "=f"(d[10]), "=f"(d[11]), "=f"(d[12]), "=f"(d[13]), "=f"(d[14]), "=f"(d[15]),
      "=f"(d[16]), "=f"(d[17]), "=f"(d[18]), "=f"(d[19])
    : "r"(a0), "r"(a1), "r"(a2), "r"(a3), "r"(db), "n"(HB));
}

constexpr uint32_t SOFF = 1024;
constexpr int STG = 57344, SL_W = 32768, SL_HD = 12288, SL_F = 3 * STG, AT_ST = 131072;
constexpr int OFF_ONES = 4 * STG;
constexpr int OFF_PATCH = OFF_ONES + 1024;
constexpr int OFF_CS = OFF_PATCH + 896;
constexpr int OFF_BAR = OFF_CS + 768;
constexpr int OFF_MISC = OFF_BAR + 304;
constexpr int SMEM_BYTES = OFF_MISC + 80;
enum { B_FULL = 0, B_EMPTY = 3, B_HALO = 6, B_CS = 9, B_KVREADY, B_QDONE = B_KVREADY + 2, B_QREADY, B_OST, B_ADONE = B_OST + 2,
       B_QFREE, B_WS, B_WFULL, B_WEMPTY = B_WFULL + 4, B_GU = B_WEMPTY + 4, B_GUFREE = B_GU + 3, B_RES, B_DN,
       B_HX = B_DN + 2, B_RST, B_WGO, B_COUNT = B_WGO + 2 };
static_assert(B_COUNT <= 38, "barrier area");
__host__ __device__ constexpr int bar_count(int i) {
  return i >= B_EMPTY && i < B_HALO ? 17 : i == B_CS ? 4 : i == B_QFREE ? 16
       : i == B_KVREADY || i == B_KVREADY + 1 || i == B_QREADY || i == B_ADONE ? 8 : i == B_OST ? 32
       : i == B_QDONE || i == B_OST + 1 || (i >= B_WEMPTY && i < B_GU) ? 16 : i == B_GUFREE ? 7 : i == B_RST ? 4 : i == B_RES ? 2 : 1;
}
enum { M_KEY = 0, M_MEAN, M_INV, M_WSUM, M_TAG, M_SEL0, M_XQ = 8, M_KEYS = 12 };
constexpr int FFN_PIECE = 14336;
constexpr int T_XS = 163840, T_HP = OFF_PATCH;
constexpr int HELP_GR = 8;
constexpr float LSUM_MIN = 5.421010862427522e-20f, LSUM_MAX = 1.8446744073709552e19f;
constexpr float SM_C = 0.17677669529663687f * 1.4426950408889634f;
constexpr uint32_t VSTEP = 64u - (64u << 16);
#define FFN_POL policy_evict_first()
#define D_SPLIT 1
#define PF_MODE 5
#define GUA_AT 2
#define GUB_PACE 1000
#define RES_K 3
#define REL_NOW 0
#define FAKE 0
#define X_STAGGER 500
#define GU_PACE1 1800
#define POLL_GAP 0
#define A1_LATE 0
#define WG_FLIP 384
#define GU_PACE 2500
#define DELAY_P 600
#define DELAY_S 2000
#define DELAY_Y 700

struct Params {
  CUtensorMap mapA[2], mapW, mapWo, mapRes[2], mapXst[2], mapG, mapU, mapD;
  const bf16 *x, *wqkv, *wo, *w_r, *w_g, *w_u, *w_d;
  bf16* out;
  int helper_first;
};

template <int N> __device__ __forceinline__ void exp_pack(const float* s, uint32_t* p) {
#pragma unroll
  for (int b = 0; b < N; b++) {
    p[2 * b] = pack_bf16(ex2(s[4 * b]), ex2(s[4 * b + 1]));
    p[2 * b + 1] = pack_bf16(ex2(s[4 * b + 2]), ex2(s[4 * b + 3]));
  }
}
template <int KIND> __device__ __forceinline__ void edge16(const float* sd, const float* st, uint32_t* pd, uint32_t* pt, int dl, uint32_t mt) {
  if (KIND == 0) { exp_pack<2>(sd, pd); pt[0] = pt[1] = pt[2] = pt[3] = 0; }
  else if (KIND == 1) { exp_pack<2>(st, pt); pd[0] = pd[1] = pd[2] = pd[3] = 0; }
  else {
    const uint32_t a = pack_bf16(ex2(dl >= 0 ? sd[0] : st[0]), ex2(dl >= 1 ? sd[1] : st[1]));
    const uint32_t c = pack_bf16(ex2(dl >= 0 ? sd[6] : st[6]), ex2(dl >= 1 ? sd[7] : st[7]));
    pd[0] = a & ~mt; pt[0] = a & mt; pd[3] = c & ~mt; pt[3] = c & mt;
    pd[1] = pack_bf16(ex2(sd[2]), ex2(sd[3])); pt[1] = 0;
    pt[2] = pack_bf16(ex2(st[4]), ex2(st[5])); pd[2] = 0;
  }
}
__device__ __forceinline__ void mix_exp(const float* sm, const float* sd, const float* st, uint32_t* p, int rel, int dl, uint32_t mt) {
  uint32_t *pd = p + 8, *pt = p + 16;
  if (rel > 1) { edge16<0>(sd, st, pd, pt, dl, mt); edge16<0>(sd + 8, st + 8, pd + 4, pt + 4, dl, mt); }
  else if (rel == 1) { edge16<0>(sd, st, pd, pt, dl, mt); edge16<2>(sd + 8, st + 8, pd + 4, pt + 4, dl, mt); }
  else if (rel == 0) { edge16<2>(sd, st, pd, pt, dl, mt); edge16<1>(sd + 8, st + 8, pd + 4, pt + 4, dl, mt); }
  else { edge16<1>(sd, st, pd, pt, dl, mt); edge16<1>(sd + 8, st + 8, pd + 4, pt + 4, dl, mt); }
  exp_pack<4>(sm, p);
}
__device__ __forceinline__ void qk64(float* s, const uint32_t* qf, uint32_t kd) {
  wg_rs64_z<H64>(s, qf[0], qf[1], qf[2], qf[3], kd);
  wg_rs64<H64>(s, qf[4], qf[5], qf[6], qf[7], kd + 2, 1);
}
__device__ __forceinline__ void qk32x3(float* a, float* b, float* c, const uint32_t* qf, uint32_t ka, uint32_t kb, uint32_t kc) {
  wg_rs32_z<H64>(a, qf[0], qf[1], qf[2], qf[3], ka); wg_rs32_z<H64>(b, qf[0], qf[1], qf[2], qf[3], kb); wg_rs32_z<H64>(c, qf[0], qf[1], qf[2], qf[3], kc);
  wg_rs32<H64>(a, qf[4], qf[5], qf[6], qf[7], ka + 2, 1); wg_rs32<H64>(b, qf[4], qf[5], qf[6], qf[7], kb + 2, 1); wg_rs32<H64>(c, qf[4], qf[5], qf[6], qf[7], kc + 2, 1);
}
__device__ __forceinline__ void pv32(float* o, const uint32_t* p, uint32_t vd) {
  wg_rs40t<H64>(o, p[0], p[1], p[2], p[3], vd, 1);
  wg_rs40t<H64>(o, p[4], p[5], p[6], p[7], vd + VSTEP, 1);
}

__device__ __forceinline__ void fma8(float* d, uint4 w, float x) {
  d[0] += x * bf_lo(w.x); d[1] += x * bf_hi(w.x); d[2] += x * bf_lo(w.y); d[3] += x * bf_hi(w.y);
  d[4] += x * bf_lo(w.z); d[5] += x * bf_hi(w.z); d[6] += x * bf_lo(w.w); d[7] += x * bf_hi(w.w);
}

__device__ __forceinline__ int fresh_tid() { int r; asm volatile("mov.u32 %0, %%tid.x;" : "=r"(r)); return r ^ WG_FLIP; }
__device__ __forceinline__ int fresh_bid() { int r; asm volatile("mov.u32 %0, %%ctaid.x;" : "=r"(r)); return r; }
#define PHASE_IDS                                                                                                              \
  const uint32_t sbase = smem_u32(smem);                                                                                       \
  const int tid = fresh_tid(), bid = fresh_bid();                                                                              \
  const int warp = __shfl_sync(0xffffffffu, tid >> 5, 0), lane = tid & 31;                                                     \
  const int rank = bid & 1, cl = bid >> 1, rb = bid & 7, hp = bid >> 3;                  \
  const int mb = 2 * rb + (hp >> 3), nb = hp & 7;                                            \
  const int wg = warp >> 2, wi = warp & 3, g = lane >> 2, q = lane & 3;                                                        \
  const int mi = lane >> 3, srow = wi * 16 + (mi & 1) * 8 + (lane & 7);      \
  auto bar = [&](int i) { return sbase + OFF_BAR + 8 * i; };                                                                   \
  volatile uint32_t* s_misc = (volatile uint32_t*)(smem + OFF_MISC);                                                           \
  auto load_w = [&](int s, int kt) {                           \
    tma_load3_mc(sbase + s * STG + SL_W + rank * SL_HD, &P.mapW, hp * 64, kt * 64 + rank * 32, 0, bar(B_FULL + s));            \
  };                                                                                                                           \
  auto load_a = [&](int s, int kt, int layer) { mbar_expect_tx(bar(B_FULL + s), STG); tma_load2(sbase + s * STG, &P.mapA[layer], kt * 64, rb * 256, bar(B_FULL + s)); }; \
  auto load_wo = [&](int k) {                                                 \
    mbar_expect_tx(bar(B_WFULL + (k & 3)), 32768);                                                                             \
    tma_load3_mc(sbase + (k & 3) * 32768 + 16384 + rank * 8192, &P.mapWo, nb * 128 + rank * 64, (k >> 3) * 32, (k & 7) * 2, bar(B_WFULL + (k & 3))); \
  };                                                                                                                           \
  auto load_o = [&](int k) {                                                            \
    bulk_load(sbase + (k & 3) * 32768, g_o + (size_t)(mb * 16 + k) * 16384, 16384, bar(B_WFULL + (k & 3)));                    \
  };                                                                                                                           \
  auto load_res = [&](int half, int layer) {                                                  \
    mbar_expect_tx(bar(B_RES), 16384);                                                                                         \
    tma_load2(sbase + AT_ST + half * 16384, &P.mapRes[layer], nb * 128, mb * 128 + half * 64, bar(B_RES));                     \
    tma_load2(sbase + AT_ST + half * 16384 + 8192, &P.mapRes[layer], nb * 128 + 64, mb * 128 + half * 64, bar(B_RES));         \
  };                                                                                                                           \
  auto store_tile = [&](int layer, int skip) {                                                     \
    _Pragma("unroll 1")                                                                                                        \
    for (int j = 0; j < 4; j++)                                                                                                \
      if ((j & 1) != skip) tma_store(&P.mapXst[layer], sbase + AT_ST + (j & 1) * 16384 + (j >> 1) * 8192, nb * 128 + (j >> 1) * 64, mb * 128 + (j & 1) * 64); \
    bulk_commit();                                                                                                             \
    bulk_wait_all();                                                                                                           \
  };                                                                                                                           \
                                    \
  auto fetch_gu = [&](uint32_t* gu, int half, int ct) {                                                                        \
    _Pragma("unroll")                                                                                                          \
    for (int j = 0; j < 8; j++)                                                                                                \
      ldsm_x4_t(sbase + SL_F + (half * 2 + (mi & 1)) * FFN_PIECE + (j * 16 + (mi >> 1) * 8 + (lane & 7)) * 112 + ct * 16,      \
                gu[4 * j], gu[4 * j + 1], gu[4 * j + 2], gu[4 * j + 3]);                                                       \
    fence_regs_u<32>(gu);                                                                                                      \
  };                                                                                                                           \
            \
  auto gemv_gu = [&](const uint32_t* gu, int x0, int x1, int ct, int part) {                                                   \
    const int u = 8 * ct + g, own = u >= 28;                                                                                   \
    const uint32_t dst = mapa(sbase + T_HP + ((rank * 2 + part) * 28 + u - 28 * own) * 8, own), dbar = mapa(bar(B_HX), own);   \
    uint4 xv[8] = {};                                                                                                          \
    named_bar(7, 512);                                                                                   \
    if (g == 0) {                                                                                                              \
      _Pragma("unroll")                                                                                                        \
      for (int j = 0; j < 8; j++) xv[j] = ((const uint4*)(smem + T_XS))[((j & 1) ? x1 : x0) + (j >> 1) * 4 + q];               \
    }                                                                                                                          \
    __syncwarp();                                                                                                              \
    float d[4][4] = {};                                                                                                        \
    _Pragma("unroll")                                                                                                          \
    for (int j = 0; j < 4; j++) {                                                                                              \
      const uint4 xa = xv[2 * j], xb = xv[2 * j + 1];                                                                          \
      const uint32_t *a = gu + 8 * j, *b = a + 32;                                                                             \
      mma_16816(d[0], a[0], a[1], a[2], a[3], xa.x, xa.y); mma_16816(d[1], a[4], a[5], a[6], a[7], xa.z, xa.w);                \
      mma_16816(d[2], b[0], b[1], b[2], b[3], xb.x, xb.y); mma_16816(d[3], b[4], b[5], b[6], b[7], xb.z, xb.w);                \
    }                                                                                                                          \
    if (q == 0) st_async2(dst, (d[0][0] + d[1][0]) + (d[2][0] + d[3][0]), (d[0][2] + d[1][2]) + (d[2][2] + d[3][2]), dbar);    \
    __syncwarp();                                                                                                              \
  };                                                                                                                           \
  auto hidden = [&]() {                                     \
    const float2* hpart = (const float2*)(smem + T_HP) + min(lane, 27);                                                        \
    const float2 v0 = hpart[0], v1 = hpart[28], v2 = hpart[56], v3 = hpart[84];                                                \
    const float gb = rbf((v0.x + v1.x) + (v2.x + v3.x)), ub = rbf((v0.y + v1.y) + (v2.y + v3.y));                              \
    return lane < 28 ? rbf(__fdividef(gb, 1.f + __expf(-gb))) * ub : 0.f;                                                      \
  };                                                                                                                           \
  (void)load_wo; (void)load_o; (void)load_res; (void)store_tile; (void)fetch_gu; (void)gemv_gu; (void)hidden; (void)cl; (void)mb; (void)nb; (void)wg; (void)g; (void)q; (void)srow; (void)s_misc; (void)load_w; (void)load_a;

__global__ void __launch_bounds__(512, 1) mega_kernel(const __grid_constant__ Params P) {
  extern __shared__ __align__(1024) uint8_t smem[];
  if ((int)blockIdx.x < P.helper_first) {
    PHASE_IDS
    if (warp == 0) {
      if (lane == 0) {
        prefetch_tmap(&P.mapA[0]); prefetch_tmap(&P.mapW);
#pragma unroll
        for (int i = 0; i < 3; i++) mbar_init(bar(B_FULL + i), 1);
        asm volatile("fence.mbarrier_init.release.cluster;" ::: "memory");
      }
      __syncwarp();
      load_a(0, 0, 0);
    } else if (tid == 32) {
#pragma unroll
      for (int i = 3; i < B_COUNT; i++) mbar_init(bar(i), bar_count(i));
      asm volatile("fence.mbarrier_init.release.cluster;" ::: "memory");
    } else if (warp == 8) {
      ((uint4*)(smem + OFF_ONES))[lane] = make_uint4(0x3F803F80u, 0x3F803F80u, 0x3F803F80u, 0x3F803F80u);
      ((uint4*)(smem + OFF_ONES))[lane + 32] = make_uint4(0x3F803F80u, 0x3F803F80u, 0x3F803F80u, 0x3F803F80u);
    }
    __syncwarp();
    cluster_arrive(); cluster_wait();
    if (warp == 0) {
#pragma unroll 1
      for (int i = 0; i < 3; i++) { load_w(i, i); if (i) load_a(i, i, 0); }
      PROFL(0, 1);
    } else if (warp == 1) {
      if (lane < 16) g_rowab[0][rb * 256 + hp * 16 + lane] = make_uint4(0, 0, 0, 0);
    } else if (warp == 2) {
      const int f = lane >> 1;
      Flag* fl = f < 3 ? &g_kvflag[rb >> 1][hp][f] : f < 5 ? &g_oflag[rb][f & 1][hp] : &g_xflag[mb][nb];
      if (f < 6 && (f >= 3 || (rank == 1 && rb < 7))) ((uint4*)fl)[lane & 1] = make_uint4(0, 0, 0, 0);
    } else if (tid == 96) {
      if ((sbase & 0x3FFFF) != SOFF) __trap();
#pragma unroll 1
      for (int i = 1; i < 11; i++) prefetch_tmap(&P.mapA[0] + i);
    }
    __syncwarp();
  } else {
    const uint32_t sbase = smem_u32(smem);
    const int tid = threadIdx.x, warp = __shfl_sync(0xffffffffu, tid >> 5, 0), lane = tid & 31;
    const int hid = blockIdx.x - P.helper_first;
    constexpr int GR = HELP_GR, NG = 36 / GR, GB = GR * 6144, NGRP = 256 / GR;
    const uint32_t hfull = sbase + NG * GB, hempty = hfull + 8 * NG;
    if (tid == 0) {
      for (int i = 0; i < NG; i++) { mbar_init(hfull + 8 * i, 1); mbar_init(hempty + 8 * i, 12); }
      asm volatile("fence.mbarrier_init.release.cluster;" ::: "memory");
    }
    __syncthreads();
    const uint8_t* wsrc = (const uint8_t*)P.wqkv + (size_t)hid * 256 * 6144;
    if (warp == 12) {
#pragma unroll 1
      for (int gI = 0; gI < NGRP; gI++) {
        const int sl = gI % NG;
        if (gI >= NG) mbar_wait(hempty + 8 * sl, ((gI / NG) & 1) ^ 1);
        mbar_expect_tx(hfull + 8 * sl, GB);
        bulk_load(sbase + sl * GB, wsrc + (size_t)gI * GB, GB, hfull + 8 * sl);
      }
    } else if (warp < 12) {
      float cs8[8] = {0, 0, 0, 0, 0, 0, 0, 0};
#pragma unroll 1
      for (int gI = 0; gI < NGRP; gI++) {
        const int sl = gI % NG;
        mbar_wait(hfull + 8 * sl, (gI / NG) & 1);
#pragma unroll
        for (int i = 0; i < GR; i++) {
          const uint4 v = *(const uint4*)(smem + sl * GB + i * 6144 + tid * 16);
          cs8[0] += bf_lo(v.x); cs8[1] += bf_hi(v.x); cs8[2] += bf_lo(v.y); cs8[3] += bf_hi(v.y);
          cs8[4] += bf_lo(v.z); cs8[5] += bf_hi(v.z); cs8[6] += bf_lo(v.w); cs8[7] += bf_hi(v.w);
        }
        __syncwarp();
        if (lane == 0) mbar_arrive(hempty + 8 * sl);
      }
      uint4* dst = (uint4*)&g_cspart[hid][tid * 8];
      st_relaxed4(dst, make_uint4(enc(cs8[0]), enc(cs8[1]), enc(cs8[2]), enc(cs8[3])));
      st_relaxed4(dst + 1, make_uint4(enc(cs8[4]), enc(cs8[5]), enc(cs8[6]), enc(cs8[7])));
    }
    return;
  }

#pragma unroll 1
  for (unsigned pass_v = 0;;) {
    const unsigned pass = __shfl_sync(0xffffffffu, pass_v, 0);
    if (__shfl_sync(0xffffffffu, fresh_tid() >> 8, 0)) {
      if (pass > 0) {
        const unsigned layer = pass - 1;
        uint32_t xr[32];
        {
          PHASE_IDS
          if (warp == 14) {
            poll_flag(&g_oflag[rb][0][lane & 15].v[layer], s_misc[M_TAG]);
            fence_async_global();
            PROF(15);
            load_o(0); load_o(1);
            mbar_arrive_e(bar(B_WGO));
          }
          float acc[64];
#pragma unroll
          for (int i = 0; i < 64; i++) acc[i] = 0.f;
          const uint32_t da0 = dlo(SOFF, 16) + (wg - 2) * 256;
          constexpr uint32_t db0 = dlo(SOFF + 16384, 8192);
#pragma unroll 1
          for (int k4 = 0; k4 < 4; k4++) {
#pragma unroll
            for (int st = 0; st < 4; st++) {
              mbar_wait(bar(B_WFULL + st), k4 & 1);
              wg_fence();
#pragma unroll
              for (int kk = 0; kk < 4; kk++)
                wg_ss128t<H64, H128>(acc, da0 + ((st * 32768) >> 4) + (kk >> 1) * 512 + (kk & 1) * 2, db0 + ((st * 32768) >> 4) + kk * 128, 1);
              wg_commit();
              if (st == 0 && k4 == 0 && warp == 9) PROF(10);
              if (st & 1) STEPT(24 + k4 * 2 + (st >> 1));
              if (REL_NOW) {
                if (st < 3 || k4 < 3) wg_wait<0>();
                if (lane < 2 && (st < 2 || k4 < 3)) mbar_arrive_cluster(bar(B_WEMPTY + st), lane);
              } else {
                wg_wait<1>();
                if (lane < 2 && (st == 0 ? k4 > 0 : (st < 3 || k4 < 3))) mbar_arrive_cluster(bar(B_WEMPTY + ((st + 3) & 3)), lane);
              }
            }
          }
          mbar_wait(bar(B_RES), layer);
          mbar_wait(bar(B_RST), layer);
          const uint32_t zoff = AT_ST + (wg - 2) * 16384;
#pragma unroll
          for (int j = 0; j < 8; j++)
            ldsm_x4(sbase + zoff + srow * 128 + (j >> 2) * 8192 + ((((2 * j + (mi >> 1)) & 7) ^ (srow & 7)) << 4), xr[4 * j], xr[4 * j + 1], xr[4 * j + 2], xr[4 * j + 3]);
          wg_wait<0>();
          fence_regs<64>(acc);
          if (warp == 9) PROF(11);
          if (layer == 0 && lane < 2) mbar_arrive_cluster(bar(B_QFREE), lane);
#pragma unroll
          for (int j = 0; j < 32; j++) xr[j] = hadd_bf2(xr[j], pack_bf16(acc[2 * j], acc[2 * j + 1]));
        }
        PHASE_IDS
        const uint32_t tag = s_misc[M_TAG];
        const int grow = mb * 128 + (warp - 8) * 16 + g;
        {
          float d[6][4];
#pragma unroll
          for (int i = 0; i < 6; i++) d[i][0] = d[i][1] = d[i][2] = d[i][3] = 0.f;
          const uint4* tab = (const uint4*)(smem + OFF_PATCH + (g == 1 ? q * 64 : (g == 0 ? 256 : 320)));
#pragma unroll
          for (int j2 = 0; j2 < 4; j2++) {
            const uint4 w = tab[j2];
#pragma unroll
            for (int jj = 0; jj < 2; jj++) {
              const uint32_t* a = &xr[8 * j2 + 4 * jj];
              mma_16816(d[jj], a[0], a[1], a[2], a[3], jj ? w.z : w.x, jj ? w.w : w.y);
              mma_16816(d[2 + jj], a[0], a[1], a[2], a[3], a[0], a[2]);
              mma_16816(d[4 + jj], a[0], a[1], a[2], a[3], a[1], a[3]);
            }
          }
          const float sq0 = __shfl_sync(0xffffffffu, (g & 1) ? d[2][1] + d[3][1] : d[2][0] + d[3][0], g * 4 + (g >> 1));
          const float sq1 = __shfl_sync(0xffffffffu, (g & 1) ? d[4][3] + d[5][3] : d[4][2] + d[5][2], g * 4 + (g >> 1));
          uint4* dst = &g_part[layer][nb * SEQ + grow];
          if (q == 0) {
            st_relaxed4(dst, make_uint4(__float_as_uint(d[0][0] + d[1][0]), __float_as_uint(sq0), __float_as_uint(d[0][1] + d[1][1]), tag));
            st_relaxed4(dst + 8, make_uint4(__float_as_uint(d[0][2] + d[1][2]), __float_as_uint(sq1), __float_as_uint(d[0][3] + d[1][3]), tag));
          }
        }
        if (warp == 9) PROF(12);
        asm volatile("bar.arrive 6, 288;" ::: "memory");
        const int t_p = (int)clock();
        const uint32_t zrow = sbase + AT_ST + (wg - 2) * 16384 + srow * 128;
        if (layer == 0) {
#pragma unroll
          for (int j = 0; j < 8; j++)
            stsm_x4(zrow + (j >> 2) * 8192 + ((((2 * j + (mi >> 1)) & 7) ^ (srow & 7)) << 4), xr[4 * j], xr[4 * j + 1], xr[4 * j + 2], xr[4 * j + 3]);
          fence_async_smem();
          asm volatile("bar.arrive 8, 288;" ::: "memory");
        }
#pragma unroll 1
        while ((int)clock() - t_p < DELAY_P) {}
        {
          const uint4* src = &g_part[layer][2 * q * SEQ + grow];
          uint4 pp[4];
          uint32_t spins = 0;
#pragma unroll 1
          do {
            pp[0] = ld_relaxed4(src); pp[1] = ld_relaxed4(src + SEQ); pp[2] = ld_relaxed4(src + 8); pp[3] = ld_relaxed4(src + SEQ + 8);
          } while (!__all_sync(0xffffffffu, pp[0].w == tag && pp[1].w == tag && pp[2].w == tag && pp[3].w == tag) && ++spins < SPIN_LIMIT);
          if (warp == 9) PROF(13);
          const int rr = q >> 1;
          float s3[3];
#pragma unroll
          for (int c = 0; c < 3; c++) {
            const float lo = __uint_as_float(c == 0 ? pp[0].x : c == 1 ? pp[0].y : pp[0].z) + __uint_as_float(c == 0 ? pp[1].x : c == 1 ? pp[1].y : pp[1].z);
            const float hi = __uint_as_float(c == 0 ? pp[2].x : c == 1 ? pp[2].y : pp[2].z) + __uint_as_float(c == 0 ? pp[3].x : c == 1 ? pp[3].y : pp[3].z);
            s3[c] = (rr ? hi : lo) + __shfl_xor_sync(0xffffffffu, rr ? lo : hi, 2);
            s3[c] += __shfl_xor_sync(0xffffffffu, s3[c], 1);
          }
          const float mu = s3[0] * (1.f / DM), var = fmaxf(fmaf(-mu, mu, s3[1] * (1.f / DM)), 0.f);
          const float mn = rbf(mu), iv = ln_inv(var);
          const uint32_t ky = router_key(rbf((s3[2] - mn * __uint_as_float(s_misc[M_WSUM])) * iv), grow + 8 * rr);
          const uint32_t wbest = __reduce_max_sync(0xffffffffu, ky);
          s_misc[M_KEYS + warp - 8] = wbest;
          named_bar(5, 256);
          if (__reduce_max_sync(0xffffffffu, s_misc[M_KEYS + (lane & 7)]) == wbest) {
            if (nb == 0 && ky == wbest && (q & 1) == 0) st_relaxed4(&g_slot[layer][mb * 8], make_uint4(ky, __float_as_uint(mn), __float_as_uint(iv), tag));
            const int r = ~wbest & 15;
            if ((r & 7) == g) {
#pragma unroll
              for (int j = 0; j < 4; j++) {
                const uint32_t* a = &xr[8 * j];
                st_relaxed4(&g_cand[layer][mb * 128 + nb * 16 + q * 4 + j],
                            r < 8 ? make_uint4(nosent(a[0]), nosent(a[2]), nosent(a[4]), nosent(a[6])) : make_uint4(nosent(a[1]), nosent(a[3]), nosent(a[5]), nosent(a[7])));
              }
            }
            __syncwarp();
          }
          if (warp == 9) PROF(14);
          if (layer == 0) {
            if ((q & 1) == 0) {
              g_rowln[nb][grow + 8 * rr] = make_float2(mn, iv);
              if (warp - 8 == nb) {
                const float mu2 = mu + (mu - mn) * iv, inv2 = ln_inv(var * (1.f + iv) * (1.f + iv));
                st_relaxed4(&g_rowab[1][grow + 8 * rr], make_uint4(__float_as_uint((1.f + iv) * inv2), __float_as_uint((mn * iv + rbf(mu2)) * inv2), tag, 0));
              }
            }
            __syncwarp();
          } else {
            const float mo = __shfl_xor_sync(0xffffffffu, mn, 2), io = __shfl_xor_sync(0xffffffffu, iv, 2);
            const uint32_t m0 = pack_bf16(rr ? mo : mn, rr ? mo : mn), m1 = pack_bf16(rr ? mn : mo, rr ? mn : mo);
            const float i0 = rr ? io : iv, i1 = rr ? iv : io;
#pragma unroll
            for (int j = 0; j < 8; j++)
              stsm_x4(zrow + (j >> 2) * 8192 + ((((2 * j + (mi >> 1)) & 7) ^ (srow & 7)) << 4), add_ln_pair(xr[4 * j], m0, i0),
                      add_ln_pair(xr[4 * j + 1], m1, i1), add_ln_pair(xr[4 * j + 2], m0, i0), add_ln_pair(xr[4 * j + 3], m1, i1));
            fence_async_smem();
          }
          if (warp == 15) asm volatile("bar.arrive 7, 512;" ::: "memory");
        }
        if (warp < 15) {
          uint32_t gu[64];
          mbar_wait(bar(B_GU), layer); mbar_wait(bar(B_GU + 2), layer);
          fetch_gu(gu, 0, warp - 8); fetch_gu(gu + 32, 1, warp - 8);
          gemv_gu(gu, 48, 0, warp - 8, 1);
        }
        if (layer == 0) asm volatile("bar.arrive 9, 512;" ::: "memory");
        else {
        uint32_t wd[64];
        mbar_wait(bar(B_DN), layer);
#pragma unroll
        for (int j = 0; j < 16; j++) {
          const uint32_t row = sbase + ((warp - 8) * 2 + (j >> 3)) * 3584 + min((j & 1) * 16 + (mi >> 1) * 8 + (lane & 7), 27) * 128;
          ldsm_x4_t(row + ((((j & 6) + (mi & 1)) ^ ((row >> 7) & 7)) << 4), wd[4 * j], wd[4 * j + 1], wd[4 * j + 2], wd[4 * j + 3]);
        }
        fence_regs_u<64>(wd);
        mbar_wait_cluster(bar(B_HX), layer);
        uint32_t hf[4];
        {
          const float hv = hidden();
          const uint32_t hp2 = pack_bf16(hv, __shfl_down_sync(0xffffffffu, hv, 1));
#pragma unroll
          for (int j = 0; j < 4; j++) hf[j] = __shfl_sync(0xffffffffu, hp2, 8 * j + 2 * q);
        }
        if (warp == 9) PROF(19);
        float y[4][4] = {};
#pragma unroll
        for (int j = 0; j < 16; j++)
          mma_16816(y[j & 3], wd[4 * j], wd[4 * j + 1], wd[4 * j + 2], wd[4 * j + 3], g == j >> 1 ? hf[(j & 1) * 2] : 0u, g == j >> 1 ? hf[(j & 1) * 2 + 1] : 0u);
        {
          float e[4];
#pragma unroll
          for (int c = 0; c < 4; c++) { const int i = (c & 1) * 2 + (c >> 1); e[c] = (y[0][i] + y[1][i]) + (y[2][i] + y[3][i]); }
          const bool b0 = g & 1, b1 = g & 2;
          float t0 = __shfl_xor_sync(0xffffffffu, b0 ? e[0] : e[1], 4), t1 = __shfl_xor_sync(0xffffffffu, b0 ? e[2] : e[3], 4);
          const float f0 = b0 ? t0 : e[0], f1 = b0 ? e[1] : t0, f2 = b0 ? t1 : e[2], f3 = b0 ? e[3] : t1;
          t0 = __shfl_xor_sync(0xffffffffu, b1 ? f0 : f2, 8); t1 = __shfl_xor_sync(0xffffffffu, b1 ? f1 : f3, 8);
          st_relaxed4(&g_ypart[layer][bid * 256 + (warp - 8) * 32 + (q * 4 + (g & 3)) * 2 + (g >> 2)],
                      b1 ? make_uint4(f2u(t0), f2u(t1), f2u(f2), f2u(f3)) : make_uint4(f2u(f0), f2u(f1), f2u(t0), f2u(t1)));
        }
        if (warp == 9) PROF(20);
        asm volatile("bar.arrive 9, 384;" ::: "memory");
        cluster_arrive(); cluster_wait();
        return;
        }
      }
      const unsigned layer = pass;
      regs_inc<224>();
      float acc[2][96];
      {
        PHASE_IDS
        const uint32_t da0 = dlo(SOFF, 16) + (wg - 2) * 512;
        constexpr uint32_t db0 = dlo(SOFF + SL_W, 4096);
#pragma unroll
        for (int i = 0; i < 96; i++) acc[0][i] = acc[1][i] = 0.f;
        int s = 0, u = 0;
#pragma unroll 1
        for (int i = 0; i < 16; i++) {
          const uint32_t da = da0 + s * (STG >> 4), db = db0 + s * (STG >> 4);
          mbar_wait(bar(B_FULL + s), (u + (s ? layer : 0)) & 1);
          if (warp == 9) STEPT(i);
          if (warp == 9 && i == 0) PROF(29);
          wg_fence();
#pragma unroll
          for (int kk = 0; kk < 4; kk++) {
            wg_ss192t(acc[0], da + kk * 2, db + (kk >> 1) * (SL_HD >> 4) + (kk & 1) * 128, 1);
            wg_ss192t(acc[1], da + 1024 + kk * 2, db + (kk >> 1) * (SL_HD >> 4) + (kk & 1) * 128, 1);
          }
          wg_commit();
          wg_wait<1>();
          if (lane < 2 && i > 0 && i < 14) mbar_arrive_cluster(bar(B_EMPTY + (s == 0 ? 2 : s - 1)), lane);
          if (++s == 3) { s = 0; u++; }
        }
      }
      PHASE_IDS
      mbar_wait(bar(B_CS), layer);
      float pa[2][2], pb[2][2];
      {
        const uint32_t tag = s_misc[M_TAG];
        const uint4* src = &g_rowab[layer][rb * 256 + (wg - 2 + (lane >> 4) * 2) * 64 + wi * 16 + (lane & 15)];
        uint4 v;
        uint32_t spins = 0;
#pragma unroll 1
        do { v = ld_relaxed4(src); } while (!__all_sync(0xffffffffu, v.z == tag) && ++spins < SPIN_LIMIT);
#pragma unroll
        for (int j = 0; j < 4; j++) {
          pa[j >> 1][j & 1] = __uint_as_float(__shfl_sync(0xffffffffu, v.x, g + 8 * j));
          pb[j >> 1][j & 1] = __uint_as_float(__shfl_sync(0xffffffffu, v.y, g + 8 * j));
        }
      }
      const int prow = (int)s_misc[M_SEL0] - rb * 256;
      const bool patch = ((prow - (wg - 2) * 64 - wi * 16) & ~0x8F) == 0;
      const float* cs = (const float*)(smem + OFF_CS);
      auto finish = [&](int m, int b, float2 c, uint32_t* dst) {
        dst[0] = pack_bf16(acc[m][4 * b] * pa[m][0] - c.x * pb[m][0], acc[m][4 * b + 1] * pa[m][0] - c.y * pb[m][0]);
        dst[1] = pack_bf16(acc[m][4 * b + 2] * pa[m][1] - c.x * pb[m][1], acc[m][4 * b + 3] * pa[m][1] - c.y * pb[m][1]);
      };
      wg_wait<0>();
      fence_regs<96>(acc[0]); fence_regs<96>(acc[1]);
      if (warp != 9) STEPT(1);
      if (lane < 2) mbar_arrive_cluster(bar(B_QDONE), lane);
      if (warp == 9) PROF(2);
#pragma unroll
      for (int h = 0; h < 2; h++) {
        const uint32_t dst = sbase + (h * 8 + 2 + wg) * 8192 + srow * 64;
#pragma unroll
        for (int jj = 0; jj < 4; jj++) {
          const int b = 8 + (jj >> 1) * 8 + h * 4 + (jj & 1) * 2;
          const float2 c0 = *(const float2*)&cs[8 * b + 2 * q], c1 = *(const float2*)&cs[8 * b + 8 + 2 * q];
          uint32_t r[2][4];
#pragma unroll
          for (int m = 0; m < 2; m++) { finish(m, b, c0, r[m]); finish(m, b + 1, c1, r[m] + 2); }
          if (h == 0 && jj == 0) named_bar(5, 256);
#pragma unroll
          for (int m = 0; m < 2; m++)
            stsm_x4(dst + m * 16384 + (jj >> 1) * 4096 + ((((jj & 1) * 2 + (mi >> 1)) ^ ((srow >> 1) & 3)) << 4), r[m][0], r[m][1], r[m][2], r[m][3]);
        }
        if (patch) {
          __syncwarp();
          if (lane < 8)
            *(uint4*)(smem + (h * 8 + 4 + (prow >> 6)) * 8192 + g * 4096 + (prow & 63) * 64 + ((q ^ ((prow >> 1) & 3)) << 4)) =
                *(const uint4*)(smem + OFF_PATCH + 128 + g * 128 + h * 64 + q * 16);
        }
        fence_async_smem();
        __syncwarp();
        mbar_arrive_e(bar(B_KVREADY + h));
        if (warp != 9) STEPT(2 + h);
      }
#pragma unroll
      for (int j = 0; j < 4; j++) { pa[j >> 1][j & 1] *= SM_C; pb[j >> 1][j & 1] *= SM_C; }
#pragma unroll
      for (int jj = 0; jj < 4; jj++) {
        const float2 c0 = *(const float2*)&cs[16 * jj + 2 * q], c1 = *(const float2*)&cs[16 * jj + 8 + 2 * q];
#pragma unroll
        for (int m = 0; m < 2; m++) {
          uint32_t r[4];
          finish(m, 2 * jj, c0, r); finish(m, 2 * jj + 1, c1, r + 2);
          *(uint4*)(smem + AT_ST + ((jj >> 1) * 16 + warp - 8 + 8 * m) * 1024 + (jj & 1) * 512 + lane * 16) = make_uint4(r[0], r[1], r[2], r[3]);
        }
      }
      __syncwarp();
      if (patch) {
        *(uint32_t*)(smem + AT_ST + ((lane >> 4) * 16 + (prow >> 4)) * 1024 + (mi & 1) * 512 + ((prow & 7) * 4 + q) * 16 + ((g & 1) * 2 + ((prow >> 3) & 1)) * 4) =
            *(const uint32_t*)(smem + OFF_PATCH + lane * 4);
        __syncwarp();
      }
      if (warp == 9) PROF(3);
      mbar_arrive_e(bar(B_QREADY));
      regs_dec<128>();
    } else {
      if (pass > 0) {
        const unsigned layer = pass - 1;
        {
          PHASE_IDS
          const uint32_t tag = s_misc[M_TAG];
          if (warp == 0) {
            mbar_wait(bar(B_WGO), layer);
            fence_async_global();
            mbar_wait(bar(B_ADONE), layer);
#pragma unroll 1
            for (int k = 2; k < 16; k++) {
              if (k == 8 && !(FAKE & 8)) { mbar_wait(bar(B_WGO + 1), layer); fence_async_global(); }
              if (k >= 4) mbar_wait(bar(B_WEMPTY + (k & 3)), ((k >> 2) - 1 + ((k & 2) ? layer : 0)) & 1);
              load_o(k); load_wo(k);
              if (k == RES_K) { mbar_wait(bar(B_OST + 1), layer); load_res(1, layer); }
            }
            if (layer == 1) {
              mbar_wait(bar(B_WEMPTY + 1), 1);
              if (FAKE & 2) mbar_arrive_e(bar(B_DN)); else mbar_expect_tx(bar(B_DN), 4 * FFN_PIECE);
              if (!(FAKE & 2)) tma_load3_h(sbase, &P.mapD, 0, bid * 28, 0, bar(B_DN), FFN_POL);
              if (D_SPLIT == 0) tma_load3_h(sbase + 2 * FFN_PIECE, &P.mapD, 0, bid * 28, 8, bar(B_DN), FFN_POL);
            }
            named_bar(6, 288);
            if (layer == 0) {
              mbar_wait(bar(B_QFREE), 0);
              load_w(0, 0); load_w(1, 1);
            } else if (D_SPLIT == 1 && !(FAKE & 2)) tma_load3_h(sbase + 2 * FFN_PIECE, &P.mapD, 0, bid * 28, 8, bar(B_DN), FFN_POL);
            spin_cycles(DELAY_S);
            uint4 c, u0, u1;
            uint32_t u2, best = 0, spins = 0;
            int src;
#pragma unroll 1
            for (;;) {
              src = (~best & 0x7FFu) >> 7;
              const uint4* xsel = &g_cand[layer][src * 128];
              c = ld_relaxed4(&g_slot[layer][(lane & 15) * 8]);
              u0 = ld_relaxed4(xsel + rank * 64 + lane); u1 = ld_relaxed4(xsel + rank * 64 + 32 + lane);
              u2 = ld_relaxed((const uint32_t*)(xsel + (bid >> 4) * 16 + q * 4) + (bid & 15));
              const uint32_t prev = best;
              best = __reduce_max_sync(0xffffffffu, c.w == tag ? c.x : 0u);
              if ((__all_sync(0xffffffffu, c.w == tag && valid4(u0) && valid4(u1) && u2 != SENT) && best == prev) || ++spins > SPIN_LIMIT) break;
            }
            const float sel_m = __uint_as_float(__shfl_sync(0xffffffffu, c.y, src)), sel_inv = __uint_as_float(__shfl_sync(0xffffffffu, c.z, src));
            const uint32_t m2 = pack_bf16(sel_m, sel_m);
            uint4* xs = (uint4*)(smem + T_XS) + (lane & 16) + q * 4 + (g & 3);
            xs[0] = make_uint4(ln_pair(u0.x, m2, sel_inv), ln_pair(u0.y, m2, sel_inv), ln_pair(u0.z, m2, sel_inv), ln_pair(u0.w, m2, sel_inv));
            xs[32] = make_uint4(ln_pair(u1.x, m2, sel_inv), ln_pair(u1.y, m2, sel_inv), ln_pair(u1.z, m2, sel_inv), ln_pair(u1.w, m2, sel_inv));
            s_misc[M_KEY] = best; s_misc[M_MEAN] = __float_as_uint(sel_m); s_misc[M_INV] = __float_as_uint(sel_inv);
            s_misc[M_XQ + q] = u2;
            PROF(16);
            named_bar(7, 512);
            if (D_SPLIT == 2 && layer == 1) tma_load3_h(sbase + 2 * FFN_PIECE, &P.mapD, 0, bid * 28, 8, bar(B_DN), FFN_POL);
          } else {
            uint32_t gu[64];
            auto next_gu = [&](int r) {
              fetch_gu(gu + r * 32, 0, warp - 1);
              fence_async_smem();
              mbar_arrive_e(bar(B_GUFREE));
              if (warp == 2) {
                mbar_wait(bar(B_GUFREE), r);
                if (r == 0) named_bar(14, 64);
                if (FAKE & 1) { mbar_arrive_e(bar(B_GU + 1 + r)); return; }
                mbar_expect_tx(bar(B_GU + 1 + r), 2 * FFN_PIECE);
                tma_load2_h(sbase + SL_F, &P.mapG, cl * 56, rank * 512 + 256 + r * 128, bar(B_GU + 1 + r), FFN_POL);
                spin_cycles(GUB_PACE);
                tma_load2_h(sbase + SL_F + FFN_PIECE, &P.mapU, cl * 56, rank * 512 + 256 + r * 128, bar(B_GU + 1 + r), FFN_POL);
              }
            };
            mbar_wait(bar(B_GU), layer);
            next_gu(0);
            if (warp == 1) {
              mbar_expect_tx(bar(B_HX), 896);
              mbar_wait(bar(B_OST + 1), layer);
              set_flag(&g_oflag[rb][1][hp].v[layer], tag);
              asm volatile("bar.arrive 14, 64;" ::: "memory");
              PROF(31);
              poll_flag(&g_oflag[rb][1][lane & 15].v[layer], tag);
              mbar_arrive_e(bar(B_WGO + 1));
              PROF(26);
            } else if (warp == 7) {
              uint32_t* tab = (uint32_t*)(smem + OFF_PATCH);
#pragma unroll
              for (int j = 0; j < 2; j++) { const int w = lane + 32 * j; tab[(w & 3) * 16 + (w >> 2)] = ((const uint32_t*)P.w_r)[nb * 64 + w]; }
              tab[64 + lane] = lane < 16 ? 0x3F803F80u : 0u;
              float tot = 0.f;
#pragma unroll
              for (int j = 0; j < 4; j++) {
                const uint4 u = ((const uint4*)P.w_r)[lane + 32 * j];
                tot += bf_lo(u.x) + bf_hi(u.x) + bf_lo(u.y) + bf_hi(u.y) + bf_lo(u.z) + bf_hi(u.z) + bf_lo(u.w) + bf_hi(u.w);
              }
              s_misc[M_WSUM] = __float_as_uint(warp_sum(tot));
            }
            if (wg == 1) {
              if (layer == 1) {
                const float2 ln = g_rowln[nb][mb * 128 + tid - 128];
                const uint32_t m2 = pack_bf16(ln.x, ln.x);
                uint8_t* row = smem + AT_ST + (wi >> 1) * 16384 + (tid & 63) * 128;
                mbar_wait(bar(B_RES), 1);
#pragma unroll 1
                for (int j = 0; j < 8; j++) {
                  uint4* c = (uint4*)(row + (((j + lane) & 7) << 4));
                  const uint4 v = c[0], w = c[512];
                  c[0] = make_uint4(add_ln_pair(v.x, m2, ln.y), add_ln_pair(v.y, m2, ln.y), add_ln_pair(v.z, m2, ln.y), add_ln_pair(v.w, m2, ln.y));
                  c[512] = make_uint4(add_ln_pair(w.x, m2, ln.y), add_ln_pair(w.y, m2, ln.y), add_ln_pair(w.z, m2, ln.y), add_ln_pair(w.w, m2, ln.y));
                }
                const int prow = (int)s_misc[M_SEL0] - mb * 128;
                __syncwarp();
                if (prow >> 5 == wi && lane < 16)
                  *(uint4*)(smem + AT_ST + (prow >> 6) * 16384 + (lane >> 3) * 8192 + (prow & 63) * 128 + (((lane ^ prow) & 7) << 4)) = poll4(&g_x2row[(nb * 16 + lane) * 2]);
                PROF(30);
              }
              __syncwarp();
              mbar_arrive_e(bar(B_RST));
            }
            mbar_wait(bar(B_GU + 1), layer);
            next_gu(1);
            if (warp == 3 && layer == 0) {
              named_bar(8, 288);
              if (nb > 0) spin_cycles(X_STAGGER);
              store_tile(0, -1);
              set_flag(&g_xflag[mb][nb].v[0], tag);
              PROF(17);
              poll_flag(&g_xflag[2 * rb + (lane & 1)][0].v[0], tag);
              fence_async_global();
              load_a(0, 0, 1);
              if (!A1_LATE) load_a(1, 1, 1);
              PROFL(1, 1);
            }
              gemv_gu(gu, 16, 32, warp - 1, 0);
            if (warp == 2) PROF(18);
          }
        }
      }
      regs_dec<32>();
      if (pass > 0) {
        const unsigned layer = pass - 1;
        PHASE_IDS
        const uint32_t tag = s_misc[M_TAG], bkey = s_misc[M_KEY];
        const int sel = SEQ - 1 - (int)(bkey & 0x7FFFu);
        if (warp == 3) {
          if (layer == 1) {
            if (lane < 24) ((uint4*)g_cspart)[bid * 24 + lane] = make_uint4(0, 0, 0, 0);
          } else s_misc[M_SEL0] = sel;
          if (bid == 0 && lane == 0) g_sel[layer] = sel;
        }
        __syncwarp();
        if (layer == 0) {
          auto load_down = [&](int j) {
            mbar_expect_tx(bar(B_DN + j), 2 * FFN_PIECE);
            bulk_load_h(sbase + SL_F + j * 2 * FFN_PIECE, P.w_d + (size_t)(bid * 28 + j * 14) * DM, 2 * FFN_PIECE, bar(B_DN + j), FFN_POL);
          };
          if (warp == 0) {
            if (A1_LATE) { fence_async_global(); load_a(1, 1, 1); }
            poll_flag(&g_xflag[2 * rb + (lane & 1)][(lane >> 1) & 7].v[0], tag);
          }
          named_bar(9, 512);
          if (warp == 0) {
            fence_async_global();
            fence_async_smem();
            if (lane < 16) mbar_arrive_cluster(bar(B_QFREE), lane & 1);
            mbar_wait(bar(B_QFREE), 1);
            load_w(2, 2); load_a(2, 2, 1);
            load_down(0);
          } else if (wg == 1) {
            if (warp == 4) { mbar_wait(bar(B_DN), 0); load_down(1); }
            mbar_wait_cluster(bar(B_HX), 0);
            const float hv = rbf(hidden());
            float d[8] = {0.f, 0.f, 0.f, 0.f, 0.f, 0.f, 0.f, 0.f};
#pragma unroll 1
            for (int j = 0; j < 28; j += 2) {
              if (j == 0 || j == 14) mbar_wait(bar(B_DN + (j > 0)), 0);
              const uint4 w0 = *(const uint4*)(smem + SL_F + j * 2048 + (tid - 128) * 16), w1 = *(const uint4*)(smem + SL_F + j * 2048 + 2048 + (tid - 128) * 16);
              fma8(d, w0, __shfl_sync(0xffffffffu, hv, j));
              fma8(d, w1, __shfl_sync(0xffffffffu, hv, j + 1));
            }
            uint4* dst = &g_ypart[0][bid * 256 + (tid - 128) * 2];
            st_relaxed4(dst, make_uint4(f2u(d[0]), f2u(d[1]), f2u(d[2]), f2u(d[3])));
            st_relaxed4(dst + 1, make_uint4(f2u(d[4]), f2u(d[5]), f2u(d[6]), f2u(d[7])));
            named_bar(2, 128);
            PROF(20);
            if (warp == 5) {
              fence_async_smem();
              mbar_expect_tx(bar(B_WS), 4 * SL_HD);
#pragma unroll 1
              for (int j = 0; j < 4; j++) tma_load3(sbase + SL_F + j * SL_HD, &P.mapW, hp * 64, rb * 128 + j * 32, 0, bar(B_WS));
            }
          }
        } else {
          const int skip = sel >> 7 == mb ? (sel >> 6) & 1 : -1;
          if (warp == 0) {
            store_tile(1, skip);
            PROF(17);
          } else if (wg == 0) {
#pragma unroll 1
            for (int c = tid - 32; c < 1024 && skip >= 0; c += 96) {
              const int r = c >> 4;
              if (r != (sel & 63))
                *(uint4*)(P.out + (size_t)(mb * 128 + skip * 64 + r) * DM + nb * 128 + (c & 15) * 8) =
                    *(const uint4*)(smem + AT_ST + skip * 16384 + ((c >> 3) & 1) * 8192 + r * 128 + (((c ^ r) & 7) << 4));
            }
          } else named_bar(9, 384);
        }
        if (wg == 1) {
          const int t_y = (int)clock();
          const uint32_t xw = s_misc[M_XQ + ((lane & 7) >> 1)];
          const float x = (lane & 1) ? bf_hi(xw) : bf_lo(xw);
          float xn = rbf(rbf(x - __uint_as_float(s_misc[M_MEAN])) * __uint_as_float(s_misc[M_INV]));
          uint32_t u = bkey & 0xFFFF0000u;
          u = (u & 0x80000000u) ? (u & 0x7FFFFFFFu) : (~u & 0xFFFF0000u);
          float sg = rbf(__fdividef(1.f, 1.f + __expf(-__uint_as_float(u))));
          uint32_t* dst = (layer == 0 ? (uint32_t*)&g_x2row[bid * 2] : (uint32_t*)(P.out + (size_t)sel * DM + bid * 8)) + (lane >> 1);
          asm volatile("" : "+f"(xn), "+f"(sg), "+l"(dst));
#pragma unroll 1
          while ((int)clock() - t_y < DELAY_Y) {}
          const uint4* src = &g_ypart[layer][((tid - 128) >> 1) * 256 + bid * 2 + (tid & 1)];
          uint4 v, w;
          uint32_t spins = 0;
#pragma unroll 1
          do { v = ld_relaxed4(src); w = ld_relaxed4(src + 64 * 256); } while (!__all_sync(0xffffffffu, valid4(v) && valid4(w)) && ++spins < SPIN_LIMIT);
          float a[4] = {__uint_as_float(v.x) + __uint_as_float(w.x), __uint_as_float(v.y) + __uint_as_float(w.y),
                        __uint_as_float(v.z) + __uint_as_float(w.z), __uint_as_float(v.w) + __uint_as_float(w.w)};
          const bool b1 = lane & 2, b2 = lane & 4;
          float c0 = (b1 ? a[1] : a[0]) + __shfl_xor_sync(0xffffffffu, b1 ? a[0] : a[1], 2);
          float c1 = (b1 ? a[3] : a[2]) + __shfl_xor_sync(0xffffffffu, b1 ? a[2] : a[3], 2);
          float y = (b2 ? c1 : c0) + __shfl_xor_sync(0xffffffffu, b2 ? c0 : c1, 4);
          y += __shfl_xor_sync(0xffffffffu, y, 8);
          y += __shfl_xor_sync(0xffffffffu, y, 16);
          float* red = (float*)(smem + OFF_PATCH);
          red[wi * 8 + (lane & 1) * 4 + ((lane >> 1) & 3)] = y;
          named_bar(2, 128);
          if (warp == 4) {
            PROF(21);
            y = (red[lane & 7] + red[8 + (lane & 7)]) + (red[16 + (lane & 7)] + red[24 + (lane & 7)]);
            const float res = x + rbf(xn + rbf(rbf(y) * sg));
            const uint32_t pr = nosent(pack_bf16(res, __shfl_down_sync(0xffffffffu, res, 1)));
            if (lane < 8 && (lane & 1) == 0) st_relaxed(dst, pr);
            PROF(22);
          }
        }
        if (pass == 2) {
          if (bid == 0 && tid == 128) g_epoch = tag;
          __syncwarp();
          cluster_arrive(); cluster_wait();
          return;
        }
      }
      const unsigned layer = pass;
      PHASE_IDS
      if (wg == 0) {
        if (warp == 0) {
          int s = 0, u = 0;
#pragma unroll 1
          for (int i = 3; i < 16; i++) {
            if (layer == 1) mbar_arrive_e(bar(B_EMPTY + s));
            mbar_wait(bar(B_EMPTY + s), (u + (s ? 0 : layer)) & 1);
            load_w(s, i);
            load_a(s, i, layer);
            if (++s == 3) { s = 0; u++; }
          }
        } else if (warp == 1) {
          if (layer == 0) {
            const uint32_t tag = ld_relaxed(&g_epoch) + 1;
            float shift = 0.f, sum = 0.f, sq = 0.f;
            const int r = hp * 16 + (lane >> 1);
#pragma unroll 1
            for (int i = 0; i < 16; i++) {
              mbar_wait(bar(B_FULL + i % 3), (i / 3) & 1);
              const uint8_t* base = smem + (i % 3) * STG + r * 128;
#pragma unroll 1
              for (int j0 = 0; j0 < 4; j0 += 2) {
                uint4 v[2];
#pragma unroll
                for (int j = 0; j < 2; j++) v[j] = *(const uint4*)(base + ((((lane & 1) * 4 + j0 + j) ^ (r & 7)) << 4));
                if (i == 0 && j0 == 0) shift = __shfl_sync(0xffffffffu, bf_lo(v[0].x), lane & ~1);
#pragma unroll
                for (int j = 0; j < 2; j++) {
                  const uint32_t w[4] = {v[j].x, v[j].y, v[j].z, v[j].w};
#pragma unroll
                  for (int c = 0; c < 4; c++) {
                    const float d0 = bf_lo(w[c]) - shift, d1 = bf_hi(w[c]) - shift;
                    sum += d0 + d1; sq = fmaf(d0, d0, fmaf(d1, d1, sq));
                  }
                }
              }
              __syncwarp();
              if (i < 13) mbar_arrive_e(bar(B_EMPTY + i % 3));
            }
            sum += __shfl_xor_sync(0xffffffffu, sum, 1); sq += __shfl_xor_sync(0xffffffffu, sq, 1);
            const float dm = sum * (1.f / DM), var = fmaxf(sq * (1.f / DM) - dm * dm, 0.f), mean = shift + dm;
            const float inv = ln_inv(var);
            if ((lane & 1) == 0) st_relaxed4(&g_rowab[0][rb * 256 + r], make_uint4(__float_as_uint(inv), __float_as_uint(rbf(mean) * inv), tag, 0));
          }
          if (rb == 0) {
            mbar_wait(bar(B_QDONE), layer);
#pragma unroll 1
            for (int j = lane; j < 512; j += 32) ((uint4*)(smem + 65536))[j] = make_uint4(0, 0, 0, 0);
            fence_async_smem();
            __syncwarp();
            if (lane < 3) mbar_arrive(bar(B_HALO + lane));
          }
        } else if (warp == 3) {
          if (layer == 1) named_bar(12, 160);
          else {
#pragma unroll 1
            for (int u = 0; u < GUA_AT; u++) mbar_wait(bar(B_FULL), u & 1);
          }
          fence_async_smem();
          if (GUA_AT == 0) mbar_arrive_e(bar(B_GU)); else mbar_expect_tx(bar(B_GU), 4 * FFN_PIECE);
#pragma unroll 1
          for (int j = 0; j < (GUA_AT ? 4 : 0); j++) {
            tma_load2_h(sbase + SL_F + j * FFN_PIECE, &P.mapG + (j & 1), cl * 56, rank * 512 + 128 - (j >> 1) * 128, bar(B_GU), FFN_POL);
            if (j < 3) spin_cycles(layer ? GU_PACE1 : GU_PACE);
          }
          PROF(27);
        } else {
#pragma unroll 1
          for (int u = 0; u < 4; u++) mbar_wait(bar(B_FULL), u & 1);
          const uint4 sent = make_uint4(SENT, SENT, SENT, SENT), zero = make_uint4(0, 0, 0, 0);
#pragma unroll 1
          for (int t = lane; t < 128; t += 32) {
            g_ypart[layer][bid * 256 + t] = sent; g_ypart[layer][bid * 256 + 128 + t] = sent;
            g_part[layer][nb * SEQ + mb * 128 + t] = zero;
            if (t < 16) g_cand[layer][mb * 128 + nb * 16 + t] = sent;
            else if (t < 18) { if (nb == 0) g_slot[layer][mb * 8 + t - 16] = zero; }
            else if (t < 20) { if (layer == 0) g_x2row[bid * 2 + t - 18] = sent; }
            else if (t >= 80 && layer == 0) *(uint4*)&g_patch[rb][((t - 80) >> 4) * DM + hp * 64 + (t & 15) * 4] = sent;
          }
        }
        __syncwarp();
        if (rank == 0) {
          if (warp == 0) {
            mbar_wait(bar(B_QDONE), layer);
#pragma unroll 1
            for (int j = 0; j < 3; j++) {
              const int o = j == 0 ? 16384 : (j == 1 ? 0 : 65536);
              mbar_wait(bar(B_KVREADY + (j > 0)), layer);
              if (j == 1) {
                if (rb > 0) {
                  poll_flag(&g_kvflag[(rb - 1) >> 1][hp][0].v[layer], s_misc[M_TAG]);
                  fence_async_global();
                  mbar_expect_tx(bar(B_HALO), 16384);
                  bulk_load_h(sbase + 16384, g_kv + (size_t)(((rb - 1) >> 1) * 16 + hp) * 65536 + 16384, 16384, bar(B_HALO), policy_evict_first());
                  PROF(5);
                } else {
                  mbar_wait(bar(B_QREADY), layer);
                }
              }
              bulk_push(mapa(sbase + o, 1), sbase + 32768 + o, j == 2 ? 32768 : 16384, mapa(bar(B_HALO + j), 1));
            }
          }
        } else if (warp > 0) {
          mbar_expect_tx(bar(B_HALO + warp - 1), warp == 3 ? 32768 : 16384);
        } else if (rb < 7) {
          uint8_t* dst = g_kv + (size_t)((rb >> 1) * 16 + hp) * 65536;
          mbar_wait(bar(B_KVREADY), layer);
          bulk_store(dst + 16384, sbase + 49152, 16384);
          bulk_commit();
          bulk_wait_all();
          set_flag(&g_kvflag[rb >> 1][hp][0].v[layer], s_misc[M_TAG]);
          PROF(4);
          mbar_wait(bar(B_KVREADY + 1), layer);
          bulk_store(dst, sbase + 32768, 16384);
          bulk_store(dst + 32768, sbase + 98304, 32768);
          bulk_commit();
          bulk_wait_all();
          set_flag(&g_kvflag[rb >> 1][hp][1].v[layer], s_misc[M_TAG]);
        }
      } else {
        const int t = tid - 128, go = (t >> 5) * DM + hp * 64 + (t & 31) * 2;
        if (layer == 0) {
          if (t == 0) { s_misc[M_TAG] = ld_relaxed(&g_epoch) + 1; s_misc[M_SEL0] = 0xFFFFFFFFu; }
#pragma unroll 1
          for (int u = 0; u < 5; u++) mbar_wait(bar(B_FULL + 2), u & 1);
          if (warp < 7) {
            uint2 v[4];
            uint32_t spins = 0;
#pragma unroll 1
            do {
#pragma unroll
              for (int j = 0; j < 4; j++) v[j] = ld_relaxed2(&g_cspart[j][go]);
            } while (!__all_sync(0xffffffffu, v[0].x && v[0].y && v[1].x && v[1].y && v[2].x && v[2].y && v[3].x && v[3].y) && ++spins < SPIN_LIMIT);
            ((float2*)(smem + OFF_CS))[t] = make_float2((dec(v[0].x) + dec(v[1].x)) + (dec(v[2].x) + dec(v[3].x)), (dec(v[0].y) + dec(v[1].y)) + (dec(v[2].y) + dec(v[3].y)));
          }
        } else {
          const uint4 v = poll4(&g_x2row[t * 2]);
          __syncwarp();
          PROF(23);
          if (t >> 4 == rb) ((uint4*)(smem + SL_F + 4 * SL_HD))[t & 15] = v;
          float* red = (float*)(smem + SL_F + 4 * SL_HD + 256);
          const float e[8] = {bf_lo(v.x), bf_hi(v.x), bf_lo(v.y), bf_hi(v.y), bf_lo(v.z), bf_hi(v.z), bf_lo(v.w), bf_hi(v.w)};
          red[wi] = warp_sum(((e[0] + e[1]) + (e[2] + e[3])) + ((e[4] + e[5]) + (e[6] + e[7])));
          named_bar(2, 128);
          const float mean = ((red[0] + red[1]) + (red[2] + red[3])) * (1.f / DM);
          float qq = 0.f;
#pragma unroll
          for (int c = 0; c < 8; c++) qq = fmaf(e[c] - mean, e[c] - mean, qq);
          red[4 + wi] = warp_sum(qq);
          mbar_wait(bar(B_WS), 0);
          if (warp < 7) {
            const uint8_t* wa = smem + SL_F + mi * SL_HD + wi * 4096;
            const uint32_t* xs = (const uint32_t*)(smem + SL_F + 4 * SL_HD) + mi * 16;
            float d[8] = {0.f, 0.f, 0.f, 0.f, 0.f, 0.f, 0.f, 0.f};
#pragma unroll 1
            for (int j = 0; j < 32; j += 2) {
              const uint4 w0 = *(const uint4*)(wa + j * 128 + (((lane ^ j) & 7) << 4)), w1 = *(const uint4*)(wa + j * 128 + 128 + (((lane ^ (j + 1)) & 7) << 4));
              const uint32_t xx = xs[j >> 1];
              fma8(d, w0, bf_lo(xx)); fma8(d, w1, bf_hi(xx));
            }
#pragma unroll
            for (int c = 0; c < 4; c++) d[c] = ((mi & 2) ? d[c + 4] : d[c]) + __shfl_xor_sync(0xffffffffu, (mi & 2) ? d[c] : d[c + 4], 16);
#pragma unroll
            for (int c = 0; c < 2; c++) d[c] = ((mi & 1) ? d[c + 2] : d[c]) + __shfl_xor_sync(0xffffffffu, (mi & 1) ? d[c] : d[c + 2], 8);
            uint32_t* dst = &g_patch[rb][wi * DM + hp * 64 + (lane & 7) * 8 + mi * 2];
            st_relaxed(dst, f2u(d[0])); st_relaxed(dst + 1, f2u(d[1]));
          }
          named_bar(2, 128);
          const float inv = ln_inv(((red[4] + red[5]) + (red[6] + red[7])) * (1.f / DM));
          asm volatile("bar.arrive 12, 160;" ::"f"(inv) : "memory");
          PROF(24);
          if ((int)s_misc[M_SEL0] >> 8 == rb && warp < 7) {
            float s0 = 0.f, s1 = 0.f;
#pragma unroll 1
            for (int hf = 0; hf < 8; hf += 4) {
              uint2 w[4];
              uint32_t spins = 0;
#pragma unroll 1
              do {
#pragma unroll
                for (int j = 0; j < 4; j++) w[j] = ld_relaxed2(&g_patch[hf + j][go]);
              } while (!__all_sync(0xffffffffu, valid4(make_uint4(w[0].x, w[0].y, w[1].x, w[1].y)) && valid4(make_uint4(w[2].x, w[2].y, w[3].x, w[3].y))) && ++spins < SPIN_LIMIT);
              s0 += (__uint_as_float(w[0].x) + __uint_as_float(w[1].x)) + (__uint_as_float(w[2].x) + __uint_as_float(w[3].x));
              s1 += (__uint_as_float(w[0].y) + __uint_as_float(w[1].y)) + (__uint_as_float(w[2].y) + __uint_as_float(w[3].y));
            }
            const float2 c = ((const float2*)(smem + OFF_CS))[t];
            const float a = warp == 4 ? inv * SM_C : inv, b = rbf(mean) * a;
            ((uint32_t*)(smem + OFF_PATCH))[t] = pack_bf16(s0 * a - c.x * b, s1 * a - c.y * b);
            PROF(25);
          }
        }
        __syncwarp();
        mbar_arrive_e(bar(B_CS));
      }
      __syncwarp();
      mbar_wait(bar(B_QREADY), layer);
      named_bar(1 + (fresh_tid() >> 7), 128);
      regs_inc<128>();
    }
    const unsigned layer = pass;
    {
      PHASE_IDS
      mbar_wait(bar(B_QREADY), layer);
      if (warp != 9) STEPT(7);
      auto kdesc = [&](int h, int b) { return dlo(SOFF, 16) + (rb == 0 && b < 4 ? 4096 : h * 4096 + b * 512); };
      auto vdesc = [&](int h, int b) { return rb == 0 && b < 4 ? dlo(SOFF + 65536, 4096) : dlo(SOFF + 4096, OFF_ONES - 4096) + (h * 8 + b) * 8 * VSTEP; };
      auto load_q = [&](uint32_t* qf, int h) {
        *(uint4*)&qf[0] = *(const uint4*)(smem + AT_ST + (h * 16 + warp) * 1024 + lane * 16);
        *(uint4*)&qf[4] = *(const uint4*)(smem + AT_ST + (h * 16 + warp) * 1024 + 512 + lane * 16);
      };
      auto store_o = [&](const float* o, int h) {
        const float i0 = __fdividef(1.f, o[16]), i1 = __fdividef(1.f, o[18]);
#pragma unroll
        for (int j = 0; j < 2; j++)
          stsm_x4(sbase + AT_ST + (h * 4 + wg) * 4096 + srow * 64 + (((2 * j + (mi >> 1)) ^ ((srow >> 1) & 3)) << 4),
                  pack_bf16(o[8 * j] * i0, o[8 * j + 1] * i0), pack_bf16(o[8 * j + 2] * i1, o[8 * j + 3] * i1),
                  pack_bf16(o[8 * j + 4] * i0, o[8 * j + 5] * i0), pack_bf16(o[8 * j + 6] * i1, o[8 * j + 7] * i1));
        fence_async_smem();
        __syncwarp();
        bulk_store(g_o + (size_t)((((rb * 2 + (wg >> 1)) * 2 + h) * 16 + hp) * 8 + (warp & 7)) * 1024, sbase + AT_ST + (h * 16 + warp) * 1024, 1024);
        bulk_commit();
      };
      auto leave_head0 = [&]() {
        bulk_wait_all();
        __syncwarp();
        if (lane < 2) mbar_arrive_cluster(bar(B_OST), lane);
      };
      bool publish = warp == 10;
      int redo = 0;
      {
        const int dl = g - 2 * q;
        const uint32_t mt = shl_clamp(0xFFFFFFFFu, max(16 * dl + 16, 0));
        uint32_t qf[8];
        float s[32];
        load_q(qf, 0);
        if (wg == 0) mbar_wait(bar(B_HALO), layer);
        wg_fence();
        qk64(s, qf, kdesc(0, wg + 3));
        wg_commit();
        wg_wait<0>();
        fence_regs<32>(s);
#pragma unroll 1
        for (int h = 0; h < 2; h++) {
          float o[20];
          uint32_t p1[16], p2[16], p3[24], p4[24];
          if (warp != 9) STEPT(8 + h * 8);
          exp_pack<8>(s, p1);
          fence_regs_u<16>(p1);
          if (wg == 1) mbar_wait(bar(B_HALO + 2 * h), layer);
          {
            float s2[32];
            const uint32_t vd = vdesc(h, wg + 3);
            wg_fence();
            qk64(s2, qf, kdesc(h, wg + 2));
            wg_commit();
            wg_rs40t_z<H64>(o, p1[0], p1[1], p1[2], p1[3], vd);
            wg_rs40t<H64>(o, p1[4], p1[5], p1[6], p1[7], vd + VSTEP, 1);
            pv32(o, p1 + 8, vd + 2 * VSTEP);
            wg_commit();
            if ((PF_MODE & 1) && wi == 1 && h == (PF_MODE >> 2 & 1)) tma_prefetch2(&P.mapG + (wg & 1), cl * 56, rank * 512 + 256 + (wg >> 1) * 128);
            if ((PF_MODE & 2) && wi == 2 && h == 1) bulk_prefetch(P.w_d + (size_t)(bid * 28 + wg * 7) * DM, FFN_PIECE);
            wg_wait<1>();
            fence_regs<32>(s2);
            if (warp != 9) STEPT(9 + h * 8);
            exp_pack<8>(s2, p2);
            fence_regs_u<16>(p2);
            wg_wait<0>();
            fence_regs<20>(o);
          }
          mbar_wait(bar(B_HALO + (h ? 2 : wg < 2)), layer);
          const uint32_t km = kdesc(h, wg + 1), kd = kdesc(h, wg + 4), kt = kdesc(h, wg);
          const uint32_t vm = vdesc(h, wg + 1), vd = vdesc(h, wg + 4), vt = vdesc(h, wg);
          {
            float sm[16], sd[16], st[16];
            wg_fence();
            qk32x3(sm, sd, st, qf, km, kd, kt);
            pv32(o, p2, vdesc(h, wg + 2)); pv32(o, p2 + 8, vdesc(h, wg + 2) + 2 * VSTEP);
            wg_commit();
            if (h == 0 && warp == 14 && rank == 0 && rb > 0) {
              poll_flag(&g_kvflag[(rb - 1) >> 1][hp][1].v[layer], s_misc[M_TAG]);
              fence_async_global();
#pragma unroll 1
              for (int n = 0; n < 2; n++) {
                mbar_expect_tx(bar(B_HALO + 1 + n), 16384 << n);
                bulk_load_h(sbase + n * 65536, g_kv + (size_t)(((rb - 1) >> 1) * 16 + hp) * 65536 + n * 32768, 16384 << n, bar(B_HALO + 1 + n), policy_evict_first());
              }
            }
            wg_wait<0>();
            fence_regs<16>(sm); fence_regs<16>(sd); fence_regs<16>(st); fence_regs<20>(o);
            if (warp != 9) STEPT(10 + h * 8);
            mix_exp(sm, sd, st, p3, wi, dl, mt);
            fence_regs_u<24>(p3);
          }
          {
            float sm[16], sd[16], st[16];
            wg_fence();
            qk32x3(sm, sd, st, qf, km + 128, kd + 128, kt + 128);
            pv32(o, p3, vm); pv32(o, p3 + 8, vd); pv32(o, p3 + 16, vt);
            wg_commit();
            if (h == 1 && publish && mbar_wait_brief(bar(B_OST), layer)) {
              set_flag(&g_oflag[rb][0][hp].v[layer], s_misc[M_TAG]);
              load_wo(0); load_wo(1); load_res(0, layer);
              publish = false;
              PROF(28);
            }
            wg_wait<0>();
            fence_regs<16>(sm); fence_regs<16>(sd); fence_regs<16>(st); fence_regs<20>(o);
            if (warp != 9) STEPT(11 + h * 8);
            load_q(qf, 1);
            mix_exp(sm, sd, st, p4, wi - 2, dl, mt);
            fence_regs_u<24>(p4);
          }
          if (wg == 0) mbar_wait(bar(B_HALO + 2), layer);
          wg_fence();
          pv32(o, p4, vm + 2 * VSTEP); pv32(o, p4 + 8, vd + 2 * VSTEP); pv32(o, p4 + 16, vt + 2 * VSTEP);
          wg_commit();
          qk64(s, qf, kdesc(1, wg + 3));
          wg_commit();
          wg_wait<1>();
          fence_regs<20>(o);
          if (warp != 9) STEPT(12 + h * 8);
          const bool unsafe = !(o[16] >= LSUM_MIN && o[16] <= LSUM_MAX && o[18] >= LSUM_MIN && o[18] <= LSUM_MAX);
          if (__any_sync(0xffffffffu, unsafe)) redo |= 1 << h;
          else { store_o(o, h); if (h == 0) leave_head0(); }
          wg_wait<0>();
          fence_regs<32>(s);
        }
      }
      if (warp != 9) STEPT(13 + 8);
      if (bar_red_or(1 + wg, 128, redo)) {
#pragma unroll 1
        for (int h = 0; h < 2; h++) {
          if (!bar_red_or(1 + wg, 128, redo >> h & 1)) continue;
          uint32_t qf[8], p[16];
          float o[20], m0 = -INFINITY, m1 = -INFINITY;
          load_q(qf, h);
#pragma unroll
          for (int i = 0; i < 20; i++) o[i] = 0.f;
#pragma unroll 1
          for (int j = 0; j <= (rb == 0 ? wg : 4); j++) {
            const int b = wg + 4 - j;
            float s[32];
            wg_fence();
            qk64(s, qf, kdesc(h, b));
            wg_commit();
            wg_wait<0>();
            fence_regs<32>(s);
            float mx0 = m0, mx1 = m1;
#pragma unroll
            for (int c = 0; c < 8; c++) {
#pragma unroll
              for (int i = 0; i < 4; i++) {
                const int diff = j * 64 + (16 * wi + g + (i >> 1) * 8) - (8 * c + 2 * q + (i & 1));
                if (diff < 0 || diff > 255) s[4 * c + i] = -INFINITY;
              }
              mx0 = fmaxf(mx0, fmaxf(s[4 * c], s[4 * c + 1]));
              mx1 = fmaxf(mx1, fmaxf(s[4 * c + 2], s[4 * c + 3]));
            }
            mx0 = fmaxf(mx0, __shfl_xor_sync(0xffffffffu, mx0, 1)); mx1 = fmaxf(mx1, __shfl_xor_sync(0xffffffffu, mx1, 1));
            mx0 = fmaxf(mx0, __shfl_xor_sync(0xffffffffu, mx0, 2)); mx1 = fmaxf(mx1, __shfl_xor_sync(0xffffffffu, mx1, 2));
            const float r0 = j == 0 ? 0.f : ex2(m0 - mx0), r1 = j == 0 ? 0.f : ex2(m1 - mx1);
            m0 = mx0; m1 = mx1;
#pragma unroll
            for (int i = 0; i < 5; i++) { o[4 * i] *= r0; o[4 * i + 1] *= r0; o[4 * i + 2] *= r1; o[4 * i + 3] *= r1; }
#pragma unroll
            for (int c = 0; c < 8; c++) { s[4 * c] -= m0; s[4 * c + 1] -= m0; s[4 * c + 2] -= m1; s[4 * c + 3] -= m1; }
            exp_pack<8>(s, p);
            fence_regs<20>(o); fence_regs_u<16>(p);
            wg_fence();
            pv32(o, p, vdesc(h, b)); pv32(o, p + 8, vdesc(h, b) + 2 * VSTEP);
            wg_commit();
            wg_wait<0>();
            fence_regs<20>(o);
          }
          named_bar(1 + wg, 128);
          if (redo >> h & 1) {
            store_o(o, h);
            if (h == 0) leave_head0();
          }
          __syncwarp();
        }
      }
      if (wi == 0) PROF(6 + wg);
      if (wi == 3 && lane < 2) mbar_arrive_cluster(bar(B_ADONE), lane);
      bulk_wait_all();
      __syncwarp();
      mbar_arrive_e(bar(B_OST + 1));
      if (publish) {
        mbar_wait(bar(B_OST), layer);
        set_flag(&g_oflag[rb][0][hp].v[layer], s_misc[M_TAG]);
#pragma unroll 1
        for (int k = 0; k < 2; k++) load_wo(k);
        load_res(0, layer);
      }
    }
    pass_v = pass + 1;
  }
}

}

typedef CUresult (*EncodeFn)(CUtensorMap*, CUtensorMapDataType, cuuint32_t, void*, const cuuint64_t*, const cuuint64_t*,
                             const cuuint32_t*, const cuuint32_t*, CUtensorMapInterleave, CUtensorMapSwizzle,
                             CUtensorMapL2promotion, CUtensorMapFloatOOBfill);
static EncodeFn g_encode = nullptr;
struct Dim { uint64_t size, stride; uint32_t box; };
template <int N> static CUtensorMap make_map(const void* ptr, const Dim (&d)[N], int swizzle) {
  CUtensorMap m;
  cuuint64_t dims[N], strides[N];
  cuuint32_t box[N], es[N];
  for (int i = 0; i < N; i++) { dims[i] = d[i].size; strides[i] = d[i].stride; box[i] = d[i].box; es[i] = 1; }
  g_encode(&m, CU_TENSOR_MAP_DATA_TYPE_BFLOAT16, N, const_cast<void*>(ptr), dims, strides + 1, box, es, CU_TENSOR_MAP_INTERLEAVE_NONE,
           swizzle == 128 ? CU_TENSOR_MAP_SWIZZLE_128B : (swizzle == 64 ? CU_TENSOR_MAP_SWIZZLE_64B : CU_TENSOR_MAP_SWIZZLE_NONE),
           swizzle ? CU_TENSOR_MAP_L2_PROMOTION_L2_256B : CU_TENSOR_MAP_L2_PROMOTION_L2_128B, CU_TENSOR_MAP_FLOAT_OOB_FILL_NONE);
  return m;
}
static CUtensorMap map2(const void* ptr, uint64_t inner, uint64_t outer, uint32_t bi, uint32_t bo, int swizzle) {
  const Dim d[2] = {{inner, 0, bi}, {outer, inner * 2, bo}};
  return make_map(ptr, d, swizzle);
}
template <class T> static void* sym_addr(T& sym) { void* p = nullptr; cudaGetSymbolAddress(&p, sym); return p; }

static Params h_p, h_p_helper;
static const void* h_key[9];
static bool h_helpers_fit = true;

static cudaLaunchConfig_t launch_cfg(int grid, cudaLaunchAttribute* at) {
  cudaLaunchConfig_t cfg = {};
  cfg.gridDim = dim3(grid); cfg.blockDim = dim3(512); cfg.dynamicSmemBytes = SMEM_BYTES; cfg.stream = cudaStreamPerThread;
  at[0].id = cudaLaunchAttributeClusterDimension;
  at[0].val.clusterDim.x = 2; at[0].val.clusterDim.y = 1; at[0].val.clusterDim.z = 1;
  cfg.attrs = at; cfg.numAttrs = 1;
  return cfg;
}

extern "C" void kernel_launch(void* const* d_in, const int* in_sizes, int n_in, void* d_out, int out_size) {
  const bf16* x = (const bf16*)d_in[0];
  const bf16* wqkv = (const bf16*)d_in[1];
  const bf16* wo = (const bf16*)d_in[2];
  cudaLaunchAttribute at[1];
  bool fresh = g_encode != nullptr && h_key[8] == d_out;
  for (int i = 0; i < 8; i++) fresh = fresh && h_key[i] == d_in[i];
  if (!fresh) {
    if (!g_encode) {
      void* fn = nullptr;
      cudaDriverEntryPointQueryResult st;
      cudaGetDriverEntryPoint("cuTensorMapEncodeTiled", &fn, cudaEnableDefault, &st);
      g_encode = (EncodeFn)fn;
      cudaFuncSetAttribute(mega_kernel, cudaFuncAttributeMaxDynamicSharedMemorySize, SMEM_BYTES);
      cudaLaunchConfig_t cfg = launch_cfg(132, at);
      int nclusters = 0;
      if (cudaOccupancyMaxActiveClusters(&nclusters, mega_kernel, &cfg) != cudaSuccess) { nclusters = 0; (void)cudaGetLastError(); }
      h_helpers_fit = nclusters >= 66;
    }
    bf16* x1 = (bf16*)sym_addr(g_x1);
    Params& p = h_p;
    p.x = x; p.wqkv = wqkv; p.wo = wo; p.w_r = (const bf16*)d_in[4]; p.w_g = (const bf16*)d_in[5]; p.w_u = (const bf16*)d_in[6]; p.w_d = (const bf16*)d_in[7];
    p.out = (bf16*)d_out;
    p.mapA[0] = map2(x, DM, SEQ, 64, 256, 128);
    p.mapA[1] = map2(x1, DM, SEQ, 64, 256, 128);
    { const Dim d[3] = {{DM, 0, 64}, {DM, 3 * DM * 2, 32}, {3, DM * 2, 3}}; p.mapW = make_map(wqkv, d, 128); }
    { const Dim d[3] = {{DM, 0, 64}, {64, DM * 2, 32}, {16, 64 * DM * 2, 2}}; p.mapWo = make_map(wo, d, 128); }
    p.mapRes[0] = map2(x, DM, SEQ, 64, 64, 128);
    p.mapRes[1] = p.mapXst[0] = map2(x1, DM, SEQ, 64, 64, 128);
    p.mapXst[1] = map2(d_out, DM, SEQ, 64, 64, 128);
    p.mapG = map2(p.w_g, FF, DM, 56, 128, 0);
    p.mapU = map2(p.w_u, FF, DM, 56, 128, 0);
    { const Dim d[3] = {{64, 0, 64}, {FF, DM * 2, 28}, {DM / 64, 128, 8}}; p.mapD = make_map(p.w_d, d, 128); }
    p.helper_first = 128;
    h_p_helper = p;
    h_p_helper.helper_first = 0;
    for (int i = 0; i < 8; i++) h_key[i] = d_in[i];
    h_key[8] = d_out;
  }
  if (!h_helpers_fit) {
    void* ah[] = {&h_p_helper};
    cudaLaunchConfig_t cfg = launch_cfg(4, at);
    cudaLaunchKernelExC(&cfg, (const void*)mega_kernel, ah);
  }
  void* a0[] = {&h_p};
  cudaLaunchConfig_t cfg = launch_cfg(h_helpers_fit ? 132 : 128, at);
  cudaLaunchKernelExC(&cfg, (const void*)mega_kernel, a0);
}
```

```cpp
#include <cuda_runtime.h>
#include <cuda_bf16.h>
#include <cuda.h>
#include <stdint.h>

namespace {

constexpr int SEQ = 2048, DM = 1024, FF = 3584;
constexpr float LN_EPS = 1e-5f;
typedef __nv_bfloat16 bf16;

__device__ __align__(1024) uint8_t g_kv[3 * 16 * 65536];
__device__ __align__(1024) uint8_t g_o[SEQ * DM * 2];
__device__ __align__(1024) bf16 g_x1[SEQ * DM];
__device__ unsigned g_epoch;
struct __align__(128) Flag { unsigned v[32]; };
__device__ Flag g_kvflag[3][16][2], g_oflag[8][2][16], g_xflag[16][8];
__device__ uint4 g_rowab[2][SEQ];
__device__ __align__(16) uint32_t g_cspart[4][3 * DM];
constexpr uint32_t SENT = 0xFFFFFFFFu;
__device__ uint4 g_part[2][8 * SEQ];
__device__ uint4 g_slot[2][16 * 8];
__device__ uint4 g_cand[2][16 * 128];
__device__ uint4 g_ypart[2][128 * DM / 4];
__device__ uint4 g_x2row[128 * 2];
__device__ __align__(16) uint32_t g_patch[8][3 * DM];
__device__ float2 g_rowln[8][SEQ];
__device__ int g_sel[2];

#define PROFL(l, e)
#define PROF(e) PROFL(layer, e)
#define STEPT(i)
#define SPIN_LIMIT 4000000u
__device__ __forceinline__ uint32_t smem_u32(const void* p) { return (uint32_t)__cvta_generic_to_shared(p); }
__device__ __forceinline__ void mbar_init(uint32_t bar, uint32_t cnt) {
  asm volatile("mbarrier.init.shared::cta.b64 [%0], %1;" ::"r"(bar), "r"(cnt) : "memory");
}
#define ELECT "{\n.reg .pred e;\nelect.sync _|e, 0xffffffff;\n@e "
__device__ __forceinline__ void mbar_expect_tx(uint32_t bar, uint32_t bytes) {
  asm volatile(ELECT "mbarrier.arrive.expect_tx.shared::cta.b64 _, [%0], %1;\n}" ::"r"(bar), "r"(bytes) : "memory");
}
__device__ __forceinline__ void mbar_arrive(uint32_t bar) {
  asm volatile("mbarrier.arrive.shared::cta.b64 _, [%0];" ::"r"(bar) : "memory");
}
__device__ __forceinline__ void mbar_arrive_e(uint32_t bar) {
  asm volatile(ELECT "mbarrier.arrive.shared::cta.b64 _, [%0];\n}" ::"r"(bar) : "memory");
}
__device__ __forceinline__ uint32_t mapa(uint32_t addr, uint32_t cta) {
  uint32_t r; asm("mapa.shared::cluster.u32 %0, %1, %2;" : "=r"(r) : "r"(addr), "r"(cta)); return r;
}
__device__ __forceinline__ void mbar_arrive_cluster(uint32_t bar, uint32_t cta) {
  asm volatile("mbarrier.arrive.shared::cluster.b64 _, [%0];" ::"r"(mapa(bar, cta)) : "memory");
}
#define MBAR_WAIT_ASM(QUAL)                                                                                                \
  asm volatile("{\n.reg .pred p;\n.reg .u32 n;\nmov.u32 n, 0;\nWAIT_LOOP:\n.pragma \"nounroll\";\n"                         \
               "mbarrier.try_wait.parity" QUAL ".shared::cta.b64 p, [%0], %1;\n@p bra WAIT_DONE;\n"                        \
               "add.u32 n, n, 1;\nsetp.lt.u32 p, n, %2;\n@p bra WAIT_LOOP;\nWAIT_DONE:\n}" ::"r"(bar), "r"(parity), "n"(SPIN_LIMIT) : "memory")
__device__ __forceinline__ void mbar_wait(uint32_t bar, uint32_t parity) { MBAR_WAIT_ASM(""); }
__device__ __forceinline__ void mbar_wait_cluster(uint32_t bar, uint32_t parity) { MBAR_WAIT_ASM(".acquire.cluster"); }
__device__ __forceinline__ bool mbar_wait_brief(uint32_t bar, uint32_t parity) {
  uint32_t ok;
  asm volatile("{\n.reg .pred p;\nmbarrier.try_wait.parity.shared::cta.b64 p, [%1], %2, 1000;\nselp.u32 %0, 1, 0, p;\n}"
               : "=r"(ok) : "r"(bar), "r"(parity) : "memory");
  return __all_sync(0xffffffffu, ok);
}
__device__ __forceinline__ void st_async2(uint32_t addr, float a, float b, uint32_t bar) {
  asm volatile("st.async.weak.shared::cluster.mbarrier::complete_tx::bytes.v2.f32 [%0], {%1, %2}, [%3];"
               ::"r"(addr), "f"(a), "f"(b), "r"(bar) : "memory");
}
__device__ __forceinline__ uint64_t policy_evict_first() {
  uint64_t p; asm volatile("createpolicy.fractional.L2::evict_first.b64 %0, 1.0;" : "=l"(p)); return p;
}
__device__ __forceinline__ uint64_t policy_normal() {
  uint64_t p; asm volatile("createpolicy.fractional.L2::evict_normal.b64 %0, 1.0;" : "=l"(p)); return p;
}
__device__ __forceinline__ void tma_load2(uint32_t dst, const CUtensorMap* m, int c0, int c1, uint32_t bar) {
  asm volatile(ELECT "cp.async.bulk.tensor.2d.shared::cluster.global.mbarrier::complete_tx::bytes [%0], [%1, {%3, %4}], [%2];\n}"
               ::"r"(dst), "l"(m), "r"(bar), "r"(c0), "r"(c1) : "memory");
}
__device__ __forceinline__ void tma_load2_h(uint32_t dst, const CUtensorMap* m, int c0, int c1, uint32_t bar, uint64_t pol) {
  asm volatile(ELECT "cp.async.bulk.tensor.2d.shared::cluster.global.mbarrier::complete_tx::bytes.L2::cache_hint [%0], [%1, {%3, %4}], [%2], %5;\n}"
               ::"r"(dst), "l"(m), "r"(bar), "r"(c0), "r"(c1), "l"(pol) : "memory");
}
__device__ __forceinline__ void tma_load3(uint32_t dst, const CUtensorMap* m, int c0, int c1, int c2, uint32_t bar) {
  asm volatile(ELECT "cp.async.bulk.tensor.3d.shared::cluster.global.mbarrier::complete_tx::bytes [%0], [%1, {%3, %4, %5}], [%2];\n}"
               ::"r"(dst), "l"(m), "r"(bar), "r"(c0), "r"(c1), "r"(c2) : "memory");
}
__device__ __forceinline__ void tma_load3_h(uint32_t dst, const CUtensorMap* m, int c0, int c1, int c2, uint32_t bar, uint64_t pol) {
  asm volatile(ELECT "cp.async.bulk.tensor.3d.shared::cluster.global.mbarrier::complete_tx::bytes.L2::cache_hint [%0], [%1, {%3, %4, %5}], [%2], %6;\n}"
               ::"r"(dst), "l"(m), "r"(bar), "r"(c0), "r"(c1), "r"(c2), "l"(pol) : "memory");
}
__device__ __forceinline__ void tma_load3_mc(uint32_t dst, const CUtensorMap* m, int c0, int c1, int c2, uint32_t bar) {
  asm volatile(ELECT "cp.async.bulk.tensor.3d.shared::cluster.global.mbarrier::complete_tx::bytes.multicast::cluster [%0], [%1, {%3, %4, %5}], [%2], %6;\n}"
               ::"r"(dst), "l"(m), "r"(bar), "r"(c0), "r"(c1), "r"(c2), "h"((uint16_t)3) : "memory");
}
__device__ __forceinline__ void bulk_push(uint32_t dst, uint32_t src, uint32_t bytes, uint32_t bar) {
  asm volatile(ELECT "cp.async.bulk.shared::cluster.shared::cta.mbarrier::complete_tx::bytes [%0], [%1], %2, [%3];\n}"
               ::"r"(dst), "r"(src), "r"(bytes), "r"(bar) : "memory");
}
template <int N> __device__ __forceinline__ void regs_inc() { asm volatile("setmaxnreg.inc.sync.aligned.u32 %0;" ::"n"(N)); }
template <int N> __device__ __forceinline__ void regs_dec() { asm volatile("setmaxnreg.dec.sync.aligned.u32 %0;" ::"n"(N)); }
__device__ __forceinline__ void tma_prefetch2(const CUtensorMap* m, int c0, int c1) {
  asm volatile(ELECT "cp.async.bulk.prefetch.tensor.2d.L2.global [%0, {%1, %2}];\n}" ::"l"(m), "r"(c0), "r"(c1) : "memory");
}
__device__ __forceinline__ void bulk_prefetch(const void* p, uint32_t bytes) {
  asm volatile(ELECT "cp.async.bulk.prefetch.L2.global [%0], %1;\n}" ::"l"(p), "r"(bytes) : "memory");
}
__device__ __forceinline__ void tma_store(const CUtensorMap* m, uint32_t src, int c0, int c1) {
  asm volatile(ELECT "cp.async.bulk.tensor.2d.global.shared::cta.bulk_group [%0, {%2, %3}], [%1];\n}"
               ::"l"(m), "r"(src), "r"(c0), "r"(c1) : "memory");
}
__device__ __forceinline__ void bulk_load(uint32_t dst, const void* src, uint32_t bytes, uint32_t bar) {
  asm volatile(ELECT "cp.async.bulk.shared::cluster.global.mbarrier::complete_tx::bytes [%0], [%1], %2, [%3];\n}"
               ::"r"(dst), "l"(src), "r"(bytes), "r"(bar) : "memory");
}
__device__ __forceinline__ void bulk_load_h(uint32_t dst, const void* src, uint32_t bytes, uint32_t bar, uint64_t pol) {
  asm volatile(ELECT "cp.async.bulk.shared::cluster.global.mbarrier::complete_tx::bytes.L2::cache_hint [%0], [%1], %2, [%3], %4;\n}"
               ::"r"(dst), "l"(src), "r"(bytes), "r"(bar), "l"(pol) : "memory");
}
__device__ __forceinline__ void bulk_store(void* dst, uint32_t src, uint32_t bytes) {
  asm volatile(ELECT "cp.async.bulk.global.shared::cta.bulk_group [%0], [%1], %2;\n}" ::"l"(dst), "r"(src), "r"(bytes) : "memory");
}
__device__ __forceinline__ void bulk_commit() { asm volatile("cp.async.bulk.commit_group;" ::: "memory"); }
__device__ __forceinline__ void bulk_wait_all() { asm volatile("cp.async.bulk.wait_group 0;" ::: "memory"); }
__device__ __forceinline__ void fence_async_smem() { asm volatile("fence.proxy.async.shared::cta;" ::: "memory"); }
__device__ __forceinline__ void fence_async_global() { asm volatile("fence.proxy.async.global;" ::: "memory"); }
__device__ __forceinline__ void fence_release() { asm volatile("fence.release.gpu;" ::: "memory"); }
__device__ __forceinline__ void l2_prefetch_line(const void* p) { asm volatile("prefetch.global.L2 [%0];" ::"l"(p) : "memory"); }
__device__ __forceinline__ void prefetch_tmap(const CUtensorMap* m) { asm volatile("prefetch.tensormap [%0];" ::"l"(m) : "memory"); }
__device__ __forceinline__ void named_bar(int id, int n) { asm volatile("bar.sync %0, %1;" ::"r"(id), "r"(n) : "memory"); }
__device__ __forceinline__ bool bar_red_or(int id, int n, bool v) {
  uint32_t r;
  asm volatile("{\n.reg .pred p, q;\nsetp.ne.u32 q, %3, 0;\nbarrier.cta.red.or.pred p, %1, %2, q;\nselp.u32 %0, 1, 0, p;\n}"
               : "=r"(r) : "r"(id), "r"(n), "r"((uint32_t)v) : "memory");
  return r != 0;
}
__device__ __forceinline__ void cluster_arrive() { asm volatile("barrier.cluster.arrive.relaxed.aligned;" ::: "memory"); }
__device__ __forceinline__ void cluster_wait() { asm volatile("barrier.cluster.wait.aligned;" ::: "memory"); }
__device__ __forceinline__ uint32_t cluster_rank() { uint32_t r; asm volatile("mov.u32 %0, %%cluster_ctarank;" : "=r"(r)); return r; }
__device__ __forceinline__ unsigned ld_relaxed(const unsigned* p) {
  unsigned v; asm volatile("ld.relaxed.gpu.global.u32 %0, [%1];" : "=r"(v) : "l"(p) : "memory"); return v;
}
__device__ __forceinline__ uint4 ld_relaxed4(const uint4* p) {
  uint4 v; asm volatile("ld.relaxed.gpu.global.v4.u32 {%0, %1, %2, %3}, [%4];" : "=r"(v.x), "=r"(v.y), "=r"(v.z), "=r"(v.w) : "l"(p) : "memory"); return v;
}
__device__ __forceinline__ void st_relaxed(unsigned* p, unsigned v) {
  asm volatile("st.relaxed.gpu.global.u32 [%0], %1;" ::"l"(p), "r"(v) : "memory");
}
__device__ __forceinline__ uint2 ld_relaxed2(const void* p) {
  uint2 v; asm volatile("ld.relaxed.gpu.global.v2.u32 {%0, %1}, [%2];" : "=r"(v.x), "=r"(v.y) : "l"(p) : "memory"); return v;
}
__device__ __forceinline__ void st_relaxed4(uint4* p, uint4 v) {
  asm volatile("st.relaxed.gpu.global.v4.u32 [%0], {%1, %2, %3, %4};" ::"l"(p), "r"(v.x), "r"(v.y), "r"(v.z), "r"(v.w) : "memory");
}
__device__ __forceinline__ bool valid4(uint4 v) { return v.x != SENT && v.y != SENT && v.z != SENT && v.w != SENT; }
__device__ __forceinline__ uint4 poll4(const uint4* p) {
  uint4 v;
  uint32_t spins = 0;
#pragma unroll 1
  do { v = ld_relaxed4(p); } while (!valid4(v) && ++spins < SPIN_LIMIT);
  return v;
}
__device__ __forceinline__ void set_flag(unsigned* p, unsigned tag) {
  asm volatile(ELECT "st.release.gpu.global.u32 [%0], %1;\n}" ::"l"(p), "r"(tag) : "memory");
}
__device__ __forceinline__ void poll_flag(const unsigned* p, unsigned tag) {
#pragma unroll 1
  for (uint32_t spins = 0; !__all_sync(0xffffffffu, ld_relaxed(p) == tag) && spins < SPIN_LIMIT; spins++) {}
  asm volatile("fence.acquire.gpu;" ::: "memory");
}
__device__ __forceinline__ uint32_t enc(float x) { return __float_as_uint(x + 0.0f) ^ 0x80000000u; }
__device__ __forceinline__ float dec(uint32_t u) { return __uint_as_float(u ^ 0x80000000u); }
__device__ __forceinline__ uint32_t f2u(float x) { uint32_t u = __float_as_uint(x); return u == SENT ? 0x7FFFFFFFu : u; }
__device__ __forceinline__ uint32_t nosent(uint32_t u) { return u == SENT ? 0x7FFF7FFFu : u; }
__device__ __forceinline__ uint32_t hadd_bf2(uint32_t a, uint32_t b) {
  uint32_t r; asm("add.rn.bf16x2 %0, %1, %2;" : "=r"(r) : "r"(a), "r"(b)); return r;
}
__device__ __forceinline__ uint32_t hsub_bf2(uint32_t a, uint32_t b) {
  uint32_t r; asm("sub.rn.bf16x2 %0, %1, %2;" : "=r"(r) : "r"(a), "r"(b)); return r;
}
__device__ __forceinline__ void wg_fence() { asm volatile("wgmma.fence.sync.aligned;" ::: "memory"); }
__device__ __forceinline__ void wg_commit() { asm volatile("wgmma.commit_group.sync.aligned;" ::: "memory"); }
template <int N> __device__ __forceinline__ void wg_wait() { asm volatile("wgmma.wait_group.sync.aligned %0;" ::"n"(N) : "memory"); }
template <int R> __device__ __forceinline__ void fence_regs(float* d) {
#pragma unroll
  for (int i = 0; i < R; i++) asm volatile("" : "+f"(d[i])::"memory");
}
template <int R> __device__ __forceinline__ void fence_regs_u(uint32_t* d) {
#pragma unroll
  for (int i = 0; i < R; i++) asm volatile("" : "+r"(d[i])::"memory");
}
__host__ __device__ constexpr uint32_t dlo(uint32_t addr, uint32_t lbo) { return ((addr & 0x3FFFF) >> 4) | ((lbo >> 4) << 16); }
constexpr uint32_t H128 = 0x40000040u, H64 = 0x80000020u;
__device__ __forceinline__ void stsm_x4(uint32_t addr, uint32_t r0, uint32_t r1, uint32_t r2, uint32_t r3) {
  asm volatile("stmatrix.sync.aligned.m8n8.x4.shared.b16 [%0], {%1, %2, %3, %4};"
               ::"r"(addr), "r"(r0), "r"(r1), "r"(r2), "r"(r3) : "memory");
}
__device__ __forceinline__ void ldsm_x4(uint32_t addr, uint32_t& r0, uint32_t& r1, uint32_t& r2, uint32_t& r3) {
  asm volatile("ldmatrix.sync.aligned.m8n8.x4.shared.b16 {%0, %1, %2, %3}, [%4];"
               : "=r"(r0), "=r"(r1), "=r"(r2), "=r"(r3) : "r"(addr) : "memory");
}
__device__ __forceinline__ void ldsm_x4_t(uint32_t addr, uint32_t& r0, uint32_t& r1, uint32_t& r2, uint32_t& r3) {
  asm volatile("ldmatrix.sync.aligned.m8n8.x4.trans.shared.b16 {%0, %1, %2, %3}, [%4];"
               : "=r"(r0), "=r"(r1), "=r"(r2), "=r"(r3) : "r"(addr) : "memory");
}
__device__ __forceinline__ void mma_16816(float* d, uint32_t a0, uint32_t a1, uint32_t a2, uint32_t a3, uint32_t b0, uint32_t b1) {
  asm volatile("mma.sync.aligned.m16n8k16.row.col.f32.bf16.bf16.f32 {%0, %1, %2, %3}, {%4, %5, %6, %7}, {%8, %9}, {%0, %1, %2, %3};"
               : "+f"(d[0]), "+f"(d[1]), "+f"(d[2]), "+f"(d[3]) : "r"(a0), "r"(a1), "r"(a2), "r"(a3), "r"(b0), "r"(b1));
}
__device__ __forceinline__ void spin_cycles(int n) {
  const int t0 = (int)clock();
#pragma unroll 1
  while ((int)clock() - t0 < n) {}
}
__device__ __forceinline__ uint32_t pack_bf16(float lo, float hi) {
  uint32_t r; asm("cvt.rn.bf16x2.f32 %0, %1, %2;" : "=r"(r) : "f"(hi), "f"(lo)); return r;
}
__device__ __forceinline__ float bf_lo(uint32_t v) { return __uint_as_float(v << 16); }
__device__ __forceinline__ float bf_hi(uint32_t v) { return __uint_as_float(v & 0xffff0000u); }
__device__ __forceinline__ float rbf(float x) { return __bfloat162float(__float2bfloat16_rn(x)); }
__device__ __forceinline__ float ex2(float x) { float y; asm("ex2.approx.ftz.f32 %0, %1;" : "=f"(y) : "f"(x)); return y; }
__device__ __forceinline__ uint32_t shl_clamp(uint32_t v, uint32_t n) {
  uint32_t r; asm("shl.b32 %0, %1, %2;" : "=r"(r) : "r"(v), "r"(n)); return r;
}
__device__ __forceinline__ float warp_sum(float v) {
#pragma unroll
  for (int o = 16; o > 0; o >>= 1) v += __shfl_xor_sync(0xffffffffu, v, o);
  return v;
}
__device__ __forceinline__ float ln_inv(float var) {
  float r;
  asm("sqrt.approx.ftz.f32 %0, %1;" : "=f"(r) : "f"(rbf(rbf(var) + LN_EPS)));
  asm("rcp.approx.ftz.f32 %0, %1;" : "=f"(r) : "f"(rbf(r)));
  return r;
}
__device__ __forceinline__ uint32_t ln_pair(uint32_t x, uint32_t mean2, float inv) {
  const uint32_t d = hsub_bf2(x, mean2);
  return pack_bf16(bf_lo(d) * inv, bf_hi(d) * inv);
}
__device__ __forceinline__ uint32_t add_ln_pair(uint32_t x, uint32_t mean2, float inv) { return hadd_bf2(x, ln_pair(x, mean2, inv)); }
__device__ __forceinline__ uint32_t router_key(float r_bf, int row) {
  uint32_t u = __float_as_uint(r_bf);
  u = (u & 0x80000000u) ? ~u : (u | 0x80000000u);
  return (u & 0xFFFF0000u) | 0x8000u | (uint32_t)(SEQ - 1 - row);
}

template <uint32_t HA = 0x40000040u, uint32_t HB = 0x40000040u>
__device__ __forceinline__ void wg_ss192t(float* d, uint32_t da, uint32_t db, int scale_d) {
  asm volatile("{\n.reg .pred p;\n.reg .b64 dA, dB;\nmov.b64 dA, {%96, %99};\nmov.b64 dB, {%97, %100};\nsetp.ne.b32 p, %98, 0;\n"
    "wgmma.mma_async.sync.aligned.m64n192k16.f32.bf16.bf16 "
    "{%0, %1, %2, %3, %4, %5, %6, %7, %8, %9, %10, %11, %12, %13, %14, %15, "
    "%16, %17, %18, %19, %20, %21, %22, %23, %24, %25, %26, %27, %28, %29, %30, %31, "
    "%32, %33, %34, %35, %36, %37, %38, %39, %40, %41, %42, %43, %44, %45, %46, %47, "
    "%48, %49, %50, %51, %52, %53, %54, %55, %56, %57, %58, %59, %60, %61, %62, %63, "
    "%64, %65, %66, %67, %68, %69, %70, %71, %72, %73, %74, %75, %76, %77, %78, %79, "
    "%80, %81, %82, %83, %84, %85, %86, %87, %88, %89, %90, %91, %92, %93, %94, %95}, "
    "dA, dB, p, 1, 1, 0, 1;\n}\n"
    : "+f"(d[0]), "+f"(d[1]), "+f"(d[2]), "+f"(d[3]), "+f"(d[4]), "+f"(d[5]), "+f"(d[6]), "+f"(d[7]),
      "+f"(d[8]), "+f"(d[9]), "+f"(d[10]), "+f"(d[11]), "+f"(d[12]), "+f"(d[13]), "+f"(d[14]), "+f"(d[15]),
      "+f"(d[16]), "+f"(d[17]), "+f"(d[18]), "+f"(d[19]), "+f"(d[20]), "+f"(d[21]), "+f"(d[22]), "+f"(d[23]),
      "+f"(d[24]), "+f"(d[25]), "+f"(d[26]), "+f"(d[27]), "+f"(d[28]), "+f"(d[29]), "+f"(d[30]), "+f"(d[31]),
      "+f"(d[32]), "+f"(d[33]), "+f"(d[34]), "+f"(d[35]), "+f"(d[36]), "+f"(d[37]), "+f"(d[38]), "+f"(d[39]),
      "+f"(d[40]), "+f"(d[41]), "+f"(d[42]), "+f"(d[43]), "+f"(d[44]), "+f"(d[45]), "+f"(d[46]), "+f"(d[47]),
      "+f"(d[48]), "+f"(d[49]), "+f"(d[50]), "+f"(d[51]), "+f"(d[52]), "+f"(d[53]), "+f"(d[54]), "+f"(d[55]),
      "+f"(d[56]), "+f"(d[57]), "+f"(d[58]), "+f"(d[59]), "+f"(d[60]), "+f"(d[61]), "+f"(d[62]), "+f"(d[63]),
      "+f"(d[64]), "+f"(d[65]), "+f"(d[66]), "+f"(d[67]), "+f"(d[68]), "+f"(d[69]), "+f"(d[70]), "+f"(d[71]),
      "+f"(d[72]), "+f"(d[73]), "+f"(d[74]), "+f"(d[75]), "+f"(d[76]), "+f"(d[77]), "+f"(d[78]), "+f"(d[79]),
      "+f"(d[80]), "+f"(d[81]), "+f"(d[82]), "+f"(d[83]), "+f"(d[84]), "+f"(d[85]), "+f"(d[86]), "+f"(d[87]),
      "+f"(d[88]), "+f"(d[89]), "+f"(d[90]), "+f"(d[91]), "+f"(d[92]), "+f"(d[93]), "+f"(d[94]), "+f"(d[95])
    : "r"(da), "r"(db), "r"(scale_d), "n"(HA), "n"(HB));
}
template <uint32_t HA = 0x40000040u, uint32_t HB = 0x40000040u>
__device__ __forceinline__ void wg_ss128t(float* d, uint32_t da, uint32_t db, int scale_d) {
  asm volatile("{\n.reg .pred p;\n.reg .b64 dA, dB;\nmov.b64 dA, {%64, %67};\nmov.b64 dB, {%65, %68};\nsetp.ne.b32 p, %66, 0;\n"
    "wgmma.mma_async.sync.aligned.m64n128k16.f32.bf16.bf16 "
    "{%0, %1, %2, %3, %4, %5, %6, %7, %8, %9, %10, %11, %12, %13, %14, %15, "
    "%16, %17, %18, %19, %20, %21, %22, %23, %24, %25, %26, %27, %28, %29, %30, %31, "
    "%32, %33, %34, %35, %36, %37, %38, %39, %40, %41, %42, %43, %44, %45, %46, %47, "
    "%48, %49, %50, %51, %52, %53, %54, %55, %56, %57, %58, %59, %60, %61, %62, %63}, "
    "dA, dB, p, 1, 1, 0, 1;\n}\n"
    : "+f"(d[0]), "+f"(d[1]), "+f"(d[2]), "+f"(d[3]), "+f"(d[4]), "+f"(d[5]), "+f"(d[6]), "+f"(d[7]),
      "+f"(d[8]), "+f"(d[9]), "+f"(d[10]), "+f"(d[11]), "+f"(d[12]), "+f"(d[13]), "+f"(d[14]), "+f"(d[15]),
      "+f"(d[16]), "+f"(d[17]), "+f"(d[18]), "+f"(d[19]), "+f"(d[20]), "+f"(d[21]), "+f"(d[22]), "+f"(d[23]),
      "+f"(d[24]), "+f"(d[25]), "+f"(d[26]), "+f"(d[27]), "+f"(d[28]), "+f"(d[29]), "+f"(d[30]), "+f"(d[31]),
      "+f"(d[32]), "+f"(d[33]), "+f"(d[34]), "+f"(d[35]), "+f"(d[36]), "+f"(d[37]), "+f"(d[38]), "+f"(d[39]),
      "+f"(d[40]), "+f"(d[41]), "+f"(d[42]), "+f"(d[43]), "+f"(d[44]), "+f"(d[45]), "+f"(d[46]), "+f"(d[47]),
      "+f"(d[48]), "+f"(d[49]), "+f"(d[50]), "+f"(d[51]), "+f"(d[52]), "+f"(d[53]), "+f"(d[54]), "+f"(d[55]),
      "+f"(d[56]), "+f"(d[57]), "+f"(d[58]), "+f"(d[59]), "+f"(d[60]), "+f"(d[61]), "+f"(d[62]), "+f"(d[63])
    : "r"(da), "r"(db), "r"(scale_d), "n"(HA), "n"(HB));
}
template <uint32_t HB = 0x40000040u>
__device__ __forceinline__ void wg_rs64(float* d, uint32_t a0, uint32_t a1, uint32_t a2, uint32_t a3, uint32_t db, int scale_d) {
  asm volatile("{\n.reg .pred p;\n.reg .b64 dB;\nmov.b64 dB, {%36, %38};\nsetp.ne.b32 p, %37, 0;\n"
    "wgmma.mma_async.sync.aligned.m64n64k16.f32.bf16.bf16 "
    "{%0, %1, %2, %3, %4, %5, %6, %7, %8, %9, %10, %11, %12, %13, %14, %15, "
    "%16, %17, %18, %19, %20, %21, %22, %23, %24, %25, %26, %27, %28, %29, %30, %31}, "
    "{%32, %33, %34, %35}, dB, p, 1, 1, 0;\n}\n"
    : "+f"(d[0]), "+f"(d[1]), "+f"(d[2]), "+f"(d[3]), "+f"(d[4]), "+f"(d[5]), "+f"(d[6]), "+f"(d[7]),
      "+f"(d[8]), "+f"(d[9]), "+f"(d[10]), "+f"(d[11]), "+f"(d[12]), "+f"(d[13]), "+f"(d[14]), "+f"(d[15]),
      "+f"(d[16]), "+f"(d[17]), "+f"(d[18]), "+f"(d[19]), "+f"(d[20]), "+f"(d[21]), "+f"(d[22]), "+f"(d[23]),
      "+f"(d[24]), "+f"(d[25]), "+f"(d[26]), "+f"(d[27]), "+f"(d[28]), "+f"(d[29]), "+f"(d[30]), "+f"(d[31])
    : "r"(a0), "r"(a1), "r"(a2), "r"(a3), "r"(db), "r"(scale_d), "n"(HB));
}
template <uint32_t HB = 0x40000040u>
__device__ __forceinline__ void wg_rs64_z(float* d, uint32_t a0, uint32_t a1, uint32_t a2, uint32_t a3, uint32_t db) {
  asm volatile("{\n.reg .pred p;\n.reg .b64 dB;\nmov.b64 dB, {%36, %37};\nsetp.ne.b32 p, 0, 0;\n"
    "wgmma.mma_async.sync.aligned.m64n64k16.f32.bf16.bf16 "
    "{%0, %1, %2, %3, %4, %5, %6, %7, %8, %9, %10, %11, %12, %13, %14, %15, "
    "%16, %17, %18, %19, %20, %21, %22, %23, %24, %25, %26, %27, %28, %29, %30, %31}, "
    "{%32, %33, %34, %35}, dB, p, 1, 1, 0;\n}\n"
    : "=f"(d[0]), "=f"(d[1]), "=f"(d[2]), "=f"(d[3]), "=f"(d[4]), "=f"(d[5]), "=f"(d[6]), "=f"(d[7]),
      "=f"(d[8]), "=f"(d[9]), "=f"(d[10]), "=f"(d[11]), "=f"(d[12]), "=f"(d[13]), "=f"(d[14]), "=f"(d[15]),
      "=f"(d[16]), "=f"(d[17]), "=f"(d[18]), "=f"(d[19]), "=f"(d[20]), "=f"(d[21]), "=f"(d[22]), "=f"(d[23]),
      "=f"(d[24]), "=f"(d[25]), "=f"(d[26]), "=f"(d[27]), "=f"(d[28]), "=f"(d[29]), "=f"(d[30]), "=f"(d[31])
    : "r"(a0), "r"(a1), "r"(a2), "r"(a3), "r"(db), "n"(HB));
}
template <uint32_t HB = 0x40000040u>
__device__ __forceinline__ void wg_rs32(float* d, uint32_t a0, uint32_t a1, uint32_t a2, uint32_t a3, uint32_t db, int scale_d) {
  asm volatile("{\n.reg .pred p;\n.reg .b64 dB;\nmov.b64 dB, {%20, %22};\nsetp.ne.b32 p, %21, 0;\n"
    "wgmma.mma_async.sync.aligned.m64n32k16.f32.bf16.bf16 "
    "{%0, %1, %2, %3, %4, %5, %6, %7, %8, %9, %10, %11, %12, %13, %14, %15}, "
    "{%16, %17, %18, %19}, dB, p, 1, 1, 0;\n}\n"
    : "+f"(d[0]), "+f"(d[1]), "+f"(d[2]), "+f"(d[3]), "+f"(d[4]), "+f"(d[5]), "+f"(d[6]), "+f"(d[7]),
      "+f"(d[8]), "+f"(d[9]), "+f"(d[10]), "+f"(d[11]), "+f"(d[12]), "+f"(d[13]), "+f"(d[14]), "+f"(d[15])
    : "r"(a0), "r"(a1), "r"(a2), "r"(a3), "r"(db), "r"(scale_d), "n"(HB));
}
template <uint32_t HB = 0x40000040u>
__device__ __forceinline__ void wg_rs32_z(float* d, uint32_t a0, uint32_t a1, uint32_t a2, uint32_t a3, uint32_t db) {
  asm volatile("{\n.reg .pred p;\n.reg .b64 dB;\nmov.b64 dB, {%20, %21};\nsetp.ne.b32 p, 0, 0;\n"
    "wgmma.mma_async.sync.aligned.m64n32k16.f32.bf16.bf16 "
    "{%0, %1, %2, %3, %4, %5, %6, %7, %8, %9, %10, %11, %12, %13, %14, %15}, "
    "{%16, %17, %18, %19}, dB, p, 1, 1, 0;\n}\n"
    : "=f"(d[0]), "=f"(d[1]), "=f"(d[2]), "=f"(d[3]), "=f"(d[4]), "=f"(d[5]), "=f"(d[6]), "=f"(d[7]),
      "=f"(d[8]), "=f"(d[9]), "=f"(d[10]), "=f"(d[11]), "=f"(d[12]), "=f"(d[13]), "=f"(d[14]), "=f"(d[15])
    : "r"(a0), "r"(a1), "r"(a2), "r"(a3), "r"(db), "n"(HB));
}
template <uint32_t HB = 0x40000040u>
__device__ __forceinline__ void wg_rs40t(float* d, uint32_t a0, uint32_t a1, uint32_t a2, uint32_t a3, uint32_t db, int scale_d) {
  asm volatile("{\n.reg .pred p;\n.reg .b64 dB;\nmov.b64 dB, {%24, %26};\nsetp.ne.b32 p, %25, 0;\n"
    "wgmma.mma_async.sync.aligned.m64n40k16.f32.bf16.bf16 "
    "{%0, %1, %2, %3, %4, %5, %6, %7, %8, %9, %10, %11, %12, %13, %14, %15, "
    "%16, %17, %18, %19}, "
    "{%20, %21, %22, %23}, dB, p, 1, 1, 1;\n}\n"
    : "+f"(d[0]), "+f"(d[1]), "+f"(d[2]), "+f"(d[3]), "+f"(d[4]), "+f"(d[5]), "+f"(d[6]), "+f"(d[7]),
      "+f"(d[8]), "+f"(d[9]), "+f"(d[10]), "+f"(d[11]), "+f"(d[12]), "+f"(d[13]), "+f"(d[14]), "+f"(d[15]),
      "+f"(d[16]), "+f"(d[17]), "+f"(d[18]), "+f"(d[19])
    : "r"(a0), "r"(a1), "r"(a2), "r"(a3), "r"(db), "r"(scale_d), "n"(HB));
}
template <uint32_t HB = 0x40000040u>
__device__ __forceinline__ void wg_rs40t_z(float* d, uint32_t a0, uint32_t a1, uint32_t a2, uint32_t a3, uint32_t db) {
  asm volatile("{\n.reg .pred p;\n.reg .b64 dB;\nmov.b64 dB, {%24, %25};\nsetp.ne.b32 p, 0, 0;\n"
    "wgmma.mma_async.sync.aligned.m64n40k16.f32.bf16.bf16 "
    "{%0, %1, %2, %3, %4, %5, %6, %7, %8, %9, %10, %11, %12, %13, %14, %15, "
    "%16, %17, %18, %19}, "
    "{%20, %21, %22, %23}, dB, p, 1, 1, 1;\n}\n"
    : "=f"(d[0]), "=f"(d[1]), "=f"(d[2]), "=f"(d[3]), "=f"(d[4]), "=f"(d[5]), "=f"(d[6]), "=f"(d[7]),
      "=f"(d[8]), "=f"(d[9]), "=f"(d[10]), "=f"(d[11]), "=f"(d[12]), "=f"(d[13]), "=f"(d[14]), "=f"(d[15]),
      "=f"(d[16]), "=f"(d[17]), "=f"(d[18]), "=f"(d[19])
    : "r"(a0), "r"(a1), "r"(a2), "r"(a3), "r"(db), "n"(HB));
}

constexpr uint32_t SOFF = 1024;
constexpr int STG = 57344, SL_W = 32768, SL_HD = 12288, SL_F = 3 * STG, AT_ST = 131072;
constexpr int OFF_ONES = 4 * STG;
constexpr int OFF_PATCH = OFF_ONES + 1024;
constexpr int OFF_CS = OFF_PATCH + 768;
constexpr int OFF_BAR = OFF_CS + 768;
constexpr int OFF_MISC = OFF_BAR + 384;
constexpr int SMEM_BYTES = OFF_MISC + 128;
enum { B_FULL = 0, B_EMPTY = 3, B_HALO = 6, B_CS = 9, B_KVREADY, B_QDONE = B_KVREADY + 2, B_QREADY, B_OST, B_ADONE = B_OST + 2,
       B_QFREE, B_WS, B_WFULL, B_WEMPTY = B_WFULL + 4, B_GU = B_WEMPTY + 4, B_RES = B_GU + 2, B_DN,
       B_HX = B_DN + 2, B_RST, B_WGO, B_COUNT = B_WGO + 2 };
static_assert(B_COUNT <= 48, "barrier area");
__host__ __device__ constexpr int bar_count(int i) {
  return i >= B_EMPTY && i < B_HALO ? 17 : i == B_CS ? 4 : i == B_QFREE ? 16
       : i == B_KVREADY || i == B_KVREADY + 1 || i == B_QREADY ? 8 : i == B_ADONE ? 6 : i == B_OST ? 32 : i == B_OST + 1 ? 12
       : i == B_QDONE || (i >= B_WEMPTY && i < B_GU) ? 16 : i == B_RST ? 4 : i == B_RES ? 2 : 1;
}
enum { M_KEY = 0, M_MEAN, M_INV, M_WSUM, M_TAG, M_SEL0, M_PMEAN, M_PINV, M_XQ = 8, M_KEYS = 12 };
constexpr int FFN_PIECE = 14336;
constexpr int T_XS = 163840, T_HP = T_XS + 1024;
constexpr int HELP_GR = 8;
constexpr float LSUM_MIN = 5.421010862427522e-20f, LSUM_MAX = 1.8446744073709552e19f;
constexpr float SM_C = 0.17677669529663687f * 1.4426950408889634f;
constexpr uint32_t VSTEP = 64u - (64u << 16);
#define FFN_POL policy_evict_first()
#define D_SPLIT 1
#define GUA_AT 2
#define GUB_PACE 1400
#define RES_K 3
#define REL_NOW 0
#define FAKE 0
#define X_STAGGER 500
#define GU_PACE1 2000
#define GU_PACE 2500
#define DELAY_P 600
#define DELAY_S 2000
#define DELAY_Y 700

struct Params {
  CUtensorMap mapA[2], mapW, mapWo, mapRes[2], mapXst[2], mapG, mapU, mapD;
  const bf16 *x, *wqkv, *wo, *w_r, *w_g, *w_u, *w_d;
  bf16* out;
  int helper_first;
};

template <int N> __device__ __forceinline__ void exp_pack(const float* s, uint32_t* p) {
#pragma unroll
  for (int b = 0; b < N; b++) {
    p[2 * b] = pack_bf16(ex2(s[4 * b]), ex2(s[4 * b + 1]));
    p[2 * b + 1] = pack_bf16(ex2(s[4 * b + 2]), ex2(s[4 * b + 3]));
  }
}
template <int KIND> __device__ __forceinline__ void edge16(const float* sd, const float* st, uint32_t* pd, uint32_t* pt, int dl, uint32_t mt) {
  if (KIND == 0) { exp_pack<2>(sd, pd); pt[0] = pt[1] = pt[2] = pt[3] = 0; }
  else if (KIND == 1) { exp_pack<2>(st, pt); pd[0] = pd[1] = pd[2] = pd[3] = 0; }
  else {
    const uint32_t a = pack_bf16(ex2(dl >= 0 ? sd[0] : st[0]), ex2(dl >= 1 ? sd[1] : st[1]));
    const uint32_t c = pack_bf16(ex2(dl >= 0 ? sd[6] : st[6]), ex2(dl >= 1 ? sd[7] : st[7]));
    pd[0] = a & ~mt; pt[0] = a & mt; pd[3] = c & ~mt; pt[3] = c & mt;
    pd[1] = pack_bf16(ex2(sd[2]), ex2(sd[3])); pt[1] = 0;
    pt[2] = pack_bf16(ex2(st[4]), ex2(st[5])); pd[2] = 0;
  }
}
__device__ __forceinline__ void edge32(const float* sd, const float* st, uint32_t* pd, uint32_t* pt, int rel, int dl, uint32_t mt) {
  if (rel > 1) { edge16<0>(sd, st, pd, pt, dl, mt); edge16<0>(sd + 8, st + 8, pd + 4, pt + 4, dl, mt); }
  else if (rel == 1) { edge16<0>(sd, st, pd, pt, dl, mt); edge16<2>(sd + 8, st + 8, pd + 4, pt + 4, dl, mt); }
  else if (rel == 0) { edge16<2>(sd, st, pd, pt, dl, mt); edge16<1>(sd + 8, st + 8, pd + 4, pt + 4, dl, mt); }
  else { edge16<1>(sd, st, pd, pt, dl, mt); edge16<1>(sd + 8, st + 8, pd + 4, pt + 4, dl, mt); }
}
__device__ __forceinline__ void qk64(float* s, const uint32_t* qf, uint32_t kd) {
  wg_rs64_z<H64>(s, qf[0], qf[1], qf[2], qf[3], kd);
  wg_rs64<H64>(s, qf[4], qf[5], qf[6], qf[7], kd + 2, 1);
}
__device__ __forceinline__ void qk32x2(float* a, float* b, const uint32_t* qf, uint32_t ka, uint32_t kb) {
  wg_rs32_z<H64>(a, qf[0], qf[1], qf[2], qf[3], ka); wg_rs32_z<H64>(b, qf[0], qf[1], qf[2], qf[3], kb);
  wg_rs32<H64>(a, qf[4], qf[5], qf[6], qf[7], ka + 2, 1); wg_rs32<H64>(b, qf[4], qf[5], qf[6], qf[7], kb + 2, 1);
}
__device__ __forceinline__ void pv32(float* o, const uint32_t* p, uint32_t vd) {
  wg_rs40t<H64>(o, p[0], p[1], p[2], p[3], vd, 1);
  wg_rs40t<H64>(o, p[4], p[5], p[6], p[7], vd + VSTEP, 1);
}

__device__ __forceinline__ void fma8(float* d, uint4 w, float x) {
  d[0] += x * bf_lo(w.x); d[1] += x * bf_hi(w.x); d[2] += x * bf_lo(w.y); d[3] += x * bf_hi(w.y);
  d[4] += x * bf_lo(w.z); d[5] += x * bf_hi(w.z); d[6] += x * bf_lo(w.w); d[7] += x * bf_hi(w.w);
}

__device__ __forceinline__ int fresh_tid() { int r; asm volatile("mov.u32 %0, %%tid.x;" : "=r"(r)); return r; }
__device__ __forceinline__ int fresh_bid() { int r; asm volatile("mov.u32 %0, %%ctaid.x;" : "=r"(r)); return r; }
#define PHASE_IDS                                                                                                              \
  const uint32_t sbase = smem_u32(smem);                                                                                       \
  const int tid = fresh_tid(), bid = fresh_bid();                                                                              \
  const int warp = __shfl_sync(0xffffffffu, tid >> 5, 0), lane = tid & 31;                                                     \
  const int rank = bid & 1, cl = bid >> 1, rb = bid & 7, hp = bid >> 3;                  \
  const int mb = 2 * rb + (hp >> 3), nb = hp & 7;                                            \
  const int wg = warp >> 2, wi = warp & 3, g = lane >> 2, q = lane & 3;                                                        \
  const int mi = lane >> 3, srow = wi * 16 + (mi & 1) * 8 + (lane & 7);      \
  auto bar = [&](int i) { return sbase + OFF_BAR + 8 * i; };                                                                   \
  volatile uint32_t* s_misc = (volatile uint32_t*)(smem + OFF_MISC);                                                           \
  auto load_w = [&](int s, int kt) {                           \
    tma_load3_mc(sbase + s * STG + SL_W + rank * SL_HD, &P.mapW, hp * 64, kt * 64 + rank * 32, 0, bar(B_FULL + s));            \
  };                                                                                                                           \
  auto load_a = [&](int s, int kt, int layer) { mbar_expect_tx(bar(B_FULL + s), STG); tma_load2(sbase + s * STG, &P.mapA[layer], kt * 64, rb * 256, bar(B_FULL + s)); }; \
  auto load_wo = [&](int k) {                                                 \
    mbar_expect_tx(bar(B_WFULL + (k & 3)), 32768);                                                                             \
    tma_load3_mc(sbase + (k & 3) * 32768 + 16384 + rank * 8192, &P.mapWo, nb * 128 + rank * 64, (k >> 3) * 32, (k & 7) * 2, bar(B_WFULL + (k & 3))); \
  };                                                                                                                           \
  auto load_o = [&](int k) {                                                            \
    bulk_load(sbase + (k & 3) * 32768, g_o + (size_t)(mb * 16 + k) * 16384, 16384, bar(B_WFULL + (k & 3)));                    \
  };                                                                                                                           \
  auto import_halo = [&](int layer, int h) {                                   \
    poll_flag(&g_kvflag[(rb - 1) >> 1][hp][h].v[layer], s_misc[M_TAG]);                                                        \
    fence_async_global();                                                                                                      \
    const uint8_t* src = g_kv + (size_t)(((rb - 1) >> 1) * 16 + hp) * 65536 + h * 32768;                                       \
    mbar_expect_tx(bar(B_HALO + 2 * h), 16384 << h);                                                                           \
    bulk_load_h(sbase + (h ? 65536 : 16384), src + (h ? 0 : 16384), 16384 << h, bar(B_HALO + 2 * h), policy_evict_first());    \
    if (h == 0) { mbar_expect_tx(bar(B_HALO + 1), 16384); bulk_load_h(sbase, src, 16384, bar(B_HALO + 1), policy_evict_first()); } \
  };                                                                                                                           \
  auto load_res = [&](int half, int layer) {                                                  \
    mbar_expect_tx(bar(B_RES), 16384);                                                                                         \
    tma_load2(sbase + AT_ST + half * 16384, &P.mapRes[layer], nb * 128, mb * 128 + half * 64, bar(B_RES));                     \
    tma_load2(sbase + AT_ST + half * 16384 + 8192, &P.mapRes[layer], nb * 128 + 64, mb * 128 + half * 64, bar(B_RES));         \
  };                                                                                                                           \
  auto store_tile = [&](int layer, int skip) {                                                     \
    _Pragma("unroll 1")                                                                                                        \
    for (int j = 0; j < 4; j++)                                                                                                \
      if ((j & 1) != skip) tma_store(&P.mapXst[layer], sbase + AT_ST + (j & 1) * 16384 + (j >> 1) * 8192, nb * 128 + (j >> 1) * 64, mb * 128 + (j & 1) * 64); \
    bulk_commit();                                                                                                             \
    bulk_wait_all();                                                                                                           \
  };                                                                                                                           \
  auto load_gu = [&](int half, int pace) {                             \
    mbar_expect_tx(bar(B_GU + half), 4 * FFN_PIECE);                                                                           \
    _Pragma("unroll 1")                                                                                                        \
    for (int j = 0; j < 4; j++) {                                                                                              \
      tma_load2_h(sbase + SL_F + j * FFN_PIECE, &P.mapG + (j >> 1), cl * 56, rank * 512 + half * 256 + (j & 1) * 128, bar(B_GU + half), FFN_POL); \
      if (j < 3) spin_cycles(pace);                                                                                            \
    }                                                                                                                          \
  };                                                                                                                           \
  auto fetch_gu = [&](uint32_t* a, int ks, int ct) {                 \
    ldsm_x4_t(sbase + SL_F + (mi & 1) * 2 * FFN_PIECE + (ks * 16 + (mi >> 1) * 8 + (lane & 7)) * 112 + ct * 16, a[0], a[1], a[2], a[3]); \
  };                                                                                                                           \
  auto send_gu = [&](float gate, float up, int ct, int part) {        \
    const int u = 8 * ct + g, own = u >= 28;                                                                                   \
    if (q == 0) st_async2(mapa(sbase + T_HP + ((rank * 5 + part) * 28 + u - 28 * own) * 8, own), gate, up, mapa(bar(B_HX), own)); \
  };                                                                                                                           \
  auto hidden = [&]() {                                     \
    const float2* hpart = (const float2*)(smem + T_HP) + min(lane, 27);                                                        \
    float gs[2] = {0.f, 0.f}, us[2] = {0.f, 0.f};                                                                              \
    _Pragma("unroll")                                                                                                          \
    for (int j = 0; j < 10; j++) { const float2 v = hpart[j * 28]; gs[j & 1] += v.x; us[j & 1] += v.y; }                       \
    const float gb = rbf(gs[0] + gs[1]), ub = rbf(us[0] + us[1]);                                                              \
    return lane < 28 ? rbf(__fdividef(gb, 1.f + __expf(-gb))) * ub : 0.f;                                                      \
  };                                                                                                                           \
  (void)load_wo; (void)load_o; (void)import_halo; (void)load_res; (void)store_tile; (void)fetch_gu; (void)load_gu; (void)send_gu; (void)hidden; (void)cl; (void)mb; (void)nb; (void)wg; (void)g; (void)q; (void)srow; (void)s_misc; (void)load_w; (void)load_a;

__global__ void __launch_bounds__(512, 1) mega_kernel(const __grid_constant__ Params P) {
  extern __shared__ __align__(1024) uint8_t smem[];
  if ((int)blockIdx.x < P.helper_first) {
    PHASE_IDS
    if (warp == 0) {
      if (lane == 0) {
        prefetch_tmap(&P.mapA[0]); prefetch_tmap(&P.mapW);
#pragma unroll
        for (int i = 0; i < 3; i++) mbar_init(bar(B_FULL + i), 1);
        asm volatile("fence.mbarrier_init.release.cluster;" ::: "memory");
      }
      __syncwarp();
      load_a(0, 0, 0);
    } else if (tid == 32) {
#pragma unroll
      for (int i = 3; i < B_COUNT; i++) mbar_init(bar(i), bar_count(i));
      asm volatile("fence.mbarrier_init.release.cluster;" ::: "memory");
    } else if (warp == 8) {
      ((uint4*)(smem + OFF_ONES))[lane] = make_uint4(0x3F803F80u, 0x3F803F80u, 0x3F803F80u, 0x3F803F80u);
      ((uint4*)(smem + OFF_ONES))[lane + 32] = make_uint4(0x3F803F80u, 0x3F803F80u, 0x3F803F80u, 0x3F803F80u);
    }
    __syncwarp();
    cluster_arrive(); cluster_wait();
    if (warp == 0) {
#pragma unroll 1
      for (int i = 0; i < 3; i++) { load_w(i, i); if (i) load_a(i, i, 0); }
      PROFL(0, 1);
    } else if (warp == 1) {
      if (lane < 16) g_rowab[0][rb * 256 + hp * 16 + lane] = make_uint4(0, 0, 0, 0);
    } else if (warp == 2) {
      const int f = lane >> 1;
      Flag* fl = f < 2 ? &g_kvflag[rb >> 1][hp][f] : f < 4 ? &g_oflag[rb][f & 1][hp] : &g_xflag[mb][nb];
      if (f < 5 && (f >= 2 || (rank == 1 && rb < 7))) ((uint4*)fl)[lane & 1] = make_uint4(0, 0, 0, 0);
    } else if (tid == 96) {
      if ((sbase & 0x3FFFF) != SOFF) __trap();
#pragma unroll 1
      for (int i = 1; i < 11; i++) prefetch_tmap(&P.mapA[0] + i);
    }
    __syncwarp();
  } else {
    const uint32_t sbase = smem_u32(smem);
    const int tid = threadIdx.x, warp = __shfl_sync(0xffffffffu, tid >> 5, 0), lane = tid & 31;
    const int hid = blockIdx.x - P.helper_first;
    constexpr int GR = HELP_GR, NG = 36 / GR, GB = GR * 6144, NGRP = 256 / GR;
    const uint32_t hfull = sbase + NG * GB, hempty = hfull + 8 * NG;
    if (tid == 0) {
      for (int i = 0; i < NG; i++) { mbar_init(hfull + 8 * i, 1); mbar_init(hempty + 8 * i, 12); }
      asm volatile("fence.mbarrier_init.release.cluster;" ::: "memory");
    }
    __syncthreads();
    const uint8_t* wsrc = (const uint8_t*)P.wqkv + (size_t)hid * 256 * 6144;
    if (warp == 12) {
#pragma unroll 1
      for (int gI = 0; gI < NGRP; gI++) {
        const int sl = gI % NG;
        if (gI >= NG) mbar_wait(hempty + 8 * sl, ((gI / NG) & 1) ^ 1);
        mbar_expect_tx(hfull + 8 * sl, GB);
        bulk_load(sbase + sl * GB, wsrc + (size_t)gI * GB, GB, hfull + 8 * sl);
      }
    } else if (warp < 12) {
      float cs8[8] = {0, 0, 0, 0, 0, 0, 0, 0};
#pragma unroll 1
      for (int gI = 0; gI < NGRP; gI++) {
        const int sl = gI % NG;
        mbar_wait(hfull + 8 * sl, (gI / NG) & 1);
#pragma unroll
        for (int i = 0; i < GR; i++) {
          const uint4 v = *(const uint4*)(smem + sl * GB + i * 6144 + tid * 16);
          cs8[0] += bf_lo(v.x); cs8[1] += bf_hi(v.x); cs8[2] += bf_lo(v.y); cs8[3] += bf_hi(v.y);
          cs8[4] += bf_lo(v.z); cs8[5] += bf_hi(v.z); cs8[6] += bf_lo(v.w); cs8[7] += bf_hi(v.w);
        }
        __syncwarp();
        if (lane == 0) mbar_arrive(hempty + 8 * sl);
      }
      uint4* dst = (uint4*)&g_cspart[hid][tid * 8];
      st_relaxed4(dst, make_uint4(enc(cs8[0]), enc(cs8[1]), enc(cs8[2]), enc(cs8[3])));
      st_relaxed4(dst + 1, make_uint4(enc(cs8[4]), enc(cs8[5]), enc(cs8[6]), enc(cs8[7])));
    }
    return;
  }

  regs_dec<120>();
#pragma unroll 1
  for (unsigned pass_v = 0;;) {
    const unsigned pass = __shfl_sync(0xffffffffu, pass_v, 0);
    if (__shfl_sync(0xffffffffu, fresh_tid() >> 8, 0)) {
      if (pass > 0) {
        const unsigned layer = pass - 1;
        uint32_t xr[32];
        {
          PHASE_IDS
          float acc[64];
#pragma unroll
          for (int i = 0; i < 64; i++) acc[i] = 0.f;
          const uint32_t da0 = dlo(SOFF, 16) + (wg - 2) * 256;
          constexpr uint32_t db0 = dlo(SOFF + 16384, 8192);
#pragma unroll 1
          for (int k4 = 0; k4 < 4; k4++) {
#pragma unroll
            for (int st = 0; st < 4; st++) {
              mbar_wait(bar(B_WFULL + st), k4 & 1);
              wg_fence();
#pragma unroll
              for (int kk = 0; kk < 4; kk++)
                wg_ss128t<H64, H128>(acc, da0 + ((st * 32768) >> 4) + (kk >> 1) * 512 + (kk & 1) * 2, db0 + ((st * 32768) >> 4) + kk * 128, 1);
              wg_commit();
              if (st == 0 && k4 == 0 && warp == 9) PROF(10);
              if (warp == 9) STEPT(16 + k4 * 4 + st);
              if (REL_NOW) {
                if (st < 3 || k4 < 3) wg_wait<0>();
                if (lane < 2 && (st < 2 || k4 < 3)) mbar_arrive_cluster(bar(B_WEMPTY + st), lane);
              } else {
                wg_wait<1>();
                if (lane < 2 && (st == 0 ? k4 > 0 : (st < 3 || k4 < 3))) mbar_arrive_cluster(bar(B_WEMPTY + ((st + 3) & 3)), lane);
              }
            }
          }
          mbar_wait(bar(B_RES), layer);
          mbar_wait(bar(B_RST), layer);
          const uint32_t zoff = AT_ST + (wg - 2) * 16384;
#pragma unroll
          for (int j = 0; j < 8; j++)
            ldsm_x4(sbase + zoff + srow * 128 + (j >> 2) * 8192 + ((((2 * j + (mi >> 1)) & 7) ^ (srow & 7)) << 4), xr[4 * j], xr[4 * j + 1], xr[4 * j + 2], xr[4 * j + 3]);
          wg_wait<0>();
          fence_regs<64>(acc);
          if (warp == 9) PROF(11);
          if (layer == 0 && lane < 2) mbar_arrive_cluster(bar(B_QFREE), lane);
#pragma unroll
          for (int j = 0; j < 32; j++) xr[j] = hadd_bf2(xr[j], pack_bf16(acc[2 * j], acc[2 * j + 1]));
        }
        PHASE_IDS
        const uint32_t tag = s_misc[M_TAG];
        const int grow = mb * 128 + (warp - 8) * 16 + g;
        {
          float d[6][4];
#pragma unroll
          for (int i = 0; i < 6; i++) d[i][0] = d[i][1] = d[i][2] = d[i][3] = 0.f;
          const uint4* tab = (const uint4*)(smem + OFF_PATCH + (g == 1 ? q * 64 : (g == 0 ? 256 : 320)));
#pragma unroll
          for (int j2 = 0; j2 < 4; j2++) {
            const uint4 w = tab[j2];
#pragma unroll
            for (int jj = 0; jj < 2; jj++) {
              const uint32_t* a = &xr[8 * j2 + 4 * jj];
              mma_16816(d[jj], a[0], a[1], a[2], a[3], jj ? w.z : w.x, jj ? w.w : w.y);
              mma_16816(d[2 + jj], a[0], a[1], a[2], a[3], a[0], a[2]);
              mma_16816(d[4 + jj], a[0], a[1], a[2], a[3], a[1], a[3]);
            }
          }
          const float sq0 = __shfl_sync(0xffffffffu, (g & 1) ? d[2][1] + d[3][1] : d[2][0] + d[3][0], g * 4 + (g >> 1));
          const float sq1 = __shfl_sync(0xffffffffu, (g & 1) ? d[4][3] + d[5][3] : d[4][2] + d[5][2], g * 4 + (g >> 1));
          uint4* dst = &g_part[layer][nb * SEQ + grow];
          if (q == 0) {
            st_relaxed4(dst, make_uint4(__float_as_uint(d[0][0] + d[1][0]), __float_as_uint(sq0), __float_as_uint(d[0][1] + d[1][1]), tag));
            st_relaxed4(dst + 8, make_uint4(__float_as_uint(d[0][2] + d[1][2]), __float_as_uint(sq1), __float_as_uint(d[0][3] + d[1][3]), tag));
          }
        }
        if (warp == 9) PROF(12);
        asm volatile("bar.arrive 6, 320;" ::: "memory");
        const int t_p = (int)clock();
        const uint32_t zrow = sbase + AT_ST + (wg - 2) * 16384 + srow * 128;
        if (layer == 0) {
#pragma unroll
          for (int j = 0; j < 8; j++)
            stsm_x4(zrow + (j >> 2) * 8192 + ((((2 * j + (mi >> 1)) & 7) ^ (srow & 7)) << 4), xr[4 * j], xr[4 * j + 1], xr[4 * j + 2], xr[4 * j + 3]);
          fence_async_smem();
          asm volatile("bar.arrive 8, 288;" ::: "memory");
        }
#pragma unroll 1
        while ((int)clock() - t_p < DELAY_P) {}
        {
          const uint4* src = &g_part[layer][2 * q * SEQ + grow];
          uint4 pp[4];
          uint32_t spins = 0;
#pragma unroll 1
          do {
            pp[0] = ld_relaxed4(src); pp[1] = ld_relaxed4(src + SEQ); pp[2] = ld_relaxed4(src + 8); pp[3] = ld_relaxed4(src + SEQ + 8);
          } while (!__all_sync(0xffffffffu, pp[0].w == tag && pp[1].w == tag && pp[2].w == tag && pp[3].w == tag) && ++spins < SPIN_LIMIT);
          if (warp == 9) PROF(13);
          const int rr = q >> 1;
          float s3[3];
#pragma unroll
          for (int c = 0; c < 3; c++) {
            const float lo = __uint_as_float(c == 0 ? pp[0].x : c == 1 ? pp[0].y : pp[0].z) + __uint_as_float(c == 0 ? pp[1].x : c == 1 ? pp[1].y : pp[1].z);
            const float hi = __uint_as_float(c == 0 ? pp[2].x : c == 1 ? pp[2].y : pp[2].z) + __uint_as_float(c == 0 ? pp[3].x : c == 1 ? pp[3].y : pp[3].z);
            s3[c] = (rr ? hi : lo) + __shfl_xor_sync(0xffffffffu, rr ? lo : hi, 2);
            s3[c] += __shfl_xor_sync(0xffffffffu, s3[c], 1);
          }
          const float mu = s3[0] * (1.f / DM), var = fmaxf(fmaf(-mu, mu, s3[1] * (1.f / DM)), 0.f);
          const float mn = rbf(mu), iv = ln_inv(var);
          const uint32_t ky = router_key(rbf((s3[2] - mn * __uint_as_float(s_misc[M_WSUM])) * iv), grow + 8 * rr);
          const uint32_t wbest = __reduce_max_sync(0xffffffffu, ky);
          s_misc[M_KEYS + warp - 8] = wbest;
          named_bar(5, 256);
          if (__reduce_max_sync(0xffffffffu, s_misc[M_KEYS + (lane & 7)]) == wbest) {
            if (nb == 0 && ky == wbest && (q & 1) == 0) st_relaxed4(&g_slot[layer][mb * 8], make_uint4(ky, __float_as_uint(mn), __float_as_uint(iv), tag));
            const int r = ~wbest & 15;
            if ((r & 7) == g) {
#pragma unroll
              for (int j = 0; j < 4; j++) {
                const uint32_t* a = &xr[8 * j];
                st_relaxed4(&g_cand[layer][mb * 128 + nb * 16 + q * 4 + j],
                            r < 8 ? make_uint4(nosent(a[0]), nosent(a[2]), nosent(a[4]), nosent(a[6])) : make_uint4(nosent(a[1]), nosent(a[3]), nosent(a[5]), nosent(a[7])));
              }
            }
            __syncwarp();
          }
          if (warp == 9) PROF(14);
          if (layer == 0) {
            if ((q & 1) == 0) {
              g_rowln[nb][grow + 8 * rr] = make_float2(mn, iv);
              if (warp - 8 == nb) {
                const float mu2 = mu + (mu - mn) * iv, inv2 = ln_inv(var * (1.f + iv) * (1.f + iv));
                st_relaxed4(&g_rowab[1][grow + 8 * rr], make_uint4(__float_as_uint((1.f + iv) * inv2), __float_as_uint((mn * iv + rbf(mu2)) * inv2), tag, 0));
              }
            }
            __syncwarp();
          } else {
            const float mo = __shfl_xor_sync(0xffffffffu, mn, 2), io = __shfl_xor_sync(0xffffffffu, iv, 2);
            const uint32_t m0 = pack_bf16(rr ? mo : mn, rr ? mo : mn), m1 = pack_bf16(rr ? mn : mo, rr ? mn : mo);
            const float i0 = rr ? io : iv, i1 = rr ? iv : io;
#pragma unroll
            for (int j = 0; j < 8; j++)
              stsm_x4(zrow + (j >> 2) * 8192 + ((((2 * j + (mi >> 1)) & 7) ^ (srow & 7)) << 4), add_ln_pair(xr[4 * j], m0, i0),
                      add_ln_pair(xr[4 * j + 1], m1, i1), add_ln_pair(xr[4 * j + 2], m0, i0), add_ln_pair(xr[4 * j + 3], m1, i1));
            fence_async_smem();
          }
          if (warp == 15) asm volatile("bar.arrive 7, 512;" ::: "memory");
        }
        if (warp < 15) {
          uint32_t gu[64];
          mbar_wait(bar(B_GU + 1), layer);
#pragma unroll
          for (int j = 0; j < 16; j++) fetch_gu(gu + 4 * j, j, warp - 8);
          fence_async_smem();
          float d[4][4] = {};
          named_bar(7, 512);
#pragma unroll
          for (int hf = 0; hf < 2; hf++) {
            uint4 xv[4] = {};
            if (g == 0) {
#pragma unroll
              for (int j = 0; j < 4; j++) xv[j] = ((const uint4*)(smem + T_XS))[32 + hf * 16 + j * 4 + q];
            }
            __syncwarp();
#pragma unroll
            for (int j = 0; j < 4; j++) {
              const uint32_t* a = gu + hf * 32 + j * 8;
              mma_16816(d[(j & 1) * 2], a[0], a[1], a[2], a[3], xv[j].x, xv[j].y);
              mma_16816(d[(j & 1) * 2 + 1], a[4], a[5], a[6], a[7], xv[j].z, xv[j].w);
            }
          }
          send_gu((d[0][0] + d[1][0]) + (d[2][0] + d[3][0]), (d[0][2] + d[1][2]) + (d[2][2] + d[3][2]), warp - 8, 4);
          __syncwarp();
        }
        if (layer == 0) asm volatile("bar.arrive 9, 512;" ::: "memory");
        else {
        uint32_t wd[64];
        mbar_wait(bar(B_DN), layer);
#pragma unroll
        for (int j = 0; j < 16; j++) {
          const uint32_t row = sbase + ((warp - 8) * 2 + (j >> 3)) * 3584 + min((j & 1) * 16 + (mi >> 1) * 8 + (lane & 7), 27) * 128;
          ldsm_x4_t(row + ((((j & 6) + (mi & 1)) ^ ((row >> 7) & 7)) << 4), wd[4 * j], wd[4 * j + 1], wd[4 * j + 2], wd[4 * j + 3]);
        }
        fence_regs_u<64>(wd);
        mbar_wait_cluster(bar(B_HX), layer);
        uint32_t hf[4];
        {
          const float hv = hidden();
          const uint32_t hp2 = pack_bf16(hv, __shfl_down_sync(0xffffffffu, hv, 1));
#pragma unroll
          for (int j = 0; j < 4; j++) hf[j] = __shfl_sync(0xffffffffu, hp2, 8 * j + 2 * q);
        }
        if (warp == 9) PROF(19);
        float y[4][4] = {};
#pragma unroll
        for (int j = 0; j < 16; j++)
          mma_16816(y[j & 3], wd[4 * j], wd[4 * j + 1], wd[4 * j + 2], wd[4 * j + 3], g == j >> 1 ? hf[(j & 1) * 2] : 0u, g == j >> 1 ? hf[(j & 1) * 2 + 1] : 0u);
        {
          float e[4];
#pragma unroll
          for (int c = 0; c < 4; c++) { const int i = (c & 1) * 2 + (c >> 1); e[c] = (y[0][i] + y[1][i]) + (y[2][i] + y[3][i]); }
          const bool b0 = g & 1, b1 = g & 2;
          float t0 = __shfl_xor_sync(0xffffffffu, b0 ? e[0] : e[1], 4), t1 = __shfl_xor_sync(0xffffffffu, b0 ? e[2] : e[3], 4);
          const float f0 = b0 ? t0 : e[0], f1 = b0 ? e[1] : t0, f2 = b0 ? t1 : e[2], f3 = b0 ? e[3] : t1;
          t0 = __shfl_xor_sync(0xffffffffu, b1 ? f0 : f2, 8); t1 = __shfl_xor_sync(0xffffffffu, b1 ? f1 : f3, 8);
          st_relaxed4(&g_ypart[layer][bid * 256 + (warp - 8) * 32 + (q * 4 + (g & 3)) * 2 + (g >> 2)],
                      b1 ? make_uint4(f2u(t0), f2u(t1), f2u(f2), f2u(f3)) : make_uint4(f2u(f0), f2u(f1), f2u(t0), f2u(t1)));
        }
        if (warp == 9) PROF(20);
        asm volatile("bar.arrive 9, 384;" ::: "memory");
        cluster_arrive(); cluster_wait();
        return;
        }
      }
      const unsigned layer = pass;
      named_bar(1 + (fresh_tid() >> 7), 128);
      regs_inc<224>();
      float acc[2][96];
      {
        PHASE_IDS
        const uint32_t da0 = dlo(SOFF, 16) + (wg - 2) * 512;
        constexpr uint32_t db0 = dlo(SOFF + SL_W, 4096);
#pragma unroll
        for (int i = 0; i < 96; i++) acc[0][i] = acc[1][i] = 0.f;
        int s = 0, u = 0;
#pragma unroll 1
        for (int i = 0; i < 16; i++) {
          const uint32_t da = da0 + s * (STG >> 4), db = db0 + s * (STG >> 4);
          mbar_wait(bar(B_FULL + s), (u + (s ? layer : 0)) & 1);
          if (warp == 9) STEPT(i);
          if (warp == 9 && i == 0) PROF(29);
          wg_fence();
#pragma unroll
          for (int kk = 0; kk < 4; kk++) {
            wg_ss192t(acc[0], da + kk * 2, db + (kk >> 1) * (SL_HD >> 4) + (kk & 1) * 128, 1);
            wg_ss192t(acc[1], da + 1024 + kk * 2, db + (kk >> 1) * (SL_HD >> 4) + (kk & 1) * 128, 1);
          }
          wg_commit();
          wg_wait<1>();
          if (lane < 2 && i > 0 && i < 14) mbar_arrive_cluster(bar(B_EMPTY + (s == 0 ? 2 : s - 1)), lane);
          if (++s == 3) { s = 0; u++; }
        }
      }
      PHASE_IDS
      mbar_wait(bar(B_CS), layer);
      float pa[2][2], pb[2][2];
      {
        const uint32_t tag = s_misc[M_TAG];
        const uint4* src = &g_rowab[layer][rb * 256 + (wg - 2 + (lane >> 4) * 2) * 64 + wi * 16 + (lane & 15)];
        uint4 v;
        uint32_t spins = 0;
#pragma unroll 1
        do { v = ld_relaxed4(src); } while (!__all_sync(0xffffffffu, v.z == tag) && ++spins < SPIN_LIMIT);
#pragma unroll
        for (int j = 0; j < 4; j++) {
          pa[j >> 1][j & 1] = __uint_as_float(__shfl_sync(0xffffffffu, v.x, g + 8 * j));
          pb[j >> 1][j & 1] = __uint_as_float(__shfl_sync(0xffffffffu, v.y, g + 8 * j));
        }
      }
      const int prow = (int)s_misc[M_SEL0] - rb * 256;
      const bool patch = ((prow - (wg - 2) * 64 - wi * 16) & ~0x8F) == 0;
      const float* cs = (const float*)(smem + OFF_CS);
      auto finish = [&](int m, int b, float2 c, uint32_t* dst) {
        dst[0] = pack_bf16(acc[m][4 * b] * pa[m][0] - c.x * pb[m][0], acc[m][4 * b + 1] * pa[m][0] - c.y * pb[m][0]);
        dst[1] = pack_bf16(acc[m][4 * b + 2] * pa[m][1] - c.x * pb[m][1], acc[m][4 * b + 3] * pa[m][1] - c.y * pb[m][1]);
      };
      wg_wait<0>();
      fence_regs<96>(acc[0]); fence_regs<96>(acc[1]);
      if (warp != 9) STEPT(1);
      if (lane < 2) mbar_arrive_cluster(bar(B_QDONE), lane);
      if (warp == 9) PROF(2);
#pragma unroll
      for (int h = 0; h < 2; h++) {
        const uint32_t dst = sbase + (h * 8 + 2 + wg) * 8192 + srow * 64;
#pragma unroll
        for (int jj = 0; jj < 4; jj++) {
          const int b = 8 + (jj >> 1) * 8 + h * 4 + (jj & 1) * 2;
          const float2 c0 = *(const float2*)&cs[8 * b + 2 * q], c1 = *(const float2*)&cs[8 * b + 8 + 2 * q];
          uint32_t r[2][4];
#pragma unroll
          for (int m = 0; m < 2; m++) { finish(m, b, c0, r[m]); finish(m, b + 1, c1, r[m] + 2); }
          if (h == 0 && jj == 0) named_bar(5, 256);
#pragma unroll
          for (int m = 0; m < 2; m++)
            stsm_x4(dst + m * 16384 + (jj >> 1) * 4096 + ((((jj & 1) * 2 + (mi >> 1)) ^ ((srow >> 1) & 3)) << 4), r[m][0], r[m][1], r[m][2], r[m][3]);
        }
        if (patch) {
          __syncwarp();
          if (lane < 8)
            *(uint4*)(smem + (h * 8 + 4 + (prow >> 6)) * 8192 + g * 4096 + (prow & 63) * 64 + ((q ^ ((prow >> 1) & 3)) << 4)) =
                *(const uint4*)(smem + OFF_PATCH + 128 + g * 128 + h * 64 + q * 16);
        }
        fence_async_smem();
        __syncwarp();
        mbar_arrive_e(bar(B_KVREADY + h));
        if (warp != 9) STEPT(2 + h);
      }
#pragma unroll
      for (int j = 0; j < 4; j++) { pa[j >> 1][j & 1] *= SM_C; pb[j >> 1][j & 1] *= SM_C; }
#pragma unroll
      for (int jj = 0; jj < 4; jj++) {
        const float2 c0 = *(const float2*)&cs[16 * jj + 2 * q], c1 = *(const float2*)&cs[16 * jj + 8 + 2 * q];
#pragma unroll
        for (int m = 0; m < 2; m++) {
          uint32_t r[4];
          finish(m, 2 * jj, c0, r); finish(m, 2 * jj + 1, c1, r + 2);
          *(uint4*)(smem + AT_ST + ((jj >> 1) * 16 + warp - 8 + 8 * m) * 1024 + (jj & 1) * 512 + lane * 16) = make_uint4(r[0], r[1], r[2], r[3]);
        }
      }
      __syncwarp();
      if (patch) {
        *(uint32_t*)(smem + AT_ST + ((lane >> 4) * 16 + (prow >> 4)) * 1024 + (mi & 1) * 512 + ((prow & 7) * 4 + q) * 16 + ((g & 1) * 2 + ((prow >> 3) & 1)) * 4) =
            *(const uint32_t*)(smem + OFF_PATCH + lane * 4);
        __syncwarp();
      }
      if (warp == 9) PROF(3);
      mbar_arrive_e(bar(B_QREADY));
      regs_dec<120>();
    } else {
      if (pass > 0 && __shfl_sync(0xffffffffu, fresh_tid() >> 7, 0)) {
        const unsigned layer = pass - 1;
        PHASE_IDS
        const uint32_t tag = s_misc[M_TAG];
        if (warp == 7) {
              uint32_t* tab = (uint32_t*)(smem + OFF_PATCH);
#pragma unroll
              for (int j = 0; j < 2; j++) { const int w = lane + 32 * j; tab[(w & 3) * 16 + (w >> 2)] = ((const uint32_t*)P.w_r)[nb * 64 + w]; }
              tab[64 + lane] = lane < 16 ? 0x3F803F80u : 0u;
              float tot = 0.f;
#pragma unroll
              for (int j = 0; j < 4; j++) {
                const uint4 u = ((const uint4*)P.w_r)[lane + 32 * j];
                tot += bf_lo(u.x) + bf_hi(u.x) + bf_lo(u.y) + bf_hi(u.y) + bf_lo(u.z) + bf_hi(u.z) + bf_lo(u.w) + bf_hi(u.w);
              }
              s_misc[M_WSUM] = __float_as_uint(warp_sum(tot));
        }
              if (layer == 1) {
                const float2 ln = g_rowln[nb][mb * 128 + tid - 128];
                const uint32_t m2 = pack_bf16(ln.x, ln.x);
                uint8_t* row = smem + AT_ST + (wi >> 1) * 16384 + (tid & 63) * 128;
                mbar_wait(bar(B_RES), 1);
#pragma unroll 1
                for (int j = 0; j < 8; j++) {
                  uint4* c = (uint4*)(row + (((j + lane) & 7) << 4));
                  const uint4 v = c[0], w = c[512];
                  c[0] = make_uint4(add_ln_pair(v.x, m2, ln.y), add_ln_pair(v.y, m2, ln.y), add_ln_pair(v.z, m2, ln.y), add_ln_pair(v.w, m2, ln.y));
                  c[512] = make_uint4(add_ln_pair(w.x, m2, ln.y), add_ln_pair(w.y, m2, ln.y), add_ln_pair(w.z, m2, ln.y), add_ln_pair(w.w, m2, ln.y));
                }
                const int prow = (int)s_misc[M_SEL0] - mb * 128;
                __syncwarp();
                if (prow >> 5 == wi && lane < 16)
                  *(uint4*)(smem + AT_ST + (prow >> 6) * 16384 + (lane >> 3) * 8192 + (prow & 63) * 128 + (((lane ^ prow) & 7) << 4)) = poll4(&g_x2row[(nb * 16 + lane) * 2]);
                PROF(30);
              }
              __syncwarp();
              mbar_arrive_e(bar(B_RST));
        if (warp == 4) {
            named_bar(6, 320);
            spin_cycles(DELAY_S);
            uint4 c, u0, u1;
            uint32_t u2, best = 0, spins = 0;
            int src;
#pragma unroll 1
            for (;;) {
              src = (~best & 0x7FFu) >> 7;
              const uint4* xsel = &g_cand[layer][src * 128];
              c = ld_relaxed4(&g_slot[layer][(lane & 15) * 8]);
              u0 = ld_relaxed4(xsel + rank * 64 + lane); u1 = ld_relaxed4(xsel + rank * 64 + 32 + lane);
              u2 = ld_relaxed((const uint32_t*)(xsel + (bid >> 4) * 16 + q * 4) + (bid & 15));
              const uint32_t prev = best;
              best = __reduce_max_sync(0xffffffffu, c.w == tag ? c.x : 0u);
              if ((__all_sync(0xffffffffu, c.w == tag && valid4(u0) && valid4(u1) && u2 != SENT) && best == prev) || ++spins > SPIN_LIMIT) break;
            }
            const float sel_m = __uint_as_float(__shfl_sync(0xffffffffu, c.y, src)), sel_inv = __uint_as_float(__shfl_sync(0xffffffffu, c.z, src));
            const uint32_t m2 = pack_bf16(sel_m, sel_m);
            uint4* xs = (uint4*)(smem + T_XS) + (lane & 16) + q * 4 + (g & 3);
            xs[0] = make_uint4(ln_pair(u0.x, m2, sel_inv), ln_pair(u0.y, m2, sel_inv), ln_pair(u0.z, m2, sel_inv), ln_pair(u0.w, m2, sel_inv));
            xs[32] = make_uint4(ln_pair(u1.x, m2, sel_inv), ln_pair(u1.y, m2, sel_inv), ln_pair(u1.z, m2, sel_inv), ln_pair(u1.w, m2, sel_inv));
            s_misc[M_KEY] = best; s_misc[M_MEAN] = __float_as_uint(sel_m); s_misc[M_INV] = __float_as_uint(sel_inv);
            s_misc[M_XQ + q] = u2;
            PROF(16);
        }
        asm volatile("bar.arrive 7, 512;" ::: "memory");
        if (warp == 5 && layer == 0) {
              named_bar(8, 288);
              if (nb > 0) spin_cycles(X_STAGGER);
              store_tile(0, -1);
              set_flag(&g_xflag[mb][nb].v[0], tag);
              PROF(17);
              poll_flag(&g_xflag[2 * rb + (lane & 1)][0].v[0], tag);
              fence_async_global();
              load_a(0, 0, 1);
              load_a(1, 1, 1);
              PROFL(1, 1);
        }
      }
      named_bar(1 + (fresh_tid() >> 7), 128);
      regs_dec<32>();
      if (pass > 0) {
        const unsigned layer = pass - 1;
        PHASE_IDS
        const uint32_t tag = s_misc[M_TAG], bkey = s_misc[M_KEY];
        const int sel = SEQ - 1 - (int)(bkey & 0x7FFFu);
        if (warp == 3) {
          if (layer == 1) {
            if (lane < 24) ((uint4*)g_cspart)[bid * 24 + lane] = make_uint4(0, 0, 0, 0);
          } else s_misc[M_SEL0] = sel;
          if (bid == 0 && lane == 0) g_sel[layer] = sel;
        }
        __syncwarp();
        if (layer == 0) {
          auto load_down = [&](int j) {
            mbar_expect_tx(bar(B_DN + j), 2 * FFN_PIECE);
            bulk_load_h(sbase + SL_F + j * 2 * FFN_PIECE, P.w_d + (size_t)(bid * 28 + j * 14) * DM, 2 * FFN_PIECE, bar(B_DN + j), FFN_POL);
          };
          if (warp == 0) {
            load_down(0);
            poll_flag(&g_xflag[2 * rb + (lane & 1)][(lane >> 1) & 7].v[0], tag);
          }
          float hv = 0.f;
          if (wg == 1) { mbar_wait_cluster(bar(B_HX), 0); hv = rbf(hidden()); fence_regs<1>(&hv); }
          named_bar(9, 512);
          if (warp == 0) {
            fence_async_global();
            fence_async_smem();
            if (lane < 16) mbar_arrive_cluster(bar(B_QFREE), lane & 1);
            mbar_wait(bar(B_QFREE), 1);
            load_w(2, 2); load_a(2, 2, 1);
          } else if (wg == 1) {
            if (warp == 4) { mbar_wait(bar(B_DN), 0); load_down(1); }
            float d[8] = {0.f, 0.f, 0.f, 0.f, 0.f, 0.f, 0.f, 0.f};
#pragma unroll 1
            for (int j = 0; j < 28; j += 2) {
              if (j == 0 || j == 14) mbar_wait(bar(B_DN + (j > 0)), 0);
              const uint4 w0 = *(const uint4*)(smem + SL_F + j * 2048 + (tid - 128) * 16), w1 = *(const uint4*)(smem + SL_F + j * 2048 + 2048 + (tid - 128) * 16);
              fma8(d, w0, __shfl_sync(0xffffffffu, hv, j));
              fma8(d, w1, __shfl_sync(0xffffffffu, hv, j + 1));
            }
            uint4* dst = &g_ypart[0][bid * 256 + (tid - 128) * 2];
            st_relaxed4(dst, make_uint4(f2u(d[0]), f2u(d[1]), f2u(d[2]), f2u(d[3])));
            st_relaxed4(dst + 1, make_uint4(f2u(d[4]), f2u(d[5]), f2u(d[6]), f2u(d[7])));
            named_bar(2, 128);
            PROF(20);
            if (warp == 5) {
              fence_async_smem();
              mbar_expect_tx(bar(B_WS), 4 * SL_HD);
#pragma unroll 1
              for (int j = 0; j < 4; j++) tma_load3(sbase + SL_F + j * SL_HD, &P.mapW, hp * 64, rb * 128 + j * 32, 0, bar(B_WS));
            }
          }
        } else {
          const int skip = sel >> 7 == mb ? (sel >> 6) & 1 : -1;
          if (warp == 0) {
            store_tile(1, skip);
            PROF(17);
          } else if (wg == 0) {
#pragma unroll 1
            for (int c = tid - 32; c < 1024 && skip >= 0; c += 96) {
              const int r = c >> 4;
              if (r != (sel & 63))
                *(uint4*)(P.out + (size_t)(mb * 128 + skip * 64 + r) * DM + nb * 128 + (c & 15) * 8) =
                    *(const uint4*)(smem + AT_ST + skip * 16384 + ((c >> 3) & 1) * 8192 + r * 128 + (((c ^ r) & 7) << 4));
            }
          } else named_bar(9, 384);
        }
        if (wg == 1) {
          const int t_y = (int)clock();
          const uint32_t xw = s_misc[M_XQ + ((lane & 7) >> 1)];
          const float x = (lane & 1) ? bf_hi(xw) : bf_lo(xw);
          float xn = rbf(rbf(x - __uint_as_float(s_misc[M_MEAN])) * __uint_as_float(s_misc[M_INV]));
          uint32_t u = bkey & 0xFFFF0000u;
          u = (u & 0x80000000u) ? (u & 0x7FFFFFFFu) : (~u & 0xFFFF0000u);
          float sg = rbf(__fdividef(1.f, 1.f + __expf(-__uint_as_float(u))));
          uint32_t* dst = (layer == 0 ? (uint32_t*)&g_x2row[bid * 2] : (uint32_t*)(P.out + (size_t)sel * DM + bid * 8)) + (lane >> 1);
          asm volatile("" : "+f"(xn), "+f"(sg), "+l"(dst));
#pragma unroll 1
          while ((int)clock() - t_y < DELAY_Y) {}
          const uint4* src = &g_ypart[layer][((tid - 128) >> 1) * 256 + bid * 2 + (tid & 1)];
          uint4 v, w;
          uint32_t spins = 0;
#pragma unroll 1
          do { v = ld_relaxed4(src); w = ld_relaxed4(src + 64 * 256); } while (!__all_sync(0xffffffffu, valid4(v) && valid4(w)) && ++spins < SPIN_LIMIT);
          float a[4] = {__uint_as_float(v.x) + __uint_as_float(w.x), __uint_as_float(v.y) + __uint_as_float(w.y),
                        __uint_as_float(v.z) + __uint_as_float(w.z), __uint_as_float(v.w) + __uint_as_float(w.w)};
          const bool b1 = lane & 2, b2 = lane & 4;
          float c0 = (b1 ? a[1] : a[0]) + __shfl_xor_sync(0xffffffffu, b1 ? a[0] : a[1], 2);
          float c1 = (b1 ? a[3] : a[2]) + __shfl_xor_sync(0xffffffffu, b1 ? a[2] : a[3], 2);
          float y = (b2 ? c1 : c0) + __shfl_xor_sync(0xffffffffu, b2 ? c0 : c1, 4);
          y += __shfl_xor_sync(0xffffffffu, y, 8);
          y += __shfl_xor_sync(0xffffffffu, y, 16);
          float* red = (float*)(smem + OFF_PATCH);
          red[wi * 8 + (lane & 1) * 4 + ((lane >> 1) & 3)] = y;
          named_bar(2, 128);
          if (warp == 4) {
            PROF(21);
            y = (red[lane & 7] + red[8 + (lane & 7)]) + (red[16 + (lane & 7)] + red[24 + (lane & 7)]);
            const float res = x + rbf(xn + rbf(rbf(y) * sg));
            const uint32_t pr = nosent(pack_bf16(res, __shfl_down_sync(0xffffffffu, res, 1)));
            if (lane < 8 && (lane & 1) == 0) st_relaxed(dst, pr);
            PROF(22);
          }
        }
        if (pass == 2) {
          if (bid == 0 && tid == 128) g_epoch = tag;
          __syncwarp();
          cluster_arrive(); cluster_wait();
          return;
        }
      }
      const unsigned layer = pass;
      if (layer == 1 && __shfl_sync(0xffffffffu, fresh_tid() >> 5, 0) > 0) {
        PHASE_IDS
        uint4* xrow = (uint4*)(smem + SL_F + 4 * SL_HD);
        if (wg == 1) { xrow[tid - 128] = poll4(&g_x2row[(tid - 128) * 2]); PROF(23); }
        named_bar(12, 224);
        if (warp == 7) {
          float mean = 0.f;
#pragma unroll 1
          for (int pass2 = 0; pass2 < 2; pass2++) {
            float acc = 0.f;
#pragma unroll 1
            for (int j = lane; j < 512; j += 32) {
              const uint32_t w = ((const uint32_t*)xrow)[j];
              const float d0 = bf_lo(w) - mean, d1 = bf_hi(w) - mean;
              acc += pass2 ? d0 * d0 + d1 * d1 : d0 + d1;
            }
            acc = warp_sum(acc) * (1.f / DM);
            if (pass2 == 0) mean = acc;
            else { s_misc[M_PMEAN] = __float_as_uint(rbf(mean)); s_misc[M_PINV] = __float_as_uint(ln_inv(acc)); }
          }
        } else {
          mbar_wait(bar(B_WS), 0);
          const uint8_t* wa = smem + SL_F + (g >> 1) * SL_HD + ((warp - 1) >> 1) * 4096 + (g & 1) * 2048;
          const uint32_t* xs = (const uint32_t*)xrow + rb * 64 + g * 8;
          const int ch = ((warp - 1) & 1) * 4 + q;
          float d[8] = {0.f, 0.f, 0.f, 0.f, 0.f, 0.f, 0.f, 0.f};
#pragma unroll 1
          for (int j0 = 0; j0 < 16; j0 += 2) {
            const int j = j0 ^ ((g & 1) * 4);
            const uint4 w0 = *(const uint4*)(wa + j * 128 + (((ch ^ j) & 7) << 4)), w1 = *(const uint4*)(wa + j * 128 + 128 + (((ch ^ (j + 1)) & 7) << 4));
            const uint32_t xx = xs[j >> 1];
            fma8(d, w0, bf_lo(xx)); fma8(d, w1, bf_hi(xx));
          }
#pragma unroll
          for (int c = 0; c < 4; c++) d[c] = ((g & 4) ? d[c + 4] : d[c]) + __shfl_xor_sync(0xffffffffu, (g & 4) ? d[c] : d[c + 4], 16);
#pragma unroll
          for (int c = 0; c < 2; c++) d[c] = ((g & 2) ? d[c + 2] : d[c]) + __shfl_xor_sync(0xffffffffu, (g & 2) ? d[c] : d[c + 2], 8);
          d[0] = ((g & 1) ? d[1] : d[0]) + __shfl_xor_sync(0xffffffffu, (g & 1) ? d[0] : d[1], 4);
          st_relaxed(&g_patch[rb][((warp - 1) >> 1) * DM + hp * 64 + ch * 8 + g], f2u(d[0]));
        }
        named_bar(12, 224);
        PROF(24);
      }
      PHASE_IDS
      if (wg == 0) {
        if (warp == 0) {
          int s = 0, u = 0;
#pragma unroll 1
          for (int i = 3; i < 16; i++) {
            if (layer == 1) mbar_arrive_e(bar(B_EMPTY + s));
            mbar_wait(bar(B_EMPTY + s), (u + (s ? 0 : layer)) & 1);
            load_w(s, i);
            load_a(s, i, layer);
            if (++s == 3) { s = 0; u++; }
          }
        } else if (warp == 1) {
          if (layer == 0) {
            const uint32_t tag = ld_relaxed(&g_epoch) + 1;
            float shift = 0.f, sum = 0.f, sq = 0.f;
            const int r = hp * 16 + (lane >> 1);
#pragma unroll 1
            for (int i = 0; i < 16; i++) {
              mbar_wait(bar(B_FULL + i % 3), (i / 3) & 1);
              const uint8_t* base = smem + (i % 3) * STG + r * 128;
#pragma unroll 1
              for (int j0 = 0; j0 < 4; j0 += 2) {
                uint4 v[2];
#pragma unroll
                for (int j = 0; j < 2; j++) v[j] = *(const uint4*)(base + ((((lane & 1) * 4 + j0 + j) ^ (r & 7)) << 4));
                if (i == 0 && j0 == 0) shift = __shfl_sync(0xffffffffu, bf_lo(v[0].x), lane & ~1);
#pragma unroll
                for (int j = 0; j < 2; j++) {
                  const uint32_t w[4] = {v[j].x, v[j].y, v[j].z, v[j].w};
#pragma unroll
                  for (int c = 0; c < 4; c++) {
                    const float d0 = bf_lo(w[c]) - shift, d1 = bf_hi(w[c]) - shift;
                    sum += d0 + d1; sq = fmaf(d0, d0, fmaf(d1, d1, sq));
                  }
                }
              }
              __syncwarp();
              if (i < 13) mbar_arrive_e(bar(B_EMPTY + i % 3));
            }
            sum += __shfl_xor_sync(0xffffffffu, sum, 1); sq += __shfl_xor_sync(0xffffffffu, sq, 1);
            const float dm = sum * (1.f / DM), var = fmaxf(sq * (1.f / DM) - dm * dm, 0.f), mean = shift + dm;
            const float inv = ln_inv(var);
            if ((lane & 1) == 0) st_relaxed4(&g_rowab[0][rb * 256 + r], make_uint4(__float_as_uint(inv), __float_as_uint(rbf(mean) * inv), tag, 0));
          }
          if (rb == 0) {
            mbar_wait(bar(B_QDONE), layer);
#pragma unroll 1
            for (int j = lane; j < 512; j += 32) ((uint4*)(smem + 65536))[j] = make_uint4(0, 0, 0, 0);
            fence_async_smem();
            __syncwarp();
            if (lane < 3) mbar_arrive(bar(B_HALO + lane));
          }
        } else if (warp == 3) {
          if (layer == 0) {
#pragma unroll 1
            for (int u = 0; u < GUA_AT; u++) mbar_wait(bar(B_FULL), u & 1);
          }
          fence_async_smem();
          load_gu(0, layer ? GU_PACE1 : GU_PACE);
          PROF(27);
        } else {
#pragma unroll 1
          for (int u = 4 * layer; u < 4; u++) mbar_wait(bar(B_FULL), u & 1);
          const uint4 sent = make_uint4(SENT, SENT, SENT, SENT), zero = make_uint4(0, 0, 0, 0);
#pragma unroll 1
          for (int t = lane; t < 128; t += 32) {
            g_ypart[layer][bid * 256 + t] = sent; g_ypart[layer][bid * 256 + 128 + t] = sent;
            g_part[layer][nb * SEQ + mb * 128 + t] = zero;
            if (t < 16) g_cand[layer][mb * 128 + nb * 16 + t] = sent;
            else if (t < 18) { if (nb == 0) g_slot[layer][mb * 8 + t - 16] = zero; }
            else if (t < 20) { if (layer == 0) g_x2row[bid * 2 + t - 18] = sent; }
            else if (t >= 80 && layer == 0) *(uint4*)&g_patch[rb][((t - 80) >> 4) * DM + hp * 64 + (t & 15) * 4] = sent;
          }
        }
        __syncwarp();
        if (rank == 0) {
          if (warp == 0) {
            mbar_wait(bar(B_QDONE), layer);
#pragma unroll 1
            for (int j = 0; j < 3; j++) {
              const int o = j == 0 ? 16384 : (j == 1 ? 0 : 65536);
              mbar_wait(bar(B_KVREADY + (j > 0)), layer);
              if (j == 1) {
                if (rb > 0) { import_halo(layer, 0); PROF(5); }
                else mbar_wait(bar(B_QREADY), layer);
              }
              bulk_push(mapa(sbase + o, 1), sbase + 32768 + o, j == 2 ? 32768 : 16384, mapa(bar(B_HALO + j), 1));
            }
          }
        } else if (warp > 0) {
          mbar_expect_tx(bar(B_HALO + warp - 1), warp == 3 ? 32768 : 16384);
        } else if (rb < 7) {
          mbar_wait(bar(B_KVREADY), layer);
          bulk_store(g_kv + (size_t)((rb >> 1) * 16 + hp) * 65536, sbase + 32768, 32768);
          bulk_commit();
          bulk_wait_all();
          set_flag(&g_kvflag[rb >> 1][hp][0].v[layer], s_misc[M_TAG]);
          PROF(4);
        }
      } else {
        const int t = tid - 128, go = (t >> 5) * DM + hp * 64 + (t & 31) * 2;
        if (layer == 0) {
          if (t == 0) { s_misc[M_TAG] = ld_relaxed(&g_epoch) + 1; s_misc[M_SEL0] = 0xFFFFFFFFu; }
#pragma unroll 1
          for (int u = 0; u < 5; u++) mbar_wait(bar(B_FULL + 2), u & 1);
          if (warp < 7) {
            uint2 v[4];
            uint32_t spins = 0;
#pragma unroll 1
            do {
#pragma unroll
              for (int j = 0; j < 4; j++) v[j] = ld_relaxed2(&g_cspart[j][go]);
            } while (!__all_sync(0xffffffffu, v[0].x && v[0].y && v[1].x && v[1].y && v[2].x && v[2].y && v[3].x && v[3].y) && ++spins < SPIN_LIMIT);
            ((float2*)(smem + OFF_CS))[t] = make_float2((dec(v[0].x) + dec(v[1].x)) + (dec(v[2].x) + dec(v[3].x)), (dec(v[0].y) + dec(v[1].y)) + (dec(v[2].y) + dec(v[3].y)));
          }
        } else {
          if ((int)s_misc[M_SEL0] >> 8 == rb && warp < 7) {
            float s0 = 0.f, s1 = 0.f;
#pragma unroll 1
            for (int hf = 0; hf < 8; hf += 4) {
              uint2 w[4];
              uint32_t spins = 0;
#pragma unroll 1
              do {
#pragma unroll
                for (int j = 0; j < 4; j++) w[j] = ld_relaxed2(&g_patch[hf + j][go]);
              } while (!__all_sync(0xffffffffu, valid4(make_uint4(w[0].x, w[0].y, w[1].x, w[1].y)) && valid4(make_uint4(w[2].x, w[2].y, w[3].x, w[3].y))) && ++spins < SPIN_LIMIT);
              s0 += (__uint_as_float(w[0].x) + __uint_as_float(w[1].x)) + (__uint_as_float(w[2].x) + __uint_as_float(w[3].x));
              s1 += (__uint_as_float(w[0].y) + __uint_as_float(w[1].y)) + (__uint_as_float(w[2].y) + __uint_as_float(w[3].y));
            }
            const float2 c = ((const float2*)(smem + OFF_CS))[t];
            const float a = __uint_as_float(s_misc[M_PINV]) * (warp == 4 ? SM_C : 1.f), b = __uint_as_float(s_misc[M_PMEAN]) * a;
            ((uint32_t*)(smem + OFF_PATCH))[t] = pack_bf16(s0 * a - c.x * b, s1 * a - c.y * b);
            PROF(25);
          }
        }
        __syncwarp();
        mbar_arrive_e(bar(B_CS));
      }
      __syncwarp();
      mbar_wait(bar(B_QREADY), layer);
      named_bar(1 + (fresh_tid() >> 7), 128);
      if (__shfl_sync(0xffffffffu, fresh_tid() >> 7, 0) == 0) {
        regs_inc<152>();
        uint32_t gu[112];
        {
          PHASE_IDS
          const uint32_t tag = s_misc[M_TAG];
          mbar_wait(bar(B_GU), layer);
#pragma unroll
          for (int j = 0; j < 28; j++) fetch_gu(gu + 4 * j, warp * 4 + (j & 3), j >> 2);
          fence_async_smem();
          named_bar(1, 128);
          if (warp == 0) {
            if (rank == 0) { if (rb > 0) import_halo(layer, 1); }
            else if (rb < 7) {
              bulk_store(g_kv + (size_t)((rb >> 1) * 16 + hp) * 65536 + 32768, sbase + 98304, 32768);
              bulk_commit();
              bulk_wait_all();
              set_flag(&g_kvflag[rb >> 1][hp][1].v[layer], tag);
            }
            load_gu(1, GUB_PACE);
            PROF(30);
            mbar_wait(bar(B_WGO), layer);
            mbar_wait(bar(B_ADONE), layer);
#pragma unroll 1
            for (int k = 2; k < 16; k++) {
              if (k == 8 && !(FAKE & 8)) { mbar_wait(bar(B_WGO + 1), layer); }
              if (k >= 4) mbar_wait(bar(B_WEMPTY + (k & 3)), ((k >> 2) - 1 + ((k & 2) ? layer : 0)) & 1);
              load_o(k); load_wo(k);
              STEPT(16 + k);
              if (k == RES_K) { mbar_wait(bar(B_OST + 1), layer); load_res(1, layer); }
            }
            if (layer == 1) {
              mbar_wait(bar(B_WEMPTY + 1), 1);
              if (FAKE & 2) mbar_arrive_e(bar(B_DN)); else mbar_expect_tx(bar(B_DN), 4 * FFN_PIECE);
              if (!(FAKE & 2)) tma_load3_h(sbase, &P.mapD, 0, bid * 28, 0, bar(B_DN), FFN_POL);
              if (D_SPLIT == 0) tma_load3_h(sbase + 2 * FFN_PIECE, &P.mapD, 0, bid * 28, 8, bar(B_DN), FFN_POL);
            }
            named_bar(6, 320);
            if (layer == 0) {
              mbar_wait(bar(B_QFREE), 0);
              load_w(0, 0); load_w(1, 1);
            } else if (D_SPLIT == 1 && !(FAKE & 2)) tma_load3_h(sbase + 2 * FFN_PIECE, &P.mapD, 0, bid * 28, 8, bar(B_DN), FFN_POL);
          } else if (warp == 1) {
            mbar_wait(bar(B_OST), layer);
            set_flag(&g_oflag[rb][0][hp].v[layer], tag);
            PROF(28);
            load_wo(0); load_wo(1); load_res(0, layer);
            poll_flag(&g_oflag[rb][0][lane & 15].v[layer], tag);
            fence_async_global();
            PROF(15);
            load_o(0); load_o(1);
            mbar_arrive_e(bar(B_WGO));
          } else if (warp == 2) {
            mbar_expect_tx(bar(B_HX), 2240);
            mbar_wait(bar(B_OST + 1), layer);
            set_flag(&g_oflag[rb][1][hp].v[layer], tag);
            PROF(31);
            poll_flag(&g_oflag[rb][1][lane & 15].v[layer], tag);
            fence_async_global();
            mbar_arrive_e(bar(B_WGO + 1));
            PROF(26);
          }
        }
        PHASE_IDS
        uint4 xa = {}, xb = {};
        named_bar(7, 512);
        if (g == 0) { xa = ((const uint4*)(smem + T_XS))[warp * 8 + q]; xb = ((const uint4*)(smem + T_XS))[warp * 8 + 4 + q]; }
        __syncwarp();
        float d[7][4] = {};
#pragma unroll
        for (int j = 0; j < 28; j++) {
          const int ks = j / 7, ct = j % 7;
          const uint32_t* a = gu + ct * 16 + ks * 4;
          mma_16816(d[ct], a[0], a[1], a[2], a[3], ks == 0 ? xa.x : ks == 1 ? xa.z : ks == 2 ? xb.x : xb.z, ks == 0 ? xa.y : ks == 1 ? xa.w : ks == 2 ? xb.y : xb.w);
        }
#pragma unroll
        for (int ct = 0; ct < 7; ct++) send_gu(d[ct][0], d[ct][2], ct, warp);
        __syncwarp();
        if (warp == 2) PROF(18);
        regs_dec<120>();
        pass_v = pass + 1;
        continue;
      }
      regs_inc<120>();
    }
    const unsigned layer = pass;
    {
      PHASE_IDS
      mbar_wait(bar(B_QREADY), layer);
      if (warp != 9) STEPT(7);
      auto kdesc = [&](int h, int b) { return dlo(SOFF, 16) + (rb == 0 && b < 4 ? 4096 : h * 4096 + b * 512); };
      auto vdesc = [&](int h, int b) { return rb == 0 && b < 4 ? dlo(SOFF + 65536, 4096) : dlo(SOFF + 4096, OFF_ONES - 4096) + (h * 8 + b) * 8 * VSTEP; };
      auto need = [&](int h, int b) { if (b == 3 || b == 1) mbar_wait(bar(B_HALO + (h ? 2 : b == 1)), layer); };
      auto load_q = [&](uint32_t* qf, int u) {
        *(uint4*)&qf[0] = *(const uint4*)(smem + AT_ST + ((u ^ 3) * 4 + wi) * 1024 + lane * 16);
        *(uint4*)&qf[4] = *(const uint4*)(smem + AT_ST + ((u ^ 3) * 4 + wi) * 1024 + 512 + lane * 16);
      };
      auto store_o = [&](const float* o, int u) {
        const float i0 = __fdividef(1.f, o[16]), i1 = __fdividef(1.f, o[18]);
        const int v = u ^ 3;
#pragma unroll
        for (int j = 0; j < 2; j++)
          stsm_x4(sbase + AT_ST + v * 4096 + srow * 64 + (((2 * j + (mi >> 1)) ^ ((srow >> 1) & 3)) << 4),
                  pack_bf16(o[8 * j] * i0, o[8 * j + 1] * i0), pack_bf16(o[8 * j + 2] * i1, o[8 * j + 3] * i1),
                  pack_bf16(o[8 * j + 4] * i0, o[8 * j + 5] * i0), pack_bf16(o[8 * j + 6] * i1, o[8 * j + 7] * i1));
        fence_async_smem();
        __syncwarp();
        bulk_store(g_o + (size_t)((((rb * 2 + ((v >> 1) & 1)) * 2 + (v >> 2)) * 16 + hp) * 8 + (v & 1) * 4 + wi) * 1024, sbase + AT_ST + (v * 4 + wi) * 1024, 1024);
        bulk_commit();
        if (u < 4) {
          bulk_wait_all();
          __syncwarp();
          if (lane < 2) mbar_arrive_cluster(bar(B_OST), lane);
        }
      };
      int redo = 0;
      {
        const int dl = g - 2 * q;
        const uint32_t mt = shl_clamp(0xFFFFFFFFu, max(16 * dl + 16, 0));
        uint32_t qf[8];
        float s[32];
        load_q(qf, 3 - wg);
        wg_fence();
        qk64(s, qf, kdesc(0, wg + 3));
        wg_commit();
        wg_wait<0>();
        fence_regs<32>(s);
#pragma unroll 1
        for (int u = 3 - wg; u < 8; u += 3) {
          const int h = u >> 2, qb = 3 - (u & 3);
          float o[20];
          uint32_t p1[16], p2[16], p3[16], p4[16], p5[16];
          if (warp != 9) STEPT(8 + nu * 8);
          exp_pack<8>(s, p1);
          fence_regs_u<16>(p1);
          need(h, qb + 2);
          {
            float s2[32];
            const uint32_t vd = vdesc(h, qb + 3);
            wg_fence();
            qk64(s2, qf, kdesc(h, qb + 2));
            wg_commit();
            wg_rs40t_z<H64>(o, p1[0], p1[1], p1[2], p1[3], vd);
            wg_rs40t<H64>(o, p1[4], p1[5], p1[6], p1[7], vd + VSTEP, 1);
            pv32(o, p1 + 8, vd + 2 * VSTEP);
            wg_commit();
            wg_wait<1>();
            fence_regs<32>(s2);
            if (warp != 9) STEPT(9 + nu * 8);
            exp_pack<8>(s2, p2);
            fence_regs_u<16>(p2);
            wg_wait<0>();
            fence_regs<20>(o);
          }
          need(h, qb + 1);
          {
            float s3[32];
            wg_fence();
            qk64(s3, qf, kdesc(h, qb + 1));
            wg_commit();
            pv32(o, p2, vdesc(h, qb + 2)); pv32(o, p2 + 8, vdesc(h, qb + 2) + 2 * VSTEP);
            wg_commit();
            wg_wait<1>();
            fence_regs<32>(s3);
            if (warp != 9) STEPT(10 + nu * 8);
            exp_pack<8>(s3, p3);
            fence_regs_u<16>(p3);
            wg_wait<0>();
            fence_regs<20>(o);
          }
          need(h, qb);
          const uint32_t kd = kdesc(h, qb + 4), kt = kdesc(h, qb), vd = vdesc(h, qb + 4), vt = vdesc(h, qb);
          {
            float sd[16], st[16];
            wg_fence();
            qk32x2(sd, st, qf, kd, kt);
            wg_commit();
            pv32(o, p3, vdesc(h, qb + 1)); pv32(o, p3 + 8, vdesc(h, qb + 1) + 2 * VSTEP);
            wg_commit();
            wg_wait<1>();
            fence_regs<16>(sd); fence_regs<16>(st);
            if (warp != 9) STEPT(11 + nu * 8);
            edge32(sd, st, p4, p4 + 8, wi, dl, mt);
            fence_regs_u<16>(p4);
            wg_wait<0>();
            fence_regs<20>(o);
          }
          const int un = min(u + 3, 7);
          {
            float sd[16], st[16];
            wg_fence();
            qk32x2(sd, st, qf, kd + 128, kt + 128);
            wg_commit();
            pv32(o, p4, vd); pv32(o, p4 + 8, vt);
            wg_commit();
            wg_wait<1>();
            fence_regs<16>(sd); fence_regs<16>(st);
            load_q(qf, un);
            edge32(sd, st, p5, p5 + 8, wi - 2, dl, mt);
            fence_regs_u<16>(p5);
          }
          need(un >> 2, 6 - (un & 3));
          wg_fence();
          pv32(o, p5, vd + 2 * VSTEP); pv32(o, p5 + 8, vt + 2 * VSTEP);
          wg_commit();
          qk64(s, qf, kdesc(un >> 2, 6 - (un & 3)));
          wg_commit();
          wg_wait<1>();
          fence_regs<20>(o);
          if (warp != 9) STEPT(12 + nu * 8);
          const bool unsafe = !(o[16] >= LSUM_MIN && o[16] <= LSUM_MAX && o[18] >= LSUM_MIN && o[18] <= LSUM_MAX);
          if (__any_sync(0xffffffffu, unsafe)) redo |= 1 << u;
          else store_o(o, u);
          wg_wait<0>();
          fence_regs<32>(s);
        }
      }
      if (warp != 9) STEPT(31);
      if (bar_red_or(1 + wg, 128, redo)) {
#pragma unroll 1
        for (int u = 3 - wg; u < 8; u += 3) {
          if (!bar_red_or(1 + wg, 128, redo >> u & 1)) continue;
          const int h = u >> 2, qb = 3 - (u & 3);
          uint32_t qf[8], p[16];
          float o[20], m0 = -INFINITY, m1 = -INFINITY;
          load_q(qf, u);
#pragma unroll
          for (int i = 0; i < 20; i++) o[i] = 0.f;
#pragma unroll 1
          for (int j = 0; j <= (rb == 0 ? qb : 4); j++) {
            const int b = qb + 4 - j;
            float s[32];
            wg_fence();
            qk64(s, qf, kdesc(h, b));
            wg_commit();
            wg_wait<0>();
            fence_regs<32>(s);
            float mx0 = m0, mx1 = m1;
#pragma unroll
            for (int c = 0; c < 8; c++) {
#pragma unroll
              for (int i = 0; i < 4; i++) {
                const int diff = j * 64 + (16 * wi + g + (i >> 1) * 8) - (8 * c + 2 * q + (i & 1));
                if (diff < 0 || diff > 255) s[4 * c + i] = -INFINITY;
              }
              mx0 = fmaxf(mx0, fmaxf(s[4 * c], s[4 * c + 1]));
              mx1 = fmaxf(mx1, fmaxf(s[4 * c + 2], s[4 * c + 3]));
            }
            mx0 = fmaxf(mx0, __shfl_xor_sync(0xffffffffu, mx0, 1)); mx1 = fmaxf(mx1, __shfl_xor_sync(0xffffffffu, mx1, 1));
            mx0 = fmaxf(mx0, __shfl_xor_sync(0xffffffffu, mx0, 2)); mx1 = fmaxf(mx1, __shfl_xor_sync(0xffffffffu, mx1, 2));
            const float r0 = j == 0 ? 0.f : ex2(m0 - mx0), r1 = j == 0 ? 0.f : ex2(m1 - mx1);
            m0 = mx0; m1 = mx1;
#pragma unroll
            for (int i = 0; i < 5; i++) { o[4 * i] *= r0; o[4 * i + 1] *= r0; o[4 * i + 2] *= r1; o[4 * i + 3] *= r1; }
#pragma unroll
            for (int c = 0; c < 8; c++) { s[4 * c] -= m0; s[4 * c + 1] -= m0; s[4 * c + 2] -= m1; s[4 * c + 3] -= m1; }
            exp_pack<8>(s, p);
            fence_regs<20>(o); fence_regs_u<16>(p);
            wg_fence();
            pv32(o, p, vdesc(h, b)); pv32(o, p + 8, vdesc(h, b) + 2 * VSTEP);
            wg_commit();
            wg_wait<0>();
            fence_regs<20>(o);
          }
          named_bar(1 + wg, 128);
          if (redo >> u & 1) store_o(o, u);
          __syncwarp();
        }
      }
    }
    {
      PHASE_IDS
      if (wi == 0) PROF(6 + wg);
      if (wi == 3 && lane < 2) mbar_arrive_cluster(bar(B_ADONE), lane);
      bulk_wait_all();
      __syncwarp();
      mbar_arrive_e(bar(B_OST + 1));
    }
    pass_v = pass + 1;
  }
}

}

typedef CUresult (*EncodeFn)(CUtensorMap*, CUtensorMapDataType, cuuint32_t, void*, const cuuint64_t*, const cuuint64_t*,
                             const cuuint32_t*, const cuuint32_t*, CUtensorMapInterleave, CUtensorMapSwizzle,
                             CUtensorMapL2promotion, CUtensorMapFloatOOBfill);
static EncodeFn g_encode = nullptr;
struct Dim { uint64_t size, stride; uint32_t box; };
template <int N> static CUtensorMap make_map(const void* ptr, const Dim (&d)[N], int swizzle) {
  CUtensorMap m;
  cuuint64_t dims[N], strides[N];
  cuuint32_t box[N], es[N];
  for (int i = 0; i < N; i++) { dims[i] = d[i].size; strides[i] = d[i].stride; box[i] = d[i].box; es[i] = 1; }
  g_encode(&m, CU_TENSOR_MAP_DATA_TYPE_BFLOAT16, N, const_cast<void*>(ptr), dims, strides + 1, box, es, CU_TENSOR_MAP_INTERLEAVE_NONE,
           swizzle == 128 ? CU_TENSOR_MAP_SWIZZLE_128B : (swizzle == 64 ? CU_TENSOR_MAP_SWIZZLE_64B : CU_TENSOR_MAP_SWIZZLE_NONE),
           swizzle ? CU_TENSOR_MAP_L2_PROMOTION_L2_256B : CU_TENSOR_MAP_L2_PROMOTION_L2_128B, CU_TENSOR_MAP_FLOAT_OOB_FILL_NONE);
  return m;
}
static CUtensorMap map2(const void* ptr, uint64_t inner, uint64_t outer, uint32_t bi, uint32_t bo, int swizzle) {
  const Dim d[2] = {{inner, 0, bi}, {outer, inner * 2, bo}};
  return make_map(ptr, d, swizzle);
}
template <class T> static void* sym_addr(T& sym) { void* p = nullptr; cudaGetSymbolAddress(&p, sym); return p; }

static Params h_p, h_p_helper;
static const void* h_key[9];
static bool h_helpers_fit = true;

static cudaLaunchConfig_t launch_cfg(int grid, cudaLaunchAttribute* at) {
  cudaLaunchConfig_t cfg = {};
  cfg.gridDim = dim3(grid); cfg.blockDim = dim3(512); cfg.dynamicSmemBytes = SMEM_BYTES; cfg.stream = cudaStreamPerThread;
  at[0].id = cudaLaunchAttributeClusterDimension;
  at[0].val.clusterDim.x = 2; at[0].val.clusterDim.y = 1; at[0].val.clusterDim.z = 1;
  cfg.attrs = at; cfg.numAttrs = 1;
  return cfg;
}

extern "C" void kernel_launch(void* const* d_in, const int* in_sizes, int n_in, void* d_out, int out_size) {
  const bf16* x = (const bf16*)d_in[0];
  const bf16* wqkv = (const bf16*)d_in[1];
  const bf16* wo = (const bf16*)d_in[2];
  cudaLaunchAttribute at[1];
  bool fresh = g_encode != nullptr && h_key[8] == d_out;
  for (int i = 0; i < 8; i++) fresh = fresh && h_key[i] == d_in[i];
  if (!fresh) {
    if (!g_encode) {
      void* fn = nullptr;
      cudaDriverEntryPointQueryResult st;
      cudaGetDriverEntryPoint("cuTensorMapEncodeTiled", &fn, cudaEnableDefault, &st);
      g_encode = (EncodeFn)fn;
      cudaFuncSetAttribute(mega_kernel, cudaFuncAttributeMaxDynamicSharedMemorySize, SMEM_BYTES);
      cudaLaunchConfig_t cfg = launch_cfg(132, at);
      int nclusters = 0;
      if (cudaOccupancyMaxActiveClusters(&nclusters, mega_kernel, &cfg) != cudaSuccess) { nclusters = 0; (void)cudaGetLastError(); }
      h_helpers_fit = nclusters >= 66;
    }
    bf16* x1 = (bf16*)sym_addr(g_x1);
    Params& p = h_p;
    p.x = x; p.wqkv = wqkv; p.wo = wo; p.w_r = (const bf16*)d_in[4]; p.w_g = (const bf16*)d_in[5]; p.w_u = (const bf16*)d_in[6]; p.w_d = (const bf16*)d_in[7];
    p.out = (bf16*)d_out;
    p.mapA[0] = map2(x, DM, SEQ, 64, 256, 128);
    p.mapA[1] = map2(x1, DM, SEQ, 64, 256, 128);
    { const Dim d[3] = {{DM, 0, 64}, {DM, 3 * DM * 2, 32}, {3, DM * 2, 3}}; p.mapW = make_map(wqkv, d, 128); }
    { const Dim d[3] = {{DM, 0, 64}, {64, DM * 2, 32}, {16, 64 * DM * 2, 2}}; p.mapWo = make_map(wo, d, 128); }
    p.mapRes[0] = map2(x, DM, SEQ, 64, 64, 128);
    p.mapRes[1] = p.mapXst[0] = map2(x1, DM, SEQ, 64, 64, 128);
    p.mapXst[1] = map2(d_out, DM, SEQ, 64, 64, 128);
    p.mapG = map2(p.w_g, FF, DM, 56, 128, 0);
    p.mapU = map2(p.w_u, FF, DM, 56, 128, 0);
    { const Dim d[3] = {{64, 0, 64}, {FF, DM * 2, 28}, {DM / 64, 128, 8}}; p.mapD = make_map(p.w_d, d, 128); }
    p.helper_first = 128;
    h_p_helper = p;
    h_p_helper.helper_first = 0;
    for (int i = 0; i < 8; i++) h_key[i] = d_in[i];
    h_key[8] = d_out;
  }
  if (!h_helpers_fit) {
    void* ah[] = {&h_p_helper};
    cudaLaunchConfig_t cfg = launch_cfg(4, at);
    cudaLaunchKernelExC(&cfg, (const void*)mega_kernel, ah);
  }
  void* a0[] = {&h_p};
  cudaLaunchConfig_t cfg = launch_cfg(h_helpers_fit ? 132 : 128, at);
  cudaLaunchKernelExC(&cfg, (const void*)mega_kernel, a0);
}
```

```cpp
#include <cuda_runtime.h>
#include <cuda_bf16.h>
#include <cuda.h>
#include <stdint.h>

namespace {

constexpr int SEQ = 2048, DM = 1024, FF = 3584;
constexpr float LN_EPS = 1e-5f;
typedef __nv_bfloat16 bf16;

__device__ __align__(1024) uint8_t g_kv[3 * 16 * 65536];
__device__ __align__(1024) uint8_t g_o[SEQ * DM * 2];
__device__ __align__(1024) bf16 g_x1[SEQ * DM];
__device__ unsigned g_epoch;
struct __align__(128) Flag { unsigned v[32]; };
__device__ Flag g_kvflag[3][16][2], g_oflag[8][2][16], g_xflag[16][8];
__device__ uint4 g_rowab[2][SEQ];
__device__ __align__(16) uint32_t g_cspart[4][3 * DM];
constexpr uint32_t SENT = 0xFFFFFFFFu;
__device__ uint4 g_part[2][8 * SEQ];
__device__ uint4 g_slot[2][16 * 8];
__device__ uint4 g_cand[2][16 * 128];
__device__ uint4 g_ypart[2][128 * DM / 4];
__device__ uint4 g_x2row[128 * 2];
__device__ __align__(16) uint32_t g_patch[8][3 * DM];
__device__ float2 g_rowln[8][SEQ];
__device__ int g_sel[2];

#define PROFL(l, e)
#define PROF(e) PROFL(layer, e)
#define STEPT(i)
#define SPIN_LIMIT 4000000u
__device__ __forceinline__ uint32_t smem_u32(const void* p) { return (uint32_t)__cvta_generic_to_shared(p); }
__device__ __forceinline__ void mbar_init(uint32_t bar, uint32_t cnt) {
  asm volatile("mbarrier.init.shared::cta.b64 [%0], %1;" ::"r"(bar), "r"(cnt) : "memory");
}
#define ELECT "{\n.reg .pred e;\nelect.sync _|e, 0xffffffff;\n@e "
__device__ __forceinline__ void mbar_expect_tx(uint32_t bar, uint32_t bytes) {
  asm volatile(ELECT "mbarrier.arrive.expect_tx.shared::cta.b64 _, [%0], %1;\n}" ::"r"(bar), "r"(bytes) : "memory");
}
__device__ __forceinline__ void mbar_arrive(uint32_t bar) {
  asm volatile("mbarrier.arrive.shared::cta.b64 _, [%0];" ::"r"(bar) : "memory");
}
__device__ __forceinline__ void mbar_arrive_e(uint32_t bar) {
  asm volatile(ELECT "mbarrier.arrive.shared::cta.b64 _, [%0];\n}" ::"r"(bar) : "memory");
}
__device__ __forceinline__ uint32_t mapa(uint32_t addr, uint32_t cta) {
  uint32_t r; asm("mapa.shared::cluster.u32 %0, %1, %2;" : "=r"(r) : "r"(addr), "r"(cta)); return r;
}
__device__ __forceinline__ void mbar_arrive_cluster(uint32_t bar, uint32_t cta) {
  asm volatile("mbarrier.arrive.shared::cluster.b64 _, [%0];" ::"r"(mapa(bar, cta)) : "memory");
}
#define MBAR_WAIT_ASM(QUAL)                                                                                                \
  asm volatile("{\n.reg .pred p;\n.reg .u32 n;\nmov.u32 n, 0;\nWAIT_LOOP:\n.pragma \"nounroll\";\n"                         \
               "mbarrier.try_wait.parity" QUAL ".shared::cta.b64 p, [%0], %1;\n@p bra WAIT_DONE;\n"                        \
               "add.u32 n, n, 1;\nsetp.lt.u32 p, n, %2;\n@p bra WAIT_LOOP;\nWAIT_DONE:\n}" ::"r"(bar), "r"(parity), "n"(SPIN_LIMIT) : "memory")
__device__ __forceinline__ void mbar_wait(uint32_t bar, uint32_t parity) { MBAR_WAIT_ASM(""); }
__device__ __forceinline__ void mbar_wait_cluster(uint32_t bar, uint32_t parity) { MBAR_WAIT_ASM(".acquire.cluster"); }
__device__ __forceinline__ bool mbar_wait_brief(uint32_t bar, uint32_t parity) {
  uint32_t ok;
  asm volatile("{\n.reg .pred p;\nmbarrier.try_wait.parity.shared::cta.b64 p, [%1], %2, 1000;\nselp.u32 %0, 1, 0, p;\n}"
               : "=r"(ok) : "r"(bar), "r"(parity) : "memory");
  return __all_sync(0xffffffffu, ok);
}
__device__ __forceinline__ void st_async2(uint32_t addr, float a, float b, uint32_t bar) {
  asm volatile("st.async.weak.shared::cluster.mbarrier::complete_tx::bytes.v2.f32 [%0], {%1, %2}, [%3];"
               ::"r"(addr), "f"(a), "f"(b), "r"(bar) : "memory");
}
__device__ __forceinline__ uint64_t policy_evict_first() {
  uint64_t p; asm volatile("createpolicy.fractional.L2::evict_first.b64 %0, 1.0;" : "=l"(p)); return p;
}
__device__ __forceinline__ uint64_t policy_normal() {
  uint64_t p; asm volatile("createpolicy.fractional.L2::evict_normal.b64 %0, 1.0;" : "=l"(p)); return p;
}
__device__ __forceinline__ void tma_load2(uint32_t dst, const CUtensorMap* m, int c0, int c1, uint32_t bar) {
  asm volatile(ELECT "cp.async.bulk.tensor.2d.shared::cluster.global.mbarrier::complete_tx::bytes [%0], [%1, {%3, %4}], [%2];\n}"
               ::"r"(dst), "l"(m), "r"(bar), "r"(c0), "r"(c1) : "memory");
}
__device__ __forceinline__ void tma_load2_h(uint32_t dst, const CUtensorMap* m, int c0, int c1, uint32_t bar, uint64_t pol) {
  asm volatile(ELECT "cp.async.bulk.tensor.2d.shared::cluster.global.mbarrier::complete_tx::bytes.L2::cache_hint [%0], [%1, {%3, %4}], [%2], %5;\n}"
               ::"r"(dst), "l"(m), "r"(bar), "r"(c0), "r"(c1), "l"(pol) : "memory");
}
__device__ __forceinline__ void tma_load3(uint32_t dst, const CUtensorMap* m, int c0, int c1, int c2, uint32_t bar) {
  asm volatile(ELECT "cp.async.bulk.tensor.3d.shared::cluster.global.mbarrier::complete_tx::bytes [%0], [%1, {%3, %4, %5}], [%2];\n}"
               ::"r"(dst), "l"(m), "r"(bar), "r"(c0), "r"(c1), "r"(c2) : "memory");
}
__device__ __forceinline__ void tma_load3_h(uint32_t dst, const CUtensorMap* m, int c0, int c1, int c2, uint32_t bar, uint64_t pol) {
  asm volatile(ELECT "cp.async.bulk.tensor.3d.shared::cluster.global.mbarrier::complete_tx::bytes.L2::cache_hint [%0], [%1, {%3, %4, %5}], [%2], %6;\n}"
               ::"r"(dst), "l"(m), "r"(bar), "r"(c0), "r"(c1), "r"(c2), "l"(pol) : "memory");
}
__device__ __forceinline__ void tma_load3_mc(uint32_t dst, const CUtensorMap* m, int c0, int c1, int c2, uint32_t bar) {
  asm volatile(ELECT "cp.async.bulk.tensor.3d.shared::cluster.global.mbarrier::complete_tx::bytes.multicast::cluster [%0], [%1, {%3, %4, %5}], [%2], %6;\n}"
               ::"r"(dst), "l"(m), "r"(bar), "r"(c0), "r"(c1), "r"(c2), "h"((uint16_t)3) : "memory");
}
__device__ __forceinline__ void bulk_push(uint32_t dst, uint32_t src, uint32_t bytes, uint32_t bar) {
  asm volatile(ELECT "cp.async.bulk.shared::cluster.shared::cta.mbarrier::complete_tx::bytes [%0], [%1], %2, [%3];\n}"
               ::"r"(dst), "r"(src), "r"(bytes), "r"(bar) : "memory");
}
template <int N> __device__ __forceinline__ void regs_inc() { asm volatile("setmaxnreg.inc.sync.aligned.u32 %0;" ::"n"(N)); }
template <int N> __device__ __forceinline__ void regs_dec() { asm volatile("setmaxnreg.dec.sync.aligned.u32 %0;" ::"n"(N)); }
__device__ __forceinline__ void tma_prefetch2(const CUtensorMap* m, int c0, int c1) {
  asm volatile(ELECT "cp.async.bulk.prefetch.tensor.2d.L2.global [%0, {%1, %2}];\n}" ::"l"(m), "r"(c0), "r"(c1) : "memory");
}
__device__ __forceinline__ void bulk_prefetch(const void* p, uint32_t bytes) {
  asm volatile(ELECT "cp.async.bulk.prefetch.L2.global [%0], %1;\n}" ::"l"(p), "r"(bytes) : "memory");
}
__device__ __forceinline__ void tma_store(const CUtensorMap* m, uint32_t src, int c0, int c1) {
  asm volatile(ELECT "cp.async.bulk.tensor.2d.global.shared::cta.bulk_group [%0, {%2, %3}], [%1];\n}"
               ::"l"(m), "r"(src), "r"(c0), "r"(c1) : "memory");
}
__device__ __forceinline__ void bulk_load(uint32_t dst, const void* src, uint32_t bytes, uint32_t bar) {
  asm volatile(ELECT "cp.async.bulk.shared::cluster.global.mbarrier::complete_tx::bytes [%0], [%1], %2, [%3];\n}"
               ::"r"(dst), "l"(src), "r"(bytes), "r"(bar) : "memory");
}
__device__ __forceinline__ void bulk_load_h(uint32_t dst, const void* src, uint32_t bytes, uint32_t bar, uint64_t pol) {
  asm volatile(ELECT "cp.async.bulk.shared::cluster.global.mbarrier::complete_tx::bytes.L2::cache_hint [%0], [%1], %2, [%3], %4;\n}"
               ::"r"(dst), "l"(src), "r"(bytes), "r"(bar), "l"(pol) : "memory");
}
__device__ __forceinline__ void bulk_store(void* dst, uint32_t src, uint32_t bytes) {
  asm volatile(ELECT "cp.async.bulk.global.shared::cta.bulk_group [%0], [%1], %2;\n}" ::"l"(dst), "r"(src), "r"(bytes) : "memory");
}
__device__ __forceinline__ void bulk_commit() { asm volatile("cp.async.bulk.commit_group;" ::: "memory"); }
__device__ __forceinline__ void bulk_wait_all() { asm volatile("cp.async.bulk.wait_group 0;" ::: "memory"); }
__device__ __forceinline__ void fence_async_smem() { asm volatile("fence.proxy.async.shared::cta;" ::: "memory"); }
__device__ __forceinline__ void fence_async_global() { asm volatile("fence.proxy.async.global;" ::: "memory"); }
__device__ __forceinline__ void fence_release() { asm volatile("fence.release.gpu;" ::: "memory"); }
__device__ __forceinline__ void l2_prefetch_line(const void* p) { asm volatile("prefetch.global.L2 [%0];" ::"l"(p) : "memory"); }
__device__ __forceinline__ void prefetch_tmap(const CUtensorMap* m) { asm volatile("prefetch.tensormap [%0];" ::"l"(m) : "memory"); }
__device__ __forceinline__ void named_bar(int id, int n) { asm volatile("bar.sync %0, %1;" ::"r"(id), "r"(n) : "memory"); }
__device__ __forceinline__ bool bar_red_or(int id, int n, bool v) {
  uint32_t r;
  asm volatile("{\n.reg .pred p, q;\nsetp.ne.u32 q, %3, 0;\nbarrier.cta.red.or.pred p, %1, %2, q;\nselp.u32 %0, 1, 0, p;\n}"
               : "=r"(r) : "r"(id), "r"(n), "r"((uint32_t)v) : "memory");
  return r != 0;
}
__device__ __forceinline__ void cluster_arrive() { asm volatile("barrier.cluster.arrive.relaxed.aligned;" ::: "memory"); }
__device__ __forceinline__ void cluster_wait() { asm volatile("barrier.cluster.wait.aligned;" ::: "memory"); }
__device__ __forceinline__ uint32_t cluster_rank() { uint32_t r; asm volatile("mov.u32 %0, %%cluster_ctarank;" : "=r"(r)); return r; }
__device__ __forceinline__ unsigned ld_relaxed(const unsigned* p) {
  unsigned v; asm volatile("ld.relaxed.gpu.global.u32 %0, [%1];" : "=r"(v) : "l"(p) : "memory"); return v;
}
__device__ __forceinline__ uint4 ld_relaxed4(const uint4* p) {
  uint4 v; asm volatile("ld.relaxed.gpu.global.v4.u32 {%0, %1, %2, %3}, [%4];" : "=r"(v.x), "=r"(v.y), "=r"(v.z), "=r"(v.w) : "l"(p) : "memory"); return v;
}
__device__ __forceinline__ void st_relaxed(unsigned* p, unsigned v) {
  asm volatile("st.relaxed.gpu.global.u32 [%0], %1;" ::"l"(p), "r"(v) : "memory");
}
__device__ __forceinline__ uint2 ld_relaxed2(const void* p) {
  uint2 v; asm volatile("ld.relaxed.gpu.global.v2.u32 {%0, %1}, [%2];" : "=r"(v.x), "=r"(v.y) : "l"(p) : "memory"); return v;
}
__device__ __forceinline__ void st_relaxed4(uint4* p, uint4 v) {
  asm volatile("st.relaxed.gpu.global.v4.u32 [%0], {%1, %2, %3, %4};" ::"l"(p), "r"(v.x), "r"(v.y), "r"(v.z), "r"(v.w) : "memory");
}
__device__ __forceinline__ bool valid4(uint4 v) { return v.x != SENT && v.y != SENT && v.z != SENT && v.w != SENT; }
__device__ __forceinline__ uint4 poll4(const uint4* p) {
  uint4 v;
  uint32_t spins = 0;
#pragma unroll 1
  do { v = ld_relaxed4(p); } while (!valid4(v) && ++spins < SPIN_LIMIT);
  return v;
}
__device__ __forceinline__ void set_flag(unsigned* p, unsigned tag) {
  asm volatile(ELECT "st.release.gpu.global.u32 [%0], %1;\n}" ::"l"(p), "r"(tag) : "memory");
}
__device__ __forceinline__ void poll_flag(const unsigned* p, unsigned tag) {
#pragma unroll 1
  for (uint32_t spins = 0; !__all_sync(0xffffffffu, ld_relaxed(p) == tag) && spins < SPIN_LIMIT; spins++) {}
  asm volatile("fence.acquire.gpu;" ::: "memory");
}
__device__ __forceinline__ uint32_t enc(float x) { return __float_as_uint(x + 0.0f) ^ 0x80000000u; }
__device__ __forceinline__ float dec(uint32_t u) { return __uint_as_float(u ^ 0x80000000u); }
__device__ __forceinline__ uint32_t f2u(float x) { uint32_t u = __float_as_uint(x); return u == SENT ? 0x7FFFFFFFu : u; }
__device__ __forceinline__ uint32_t nosent(uint32_t u) { return u == SENT ? 0x7FFF7FFFu : u; }
__device__ __forceinline__ uint32_t hadd_bf2(uint32_t a, uint32_t b) {
  uint32_t r; asm("add.rn.bf16x2 %0, %1, %2;" : "=r"(r) : "r"(a), "r"(b)); return r;
}
__device__ __forceinline__ uint32_t hsub_bf2(uint32_t a, uint32_t b) {
  uint32_t r; asm("sub.rn.bf16x2 %0, %1, %2;" : "=r"(r) : "r"(a), "r"(b)); return r;
}
__device__ __forceinline__ void wg_fence() { asm volatile("wgmma.fence.sync.aligned;" ::: "memory"); }
__device__ __forceinline__ void wg_commit() { asm volatile("wgmma.commit_group.sync.aligned;" ::: "memory"); }
template <int N> __device__ __forceinline__ void wg_wait() { asm volatile("wgmma.wait_group.sync.aligned %0;" ::"n"(N) : "memory"); }
template <int R> __device__ __forceinline__ void fence_regs(float* d) {
#pragma unroll
  for (int i = 0; i < R; i++) asm volatile("" : "+f"(d[i])::"memory");
}
template <int R> __device__ __forceinline__ void fence_regs_u(uint32_t* d) {
#pragma unroll
  for (int i = 0; i < R; i++) asm volatile("" : "+r"(d[i])::"memory");
}
__host__ __device__ constexpr uint32_t dlo(uint32_t addr, uint32_t lbo) { return ((addr & 0x3FFFF) >> 4) | ((lbo >> 4) << 16); }
constexpr uint32_t H128 = 0x40000040u, H64 = 0x80000020u;
__device__ __forceinline__ void stsm_x4(uint32_t addr, uint32_t r0, uint32_t r1, uint32_t r2, uint32_t r3) {
  asm volatile("stmatrix.sync.aligned.m8n8.x4.shared.b16 [%0], {%1, %2, %3, %4};"
               ::"r"(addr), "r"(r0), "r"(r1), "r"(r2), "r"(r3) : "memory");
}
__device__ __forceinline__ void ldsm_x4(uint32_t addr, uint32_t& r0, uint32_t& r1, uint32_t& r2, uint32_t& r3) {
  asm volatile("ldmatrix.sync.aligned.m8n8.x4.shared.b16 {%0, %1, %2, %3}, [%4];"
               : "=r"(r0), "=r"(r1), "=r"(r2), "=r"(r3) : "r"(addr) : "memory");
}
__device__ __forceinline__ void ldsm_x4_t(uint32_t addr, uint32_t& r0, uint32_t& r1, uint32_t& r2, uint32_t& r3) {
  asm volatile("ldmatrix.sync.aligned.m8n8.x4.trans.shared.b16 {%0, %1, %2, %3}, [%4];"
               : "=r"(r0), "=r"(r1), "=r"(r2), "=r"(r3) : "r"(addr) : "memory");
}
__device__ __forceinline__ void mma_16816(float* d, uint32_t a0, uint32_t a1, uint32_t a2, uint32_t a3, uint32_t b0, uint32_t b1) {
  asm volatile("mma.sync.aligned.m16n8k16.row.col.f32.bf16.bf16.f32 {%0, %1, %2, %3}, {%4, %5, %6, %7}, {%8, %9}, {%0, %1, %2, %3};"
               : "+f"(d[0]), "+f"(d[1]), "+f"(d[2]), "+f"(d[3]) : "r"(a0), "r"(a1), "r"(a2), "r"(a3), "r"(b0), "r"(b1));
}
__device__ __forceinline__ void spin_cycles(int n) {
  const int t0 = (int)clock();
#pragma unroll 1
  while ((int)clock() - t0 < n) {}
}
__device__ __forceinline__ uint32_t pack_bf16(float lo, float hi) {
  uint32_t r; asm("cvt.rn.bf16x2.f32 %0, %1, %2;" : "=r"(r) : "f"(hi), "f"(lo)); return r;
}
__device__ __forceinline__ float bf_lo(uint32_t v) { return __uint_as_float(v << 16); }
__device__ __forceinline__ float bf_hi(uint32_t v) { return __uint_as_float(v & 0xffff0000u); }
__device__ __forceinline__ float rbf(float x) { return __bfloat162float(__float2bfloat16_rn(x)); }
__device__ __forceinline__ float ex2(float x) { float y; asm("ex2.approx.ftz.f32 %0, %1;" : "=f"(y) : "f"(x)); return y; }
__device__ __forceinline__ uint32_t shl_clamp(uint32_t v, uint32_t n) {
  uint32_t r; asm("shl.b32 %0, %1, %2;" : "=r"(r) : "r"(v), "r"(n)); return r;
}
__device__ __forceinline__ float warp_sum(float v) {
#pragma unroll
  for (int o = 16; o > 0; o >>= 1) v += __shfl_xor_sync(0xffffffffu, v, o);
  return v;
}
__device__ __forceinline__ float ln_inv(float var) {
  float r;
  asm("sqrt.approx.ftz.f32 %0, %1;" : "=f"(r) : "f"(rbf(rbf(var) + LN_EPS)));
  asm("rcp.approx.ftz.f32 %0, %1;" : "=f"(r) : "f"(rbf(r)));
  return r;
}
__device__ __forceinline__ uint32_t ln_pair(uint32_t x, uint32_t mean2, float inv) {
  const uint32_t d = hsub_bf2(x, mean2);
  return pack_bf16(bf_lo(d) * inv, bf_hi(d) * inv);
}
__device__ __forceinline__ uint32_t add_ln_pair(uint32_t x, uint32_t mean2, float inv) { return hadd_bf2(x, ln_pair(x, mean2, inv)); }
__device__ __forceinline__ uint32_t router_key(float r_bf, int row) {
  uint32_t u = __float_as_uint(r_bf);
  u = (u & 0x80000000u) ? ~u : (u | 0x80000000u);
  return (u & 0xFFFF0000u) | 0x8000u | (uint32_t)(SEQ - 1 - row);
}

template <uint32_t HA = 0x40000040u, uint32_t HB = 0x40000040u>
__device__ __forceinline__ void wg_ss192t(float* d, uint32_t da, uint32_t db, int scale_d) {
  asm volatile("{\n.reg .pred p;\n.reg .b64 dA, dB;\nmov.b64 dA, {%96, %99};\nmov.b64 dB, {%97, %100};\nsetp.ne.b32 p, %98, 0;\n"
    "wgmma.mma_async.sync.aligned.m64n192k16.f32.bf16.bf16 "
    "{%0, %1, %2, %3, %4, %5, %6, %7, %8, %9, %10, %11, %12, %13, %14, %15, "
    "%16, %17, %18, %19, %20, %21, %22, %23, %24, %25, %26, %27, %28, %29, %30, %31, "
    "%32, %33, %34, %35, %36, %37, %38, %39, %40, %41, %42, %43, %44, %45, %46, %47, "
    "%48, %49, %50, %51, %52, %53, %54, %55, %56, %57, %58, %59, %60, %61, %62, %63, "
    "%64, %65, %66, %67, %68, %69, %70, %71, %72, %73, %74, %75, %76, %77, %78, %79, "
    "%80, %81, %82, %83, %84, %85, %86, %87, %88, %89, %90, %91, %92, %93, %94, %95}, "
    "dA, dB, p, 1, 1, 0, 1;\n}\n"
    : "+f"(d[0]), "+f"(d[1]), "+f"(d[2]), "+f"(d[3]), "+f"(d[4]), "+f"(d[5]), "+f"(d[6]), "+f"(d[7]),
      "+f"(d[8]), "+f"(d[9]), "+f"(d[10]), "+f"(d[11]), "+f"(d[12]), "+f"(d[13]), "+f"(d[14]), "+f"(d[15]),
      "+f"(d[16]), "+f"(d[17]), "+f"(d[18]), "+f"(d[19]), "+f"(d[20]), "+f"(d[21]), "+f"(d[22]), "+f"(d[23]),
      "+f"(d[24]), "+f"(d[25]), "+f"(d[26]), "+f"(d[27]), "+f"(d[28]), "+f"(d[29]), "+f"(d[30]), "+f"(d[31]),
      "+f"(d[32]), "+f"(d[33]), "+f"(d[34]), "+f"(d[35]), "+f"(d[36]), "+f"(d[37]), "+f"(d[38]), "+f"(d[39]),
      "+f"(d[40]), "+f"(d[41]), "+f"(d[42]), "+f"(d[43]), "+f"(d[44]), "+f"(d[45]), "+f"(d[46]), "+f"(d[47]),
      "+f"(d[48]), "+f"(d[49]), "+f"(d[50]), "+f"(d[51]), "+f"(d[52]), "+f"(d[53]), "+f"(d[54]), "+f"(d[55]),
      "+f"(d[56]), "+f"(d[57]), "+f"(d[58]), "+f"(d[59]), "+f"(d[60]), "+f"(d[61]), "+f"(d[62]), "+f"(d[63]),
      "+f"(d[64]), "+f"(d[65]), "+f"(d[66]), "+f"(d[67]), "+f"(d[68]), "+f"(d[69]), "+f"(d[70]), "+f"(d[71]),
      "+f"(d[72]), "+f"(d[73]), "+f"(d[74]), "+f"(d[75]), "+f"(d[76]), "+f"(d[77]), "+f"(d[78]), "+f"(d[79]),
      "+f"(d[80]), "+f"(d[81]), "+f"(d[82]), "+f"(d[83]), "+f"(d[84]), "+f"(d[85]), "+f"(d[86]), "+f"(d[87]),
      "+f"(d[88]), "+f"(d[89]), "+f"(d[90]), "+f"(d[91]), "+f"(d[92]), "+f"(d[93]), "+f"(d[94]), "+f"(d[95])
    : "r"(da), "r"(db), "r"(scale_d), "n"(HA), "n"(HB));
}
template <uint32_t HA = 0x40000040u, uint32_t HB = 0x40000040u>
__device__ __forceinline__ void wg_ss192t_z(float* d, uint32_t da, uint32_t db) {
  asm volatile("{\n.reg .pred p;\n.reg .b64 dA, dB;\nmov.b64 dA, {%96, %98};\nmov.b64 dB, {%97, %99};\nsetp.ne.b32 p, 0, 0;\n"
    "wgmma.mma_async.sync.aligned.m64n192k16.f32.bf16.bf16 "
    "{%0, %1, %2, %3, %4, %5, %6, %7, %8, %9, %10, %11, %12, %13, %14, %15, "
    "%16, %17, %18, %19, %20, %21, %22, %23, %24, %25, %26, %27, %28, %29, %30, %31, "
    "%32, %33, %34, %35, %36, %37, %38, %39, %40, %41, %42, %43, %44, %45, %46, %47, "
    "%48, %49, %50, %51, %52, %53, %54, %55, %56, %57, %58, %59, %60, %61, %62, %63, "
    "%64, %65, %66, %67, %68, %69, %70, %71, %72, %73, %74, %75, %76, %77, %78, %79, "
    "%80, %81, %82, %83, %84, %85, %86, %87, %88, %89, %90, %91, %92, %93, %94, %95}, "
    "dA, dB, p, 1, 1, 0, 1;\n}\n"
    : "=f"(d[0]), "=f"(d[1]), "=f"(d[2]), "=f"(d[3]), "=f"(d[4]), "=f"(d[5]), "=f"(d[6]), "=f"(d[7]),
      "=f"(d[8]), "=f"(d[9]), "=f"(d[10]), "=f"(d[11]), "=f"(d[12]), "=f"(d[13]), "=f"(d[14]), "=f"(d[15]),
      "=f"(d[16]), "=f"(d[17]), "=f"(d[18]), "=f"(d[19]), "=f"(d[20]), "=f"(d[21]), "=f"(d[22]), "=f"(d[23]),
      "=f"(d[24]), "=f"(d[25]), "=f"(d[26]), "=f"(d[27]), "=f"(d[28]), "=f"(d[29]), "=f"(d[30]), "=f"(d[31]),
      "=f"(d[32]), "=f"(d[33]), "=f"(d[34]), "=f"(d[35]), "=f"(d[36]), "=f"(d[37]), "=f"(d[38]), "=f"(d[39]),
      "=f"(d[40]), "=f"(d[41]), "=f"(d[42]), "=f"(d[43]), "=f"(d[44]), "=f"(d[45]), "=f"(d[46]), "=f"(d[47]),
      "=f"(d[48]), "=f"(d[49]), "=f"(d[50]), "=f"(d[51]), "=f"(d[52]), "=f"(d[53]), "=f"(d[54]), "=f"(d[55]),
      "=f"(d[56]), "=f"(d[57]), "=f"(d[58]), "=f"(d[59]), "=f"(d[60]), "=f"(d[61]), "=f"(d[62]), "=f"(d[63]),
      "=f"(d[64]), "=f"(d[65]), "=f"(d[66]), "=f"(d[67]), "=f"(d[68]), "=f"(d[69]), "=f"(d[70]), "=f"(d[71]),
      "=f"(d[72]), "=f"(d[73]), "=f"(d[74]), "=f"(d[75]), "=f"(d[76]), "=f"(d[77]), "=f"(d[78]), "=f"(d[79]),
      "=f"(d[80]), "=f"(d[81]), "=f"(d[82]), "=f"(d[83]), "=f"(d[84]), "=f"(d[85]), "=f"(d[86]), "=f"(d[87]),
      "=f"(d[88]), "=f"(d[89]), "=f"(d[90]), "=f"(d[91]), "=f"(d[92]), "=f"(d[93]), "=f"(d[94]), "=f"(d[95])
    : "r"(da), "r"(db), "n"(HA), "n"(HB));
}
template <uint32_t HA = 0x40000040u, uint32_t HB = 0x40000040u>
__device__ __forceinline__ void wg_ss128t(float* d, uint32_t da, uint32_t db, int scale_d) {
  asm volatile("{\n.reg .pred p;\n.reg .b64 dA, dB;\nmov.b64 dA, {%64, %67};\nmov.b64 dB, {%65, %68};\nsetp.ne.b32 p, %66, 0;\n"
    "wgmma.mma_async.sync.aligned.m64n128k16.f32.bf16.bf16 "
    "{%0, %1, %2, %3, %4, %5, %6, %7, %8, %9, %10, %11, %12, %13, %14, %15, "
    "%16, %17, %18, %19, %20, %21, %22, %23, %24, %25, %26, %27, %28, %29, %30, %31, "
    "%32, %33, %34, %35, %36, %37, %38, %39, %40, %41, %42, %43, %44, %45, %46, %47, "
    "%48, %49, %50, %51, %52, %53, %54, %55, %56, %57, %58, %59, %60, %61, %62, %63}, "
    "dA, dB, p, 1, 1, 0, 1;\n}\n"
    : "+f"(d[0]), "+f"(d[1]), "+f"(d[2]), "+f"(d[3]), "+f"(d[4]), "+f"(d[5]), "+f"(d[6]), "+f"(d[7]),
      "+f"(d[8]), "+f"(d[9]), "+f"(d[10]), "+f"(d[11]), "+f"(d[12]), "+f"(d[13]), "+f"(d[14]), "+f"(d[15]),
      "+f"(d[16]), "+f"(d[17]), "+f"(d[18]), "+f"(d[19]), "+f"(d[20]), "+f"(d[21]), "+f"(d[22]), "+f"(d[23]),
      "+f"(d[24]), "+f"(d[25]), "+f"(d[26]), "+f"(d[27]), "+f"(d[28]), "+f"(d[29]), "+f"(d[30]), "+f"(d[31]),
      "+f"(d[32]), "+f"(d[33]), "+f"(d[34]), "+f"(d[35]), "+f"(d[36]), "+f"(d[37]), "+f"(d[38]), "+f"(d[39]),
      "+f"(d[40]), "+f"(d[41]), "+f"(d[42]), "+f"(d[43]), "+f"(d[44]), "+f"(d[45]), "+f"(d[46]), "+f"(d[47]),
      "+f"(d[48]), "+f"(d[49]), "+f"(d[50]), "+f"(d[51]), "+f"(d[52]), "+f"(d[53]), "+f"(d[54]), "+f"(d[55]),
      "+f"(d[56]), "+f"(d[57]), "+f"(d[58]), "+f"(d[59]), "+f"(d[60]), "+f"(d[61]), "+f"(d[62]), "+f"(d[63])
    : "r"(da), "r"(db), "r"(scale_d), "n"(HA), "n"(HB));
}
template <uint32_t HB = 0x40000040u>
__device__ __forceinline__ void wg_rs64(float* d, uint32_t a0, uint32_t a1, uint32_t a2, uint32_t a3, uint32_t db, int scale_d) {
  asm volatile("{\n.reg .pred p;\n.reg .b64 dB;\nmov.b64 dB, {%36, %38};\nsetp.ne.b32 p, %37, 0;\n"
    "wgmma.mma_async.sync.aligned.m64n64k16.f32.bf16.bf16 "
    "{%0, %1, %2, %3, %4, %5, %6, %7, %8, %9, %10, %11, %12, %13, %14, %15, "
    "%16, %17, %18, %19, %20, %21, %22, %23, %24, %25, %26, %27, %28, %29, %30, %31}, "
    "{%32, %33, %34, %35}, dB, p, 1, 1, 0;\n}\n"
    : "+f"(d[0]), "+f"(d[1]), "+f"(d[2]), "+f"(d[3]), "+f"(d[4]), "+f"(d[5]), "+f"(d[6]), "+f"(d[7]),
      "+f"(d[8]), "+f"(d[9]), "+f"(d[10]), "+f"(d[11]), "+f"(d[12]), "+f"(d[13]), "+f"(d[14]), "+f"(d[15]),
      "+f"(d[16]), "+f"(d[17]), "+f"(d[18]), "+f"(d[19]), "+f"(d[20]), "+f"(d[21]), "+f"(d[22]), "+f"(d[23]),
      "+f"(d[24]), "+f"(d[25]), "+f"(d[26]), "+f"(d[27]), "+f"(d[28]), "+f"(d[29]), "+f"(d[30]), "+f"(d[31])
    : "r"(a0), "r"(a1), "r"(a2), "r"(a3), "r"(db), "r"(scale_d), "n"(HB));
}
template <uint32_t HB = 0x40000040u>
__device__ __forceinline__ void wg_rs64_z(float* d, uint32_t a0, uint32_t a1, uint32_t a2, uint32_t a3, uint32_t db) {
  asm volatile("{\n.reg .pred p;\n.reg .b64 dB;\nmov.b64 dB, {%36, %37};\nsetp.ne.b32 p, 0, 0;\n"
    "wgmma.mma_async.sync.aligned.m64n64k16.f32.bf16.bf16 "
    "{%0, %1, %2, %3, %4, %5, %6, %7, %8, %9, %10, %11, %12, %13, %14, %15, "
    "%16, %17, %18, %19, %20, %21, %22, %23, %24, %25, %26, %27, %28, %29, %30, %31}, "
    "{%32, %33, %34, %35}, dB, p, 1, 1, 0;\n}\n"
    : "=f"(d[0]), "=f"(d[1]), "=f"(d[2]), "=f"(d[3]), "=f"(d[4]), "=f"(d[5]), "=f"(d[6]), "=f"(d[7]),
      "=f"(d[8]), "=f"(d[9]), "=f"(d[10]), "=f"(d[11]), "=f"(d[12]), "=f"(d[13]), "=f"(d[14]), "=f"(d[15]),
      "=f"(d[16]), "=f"(d[17]), "=f"(d[18]), "=f"(d[19]), "=f"(d[20]), "=f"(d[21]), "=f"(d[22]), "=f"(d[23]),
      "=f"(d[24]), "=f"(d[25]), "=f"(d[26]), "=f"(d[27]), "=f"(d[28]), "=f"(d[29]), "=f"(d[30]), "=f"(d[31])
    : "r"(a0), "r"(a1), "r"(a2), "r"(a3), "r"(db), "n"(HB));
}
template <uint32_t HB = 0x40000040u>
__device__ __forceinline__ void wg_rs32(float* d, uint32_t a0, uint32_t a1, uint32_t a2, uint32_t a3, uint32_t db, int scale_d) {
  asm volatile("{\n.reg .pred p;\n.reg .b64 dB;\nmov.b64 dB, {%20, %22};\nsetp.ne.b32 p, %21, 0;\n"
    "wgmma.mma_async.sync.aligned.m64n32k16.f32.bf16.bf16 "
    "{%0, %1, %2, %3, %4, %5, %6, %7, %8, %9, %10, %11, %12, %13, %14, %15}, "
    "{%16, %17, %18, %19}, dB, p, 1, 1, 0;\n}\n"
    : "+f"(d[0]), "+f"(d[1]), "+f"(d[2]), "+f"(d[3]), "+f"(d[4]), "+f"(d[5]), "+f"(d[6]), "+f"(d[7]),
      "+f"(d[8]), "+f"(d[9]), "+f"(d[10]), "+f"(d[11]), "+f"(d[12]), "+f"(d[13]), "+f"(d[14]), "+f"(d[15])
    : "r"(a0), "r"(a1), "r"(a2), "r"(a3), "r"(db), "r"(scale_d), "n"(HB));
}
template <uint32_t HB = 0x40000040u>
__device__ __forceinline__ void wg_rs32_z(float* d, uint32_t a0, uint32_t a1, uint32_t a2, uint32_t a3, uint32_t db) {
  asm volatile("{\n.reg .pred p;\n.reg .b64 dB;\nmov.b64 dB, {%20, %21};\nsetp.ne.b32 p, 0, 0;\n"
    "wgmma.mma_async.sync.aligned.m64n32k16.f32.bf16.bf16 "
    "{%0, %1, %2, %3, %4, %5, %6, %7, %8, %9, %10, %11, %12, %13, %14, %15}, "
    "{%16, %17, %18, %19}, dB, p, 1, 1, 0;\n}\n"
    : "=f"(d[0]), "=f"(d[1]), "=f"(d[2]), "=f"(d[3]), "=f"(d[4]), "=f"(d[5]), "=f"(d[6]), "=f"(d[7]),
      "=f"(d[8]), "=f"(d[9]), "=f"(d[10]), "=f"(d[11]), "=f"(d[12]), "=f"(d[13]), "=f"(d[14]), "=f"(d[15])
    : "r"(a0), "r"(a1), "r"(a2), "r"(a3), "r"(db), "n"(HB));
}
template <uint32_t HB = 0x40000040u>
__device__ __forceinline__ void wg_rs40t(float* d, uint32_t a0, uint32_t a1, uint32_t a2, uint32_t a3, uint32_t db, int scale_d) {
  asm volatile("{\n.reg .pred p;\n.reg .b64 dB;\nmov.b64 dB, {%24, %26};\nsetp.ne.b32 p, %25, 0;\n"
    "wgmma.mma_async.sync.aligned.m64n40k16.f32.bf16.bf16 "
    "{%0, %1, %2, %3, %4, %5, %6, %7, %8, %9, %10, %11, %12, %13, %14, %15, "
    "%16, %17, %18, %19}, "
    "{%20, %21, %22, %23}, dB, p, 1, 1, 1;\n}\n"
    : "+f"(d[0]), "+f"(d[1]), "+f"(d[2]), "+f"(d[3]), "+f"(d[4]), "+f"(d[5]), "+f"(d[6]), "+f"(d[7]),
      "+f"(d[8]), "+f"(d[9]), "+f"(d[10]), "+f"(d[11]), "+f"(d[12]), "+f"(d[13]), "+f"(d[14]), "+f"(d[15]),
      "+f"(d[16]), "+f"(d[17]), "+f"(d[18]), "+f"(d[19])
    : "r"(a0), "r"(a1), "r"(a2), "r"(a3), "r"(db), "r"(scale_d), "n"(HB));
}
template <uint32_t HB = 0x40000040u>
__device__ __forceinline__ void wg_rs40t_z(float* d, uint32_t a0, uint32_t a1, uint32_t a2, uint32_t a3, uint32_t db) {
  asm volatile("{\n.reg .pred p;\n.reg .b64 dB;\nmov.b64 dB, {%24, %25};\nsetp.ne.b32 p, 0, 0;\n"
    "wgmma.mma_async.sync.aligned.m64n40k16.f32.bf16.bf16 "
    "{%0, %1, %2, %3, %4, %5, %6, %7, %8, %9, %10, %11, %12, %13, %14, %15, "
    "%16, %17, %18, %19}, "
    "{%20, %21, %22, %23}, dB, p, 1, 1, 1;\n}\n"
    : "=f"(d[0]), "=f"(d[1]), "=f"(d[2]), "=f"(d[3]), "=f"(d[4]), "=f"(d[5]), "=f"(d[6]), "=f"(d[7]),
      "=f"(d[8]), "=f"(d[9]), "=f"(d[10]), "=f"(d[11]), "=f"(d[12]), "=f"(d[13]), "=f"(d[14]), "=f"(d[15]),
      "=f"(d[16]), "=f"(d[17]), "=f"(d[18]), "=f"(d[19])
    : "r"(a0), "r"(a1), "r"(a2), "r"(a3), "r"(db), "n"(HB));
}

constexpr uint32_t SOFF = 1024;
constexpr int STG = 57344, SL_W = 32768, SL_HD = 12288, SL_F = 3 * STG, AT_ST = 131072;
constexpr int OFF_ONES = 4 * STG;
constexpr int OFF_PATCH = OFF_ONES + 1024;
constexpr int OFF_CS = OFF_PATCH + 768;
constexpr int OFF_BAR = OFF_CS + 768;
constexpr int OFF_MISC = OFF_BAR + 384;
constexpr int SMEM_BYTES = OFF_MISC + 128;
enum { B_FULL = 0, B_EMPTY = 3, B_HALO = 6, B_CS = 9, B_KVREADY, B_QDONE = B_KVREADY + 2, B_QREADY, B_OST, B_ADONE = B_OST + 2,
       B_QFREE, B_WS, B_WFULL, B_WEMPTY = B_WFULL + 4, B_GU = B_WEMPTY + 4, B_RES = B_GU + 2, B_DN,
       B_HX = B_DN + 2, B_RST, B_WGO, B_UNIT = B_WGO + 2, B_COUNT = B_UNIT + 8 };
static_assert(B_COUNT <= 48, "barrier area");
__host__ __device__ constexpr int bar_count(int i) {
  return i >= B_EMPTY && i < B_HALO ? 17 : i == B_CS ? 4 : i == B_QFREE ? 16
       : i == B_KVREADY || i == B_KVREADY + 1 || i == B_QREADY ? 8 : i == B_ADONE ? 32 : i == B_OST ? 2 : i >= B_UNIT ? 4
       : i == B_QDONE || (i >= B_WEMPTY && i < B_GU) ? 16 : i == B_RST ? 4 : i == B_RES ? 2 : 1;
}
enum { M_KEY = 0, M_MEAN, M_INV, M_WSUM, M_TAG, M_SEL0, M_PMEAN, M_PINV, M_XQ = 8, M_KEYS = 12, M_PROG = 20 };
constexpr int FFN_PIECE = 14336;
constexpr int T_XS = 163840, T_HP = T_XS + 1024;
constexpr int HELP_GR = 8;
constexpr float LSUM_MIN = 5.421010862427522e-20f, LSUM_MAX = 1.8446744073709552e19f;
constexpr float SM_C = 0.17677669529663687f * 1.4426950408889634f;
constexpr uint32_t VSTEP = 64u - (64u << 16);
#define FFN_POL policy_evict_first()
#define D_SPLIT 1
#define GUA_AT 2
#define GUB_PACE 800
#define HOLD_K 0
#define PROG 1
#define ULIST1 0x854
#define ULIST2 0x8721
#define RES_K 3
#define REL_NOW 0
#define FAKE 0
#define X_STAGGER 500
#define GU_PACE1 2000
#define GU_PACE 2500
#define DELAY_P 600
#define DELAY_S 2000
#define DELAY_Y 700

struct Params {
  CUtensorMap mapA[2], mapW, mapWo, mapRes[2], mapXst[2], mapG, mapU, mapD;
  const bf16 *x, *wqkv, *wo, *w_r, *w_g, *w_u, *w_d;
  bf16* out;
  int helper_first;
};

template <int N> __device__ __forceinline__ void exp_pack(const float* s, uint32_t* p) {
#pragma unroll
  for (int b = 0; b < N; b++) {
    p[2 * b] = pack_bf16(ex2(s[4 * b]), ex2(s[4 * b + 1]));
    p[2 * b + 1] = pack_bf16(ex2(s[4 * b + 2]), ex2(s[4 * b + 3]));
  }
}
template <int KIND> __device__ __forceinline__ void edge16(const float* sd, const float* st, uint32_t* pd, uint32_t* pt, int dl, uint32_t mt) {
  if (KIND == 0) { exp_pack<2>(sd, pd); pt[0] = pt[1] = pt[2] = pt[3] = 0; }
  else if (KIND == 1) { exp_pack<2>(st, pt); pd[0] = pd[1] = pd[2] = pd[3] = 0; }
  else {
    const uint32_t a = pack_bf16(ex2(dl >= 0 ? sd[0] : st[0]), ex2(dl >= 1 ? sd[1] : st[1]));
    const uint32_t c = pack_bf16(ex2(dl >= 0 ? sd[6] : st[6]), ex2(dl >= 1 ? sd[7] : st[7]));
    pd[0] = a & ~mt; pt[0] = a & mt; pd[3] = c & ~mt; pt[3] = c & mt;
    pd[1] = pack_bf16(ex2(sd[2]), ex2(sd[3])); pt[1] = 0;
    pt[2] = pack_bf16(ex2(st[4]), ex2(st[5])); pd[2] = 0;
  }
}
__device__ __forceinline__ void edge32(const float* sd, const float* st, uint32_t* pd, uint32_t* pt, int rel, int dl, uint32_t mt) {
  if (rel > 1) { edge16<0>(sd, st, pd, pt, dl, mt); edge16<0>(sd + 8, st + 8, pd + 4, pt + 4, dl, mt); }
  else if (rel == 1) { edge16<0>(sd, st, pd, pt, dl, mt); edge16<2>(sd + 8, st + 8, pd + 4, pt + 4, dl, mt); }
  else if (rel == 0) { edge16<2>(sd, st, pd, pt, dl, mt); edge16<1>(sd + 8, st + 8, pd + 4, pt + 4, dl, mt); }
  else { edge16<1>(sd, st, pd, pt, dl, mt); edge16<1>(sd + 8, st + 8, pd + 4, pt + 4, dl, mt); }
}
__device__ __forceinline__ void qk64(float* s, const uint32_t* qf, uint32_t kd) {
  wg_rs64_z<H64>(s, qf[0], qf[1], qf[2], qf[3], kd);
  wg_rs64<H64>(s, qf[4], qf[5], qf[6], qf[7], kd + 2, 1);
}
__device__ __forceinline__ void qk32x2(float* a, float* b, const uint32_t* qf, uint32_t ka, uint32_t kb) {
  wg_rs32_z<H64>(a, qf[0], qf[1], qf[2], qf[3], ka); wg_rs32_z<H64>(b, qf[0], qf[1], qf[2], qf[3], kb);
  wg_rs32<H64>(a, qf[4], qf[5], qf[6], qf[7], ka + 2, 1); wg_rs32<H64>(b, qf[4], qf[5], qf[6], qf[7], kb + 2, 1);
}
__device__ __forceinline__ void pv32(float* o, const uint32_t* p, uint32_t vd) {
  wg_rs40t<H64>(o, p[0], p[1], p[2], p[3], vd, 1);
  wg_rs40t<H64>(o, p[4], p[5], p[6], p[7], vd + VSTEP, 1);
}

__device__ __forceinline__ void fma8(float* d, uint4 w, float x) {
  d[0] += x * bf_lo(w.x); d[1] += x * bf_hi(w.x); d[2] += x * bf_lo(w.y); d[3] += x * bf_hi(w.y);
  d[4] += x * bf_lo(w.z); d[5] += x * bf_hi(w.z); d[6] += x * bf_lo(w.w); d[7] += x * bf_hi(w.w);
}

__device__ __forceinline__ int fresh_tid() { int r; asm volatile("mov.u32 %0, %%tid.x;" : "=r"(r)); return r; }
__device__ __forceinline__ int fresh_bid() { int r; asm volatile("mov.u32 %0, %%ctaid.x;" : "=r"(r)); return r; }
#define PHASE_IDS                                                                                                              \
  const uint32_t sbase = smem_u32(smem);                                                                                       \
  const int tid = fresh_tid(), bid = fresh_bid();                                                                              \
  const int warp = __shfl_sync(0xffffffffu, tid >> 5, 0), lane = tid & 31;                                                     \
  const int rank = bid & 1, cl = bid >> 1, rb = bid & 7, hp = bid >> 3;                  \
  const int mb = 2 * rb + (hp >> 3), nb = hp & 7;                                            \
  const int wg = warp >> 2, wi = warp & 3, g = lane >> 2, q = lane & 3;                                                        \
  const int mi = lane >> 3, srow = wi * 16 + (mi & 1) * 8 + (lane & 7);      \
  auto bar = [&](int i) { return sbase + OFF_BAR + 8 * i; };                                                                   \
  volatile uint32_t* s_misc = (volatile uint32_t*)(smem + OFF_MISC);                                                           \
  auto load_w = [&](int s, int kt) {                           \
    tma_load3_mc(sbase + s * STG + SL_W + rank * SL_HD, &P.mapW, hp * 64, kt * 64 + rank * 32, 0, bar(B_FULL + s));            \
  };                                                                                                                           \
  auto load_a = [&](int s, int kt, int layer) { mbar_expect_tx(bar(B_FULL + s), STG); tma_load2(sbase + s * STG, &P.mapA[layer], kt * 64, rb * 256, bar(B_FULL + s)); }; \
  auto load_wo = [&](int k) {                                                 \
    mbar_expect_tx(bar(B_WFULL + (k & 3)), 32768);                                                                             \
    tma_load3_mc(sbase + (k & 3) * 32768 + 16384 + rank * 8192, &P.mapWo, nb * 128 + rank * 64, (k >> 3) * 32, (k & 7) * 2, bar(B_WFULL + (k & 3))); \
  };                                                                                                                           \
  auto load_o = [&](int k) {                                                            \
    bulk_load(sbase + (k & 3) * 32768, g_o + (size_t)(mb * 16 + k) * 16384, 16384, bar(B_WFULL + (k & 3)));                    \
  };                                                                                                                           \
  auto import_halo = [&](int layer, int h) {                                   \
    poll_flag(&g_kvflag[(rb - 1) >> 1][hp][h].v[layer], s_misc[M_TAG]);                                                        \
    fence_async_global();                                                                                                      \
    const uint8_t* src = g_kv + (size_t)(((rb - 1) >> 1) * 16 + hp) * 65536 + h * 32768;                                       \
    mbar_expect_tx(bar(B_HALO + 2 * h), 16384 << h);                                                                           \
    bulk_load_h(sbase + (h ? 65536 : 16384), src + (h ? 0 : 16384), 16384 << h, bar(B_HALO + 2 * h), policy_evict_first());    \
    if (h == 0) { mbar_expect_tx(bar(B_HALO + 1), 16384); bulk_load_h(sbase, src, 16384, bar(B_HALO + 1), policy_evict_first()); } \
  };                                                                                                                           \
  auto load_res = [&](int half, int layer) {                                                  \
    mbar_expect_tx(bar(B_RES), 16384);                                                                                         \
    tma_load2(sbase + AT_ST + half * 16384, &P.mapRes[layer], nb * 128, mb * 128 + half * 64, bar(B_RES));                     \
    tma_load2(sbase + AT_ST + half * 16384 + 8192, &P.mapRes[layer], nb * 128 + 64, mb * 128 + half * 64, bar(B_RES));         \
  };                                                                                                                           \
  auto store_tile = [&](int layer, int skip, bool wait) {                                           \
    _Pragma("unroll 1")                                                                                                        \
    for (int j = 0; j < 4; j++)                                                                                                \
      if ((j & 1) != skip) tma_store(&P.mapXst[layer], sbase + AT_ST + (j & 1) * 16384 + (j >> 1) * 8192, nb * 128 + (j >> 1) * 64, mb * 128 + (j & 1) * 64); \
    bulk_commit();                                                                                                             \
    if (wait) bulk_wait_all();                                                                                                 \
  };                                                                                                                           \
  auto load_gu = [&](int half, int pace) {                             \
    mbar_expect_tx(bar(B_GU + half), 4 * FFN_PIECE);                                                                           \
    _Pragma("unroll 1")                                                                                                        \
    for (int j = 0; j < 4; j++) {                                                                                              \
      tma_load2_h(sbase + SL_F + j * FFN_PIECE, &P.mapG + (j >> 1), cl * 56, rank * 512 + half * 256 + (j & 1) * 128, bar(B_GU + half), FFN_POL); \
      if (j < 3) spin_cycles(pace);                                                                                            \
    }                                                                                                                          \
  };                                                                                                                           \
  auto fetch_gu = [&](uint32_t* a, int ks, int ct) {                 \
    ldsm_x4_t(sbase + SL_F + (mi & 1) * 2 * FFN_PIECE + (ks * 16 + (mi >> 1) * 8 + (lane & 7)) * 112 + ct * 16, a[0], a[1], a[2], a[3]); \
  };                                                                                                                           \
  auto send_gu = [&](float gate, float up, int ct, int part) {        \
    const int u = 8 * ct + g, own = u >= 28;                                                                                   \
    if (q == 0) st_async2(mapa(sbase + T_HP + ((rank * 5 + part) * 28 + u - 28 * own) * 8, own), gate, up, mapa(bar(B_HX), own)); \
  };                                                                                                                           \
  auto hidden = [&]() {                                     \
    const float2* hpart = (const float2*)(smem + T_HP) + min(lane, 27);                                                        \
    float gs[2] = {0.f, 0.f}, us[2] = {0.f, 0.f};                                                                              \
    _Pragma("unroll")                                                                                                          \
    for (int j = 0; j < 10; j++) { const float2 v = hpart[j * 28]; gs[j & 1] += v.x; us[j & 1] += v.y; }                       \
    const float gb = rbf(gs[0] + gs[1]), ub = rbf(us[0] + us[1]);                                                              \
    return lane < 28 ? rbf(__fdividef(gb, 1.f + __expf(-gb))) * ub : 0.f;                                                      \
  };                                                                                                                           \
  (void)load_wo; (void)load_o; (void)import_halo; (void)load_res; (void)store_tile; (void)fetch_gu; (void)load_gu; (void)send_gu; (void)hidden; (void)cl; (void)mb; (void)nb; (void)wg; (void)g; (void)q; (void)srow; (void)s_misc; (void)load_w; (void)load_a;

__global__ void __launch_bounds__(512, 1) mega_kernel(const __grid_constant__ Params P) {
  extern __shared__ __align__(1024) uint8_t smem[];
  if ((int)blockIdx.x < P.helper_first) {
    PHASE_IDS
    if (warp == 0) {
      if (lane == 0) {
        prefetch_tmap(&P.mapA[0]); prefetch_tmap(&P.mapW);
#pragma unroll
        for (int i = 0; i < 3; i++) mbar_init(bar(B_FULL + i), 1);
        asm volatile("fence.mbarrier_init.release.cluster;" ::: "memory");
      }
      __syncwarp();
      load_a(0, 0, 0);
    } else if (tid == 32) {
#pragma unroll
      for (int i = 3; i < B_COUNT; i++) mbar_init(bar(i), bar_count(i));
      asm volatile("fence.mbarrier_init.release.cluster;" ::: "memory");
    } else if (warp == 8) {
      ((uint4*)(smem + OFF_ONES))[lane] = make_uint4(0x3F803F80u, 0x3F803F80u, 0x3F803F80u, 0x3F803F80u);
      ((uint4*)(smem + OFF_ONES))[lane + 32] = make_uint4(0x3F803F80u, 0x3F803F80u, 0x3F803F80u, 0x3F803F80u);
    }
    __syncwarp();
    cluster_arrive(); cluster_wait();
    if (warp == 0) {
#pragma unroll 1
      for (int i = 0; i < 3; i++) { load_w(i, i); if (i) load_a(i, i, 0); }
      PROFL(0, 1);
    } else if (warp == 1) {
      if (lane < 16) g_rowab[0][rb * 256 + hp * 16 + lane] = make_uint4(0, 0, 0, 0);
    } else if (warp == 2) {
      const int f = lane >> 1;
      Flag* fl = f < 2 ? &g_kvflag[rb >> 1][hp][f] : f < 4 ? &g_oflag[rb][f & 1][hp] : &g_xflag[mb][nb];
      if (f < 5 && (f >= 2 || (rank == 1 && rb < 7))) ((uint4*)fl)[lane & 1] = make_uint4(0, 0, 0, 0);
    } else if (tid == 96) {
      if ((sbase & 0x3FFFF) != SOFF) __trap();
#pragma unroll 1
      for (int i = 1; i < 11; i++) prefetch_tmap(&P.mapA[0] + i);
    }
    __syncwarp();
  } else {
    const uint32_t sbase = smem_u32(smem);
    const int tid = threadIdx.x, warp = __shfl_sync(0xffffffffu, tid >> 5, 0), lane = tid & 31;
    const int hid = blockIdx.x - P.helper_first;
    constexpr int GR = HELP_GR, NG = 36 / GR, GB = GR * 6144, NGRP = 256 / GR;
    const uint32_t hfull = sbase + NG * GB, hempty = hfull + 8 * NG;
    if (tid == 0) {
      for (int i = 0; i < NG; i++) { mbar_init(hfull + 8 * i, 1); mbar_init(hempty + 8 * i, 12); }
      asm volatile("fence.mbarrier_init.release.cluster;" ::: "memory");
    }
    __syncthreads();
    const uint8_t* wsrc = (const uint8_t*)P.wqkv + (size_t)hid * 256 * 6144;
    if (warp == 12) {
#pragma unroll 1
      for (int gI = 0; gI < NGRP; gI++) {
        const int sl = gI % NG;
        if (gI >= NG) mbar_wait(hempty + 8 * sl, ((gI / NG) & 1) ^ 1);
        mbar_expect_tx(hfull + 8 * sl, GB);
        bulk_load(sbase + sl * GB, wsrc + (size_t)gI * GB, GB, hfull + 8 * sl);
      }
    } else if (warp < 12) {
      float cs8[8] = {0, 0, 0, 0, 0, 0, 0, 0};
#pragma unroll 1
      for (int gI = 0; gI < NGRP; gI++) {
        const int sl = gI % NG;
        mbar_wait(hfull + 8 * sl, (gI / NG) & 1);
#pragma unroll
        for (int i = 0; i < GR; i++) {
          const uint4 v = *(const uint4*)(smem + sl * GB + i * 6144 + tid * 16);
          cs8[0] += bf_lo(v.x); cs8[1] += bf_hi(v.x); cs8[2] += bf_lo(v.y); cs8[3] += bf_hi(v.y);
          cs8[4] += bf_lo(v.z); cs8[5] += bf_hi(v.z); cs8[6] += bf_lo(v.w); cs8[7] += bf_hi(v.w);
        }
        __syncwarp();
        if (lane == 0) mbar_arrive(hempty + 8 * sl);
      }
      uint4* dst = (uint4*)&g_cspart[hid][tid * 8];
      st_relaxed4(dst, make_uint4(enc(cs8[0]), enc(cs8[1]), enc(cs8[2]), enc(cs8[3])));
      st_relaxed4(dst + 1, make_uint4(enc(cs8[4]), enc(cs8[5]), enc(cs8[6]), enc(cs8[7])));
    }
    return;
  }

  regs_dec<120>();
#pragma unroll 1
  for (unsigned pass_v = 0;;) {
    const unsigned pass = __shfl_sync(0xffffffffu, pass_v, 0);
    if (__shfl_sync(0xffffffffu, fresh_tid() >> 8, 0)) {
      if (pass > 0) {
        const unsigned layer = pass - 1;
        uint32_t xr[32];
        {
          PHASE_IDS
          float acc[64];
#pragma unroll
          for (int i = 0; i < 64; i++) acc[i] = 0.f;
          const uint32_t da0 = dlo(SOFF, 16) + (wg - 2) * 256;
          constexpr uint32_t db0 = dlo(SOFF + 16384, 8192);
#pragma unroll 1
          for (int k4 = 0; k4 < 4; k4++) {
#pragma unroll
            for (int st = 0; st < 4; st++) {
              mbar_wait(bar(B_WFULL + st), k4 & 1);
              wg_fence();
#pragma unroll
              for (int kk = 0; kk < 4; kk++)
                wg_ss128t<H64, H128>(acc, da0 + ((st * 32768) >> 4) + (kk >> 1) * 512 + (kk & 1) * 2, db0 + ((st * 32768) >> 4) + kk * 128, 1);
              wg_commit();
              if (st == 0 && k4 == 0 && warp == 9) PROF(10);
              if (warp == 9) STEPT(16 + k4 * 4 + st);
              if (REL_NOW) {
                if (st < 3 || k4 < 3) wg_wait<0>();
                if (lane < 2 && (st < 2 || k4 < 3)) mbar_arrive_cluster(bar(B_WEMPTY + st), lane);
              } else {
                wg_wait<1>();
                if (lane < 2 && (st == 0 ? k4 > 0 : (st < 3 || k4 < 3))) mbar_arrive_cluster(bar(B_WEMPTY + ((st + 3) & 3)), lane);
              }
            }
          }
          mbar_wait(bar(B_RES), layer);
          mbar_wait(bar(B_RST), layer);
          const uint32_t zoff = AT_ST + (wg - 2) * 16384;
#pragma unroll
          for (int j = 0; j < 8; j++)
            ldsm_x4(sbase + zoff + srow * 128 + (j >> 2) * 8192 + ((((2 * j + (mi >> 1)) & 7) ^ (srow & 7)) << 4), xr[4 * j], xr[4 * j + 1], xr[4 * j + 2], xr[4 * j + 3]);
          wg_wait<0>();
          fence_regs<64>(acc);
          if (warp == 9) PROF(11);
          if (layer == 0 && lane < 2) mbar_arrive_cluster(bar(B_QFREE), lane);
#pragma unroll
          for (int j = 0; j < 32; j++) xr[j] = hadd_bf2(xr[j], pack_bf16(acc[2 * j], acc[2 * j + 1]));
        }
        PHASE_IDS
        const uint32_t tag = s_misc[M_TAG];
        const int grow = mb * 128 + (warp - 8) * 16 + g;
        {
          float d[6][4];
#pragma unroll
          for (int i = 0; i < 6; i++) d[i][0] = d[i][1] = d[i][2] = d[i][3] = 0.f;
          const uint4* tab = (const uint4*)(smem + OFF_PATCH + (g == 1 ? q * 64 : (g == 0 ? 256 : 320)));
#pragma unroll
          for (int j2 = 0; j2 < 4; j2++) {
            const uint4 w = tab[j2];
#pragma unroll
            for (int jj = 0; jj < 2; jj++) {
              const uint32_t* a = &xr[8 * j2 + 4 * jj];
              mma_16816(d[jj], a[0], a[1], a[2], a[3], jj ? w.z : w.x, jj ? w.w : w.y);
              mma_16816(d[2 + jj], a[0], a[1], a[2], a[3], a[0], a[2]);
              mma_16816(d[4 + jj], a[0], a[1], a[2], a[3], a[1], a[3]);
            }
          }
          const float sq0 = __shfl_sync(0xffffffffu, (g & 1) ? d[2][1] + d[3][1] : d[2][0] + d[3][0], g * 4 + (g >> 1));
          const float sq1 = __shfl_sync(0xffffffffu, (g & 1) ? d[4][3] + d[5][3] : d[4][2] + d[5][2], g * 4 + (g >> 1));
          uint4* dst = &g_part[layer][nb * SEQ + grow];
          if (q == 0) {
            st_relaxed4(dst, make_uint4(__float_as_uint(d[0][0] + d[1][0]), __float_as_uint(sq0), __float_as_uint(d[0][1] + d[1][1]), tag));
            st_relaxed4(dst + 8, make_uint4(__float_as_uint(d[0][2] + d[1][2]), __float_as_uint(sq1), __float_as_uint(d[0][3] + d[1][3]), tag));
          }
        }
        if (warp == 9) PROF(12);
        asm volatile("bar.arrive 6, 320;" ::: "memory");
        const int t_p = (int)clock();
        const uint32_t zrow = sbase + AT_ST + (wg - 2) * 16384 + srow * 128;
        if (layer == 0) {
#pragma unroll
          for (int j = 0; j < 8; j++)
            stsm_x4(zrow + (j >> 2) * 8192 + ((((2 * j + (mi >> 1)) & 7) ^ (srow & 7)) << 4), xr[4 * j], xr[4 * j + 1], xr[4 * j + 2], xr[4 * j + 3]);
          fence_async_smem();
          asm volatile("bar.arrive 8, 288;" ::: "memory");
        }
#pragma unroll 1
        while ((int)clock() - t_p < DELAY_P) {}
        {
          const uint4* src = &g_part[layer][2 * q * SEQ + grow];
          uint4 pp[4];
          uint32_t spins = 0;
#pragma unroll 1
          do {
            pp[0] = ld_relaxed4(src); pp[1] = ld_relaxed4(src + SEQ); pp[2] = ld_relaxed4(src + 8); pp[3] = ld_relaxed4(src + SEQ + 8);
          } while (!__all_sync(0xffffffffu, pp[0].w == tag && pp[1].w == tag && pp[2].w == tag && pp[3].w == tag) && ++spins < SPIN_LIMIT);
          if (warp == 9) PROF(13);
          const int rr = q >> 1;
          float s3[3];
#pragma unroll
          for (int c = 0; c < 3; c++) {
            const float lo = __uint_as_float(c == 0 ? pp[0].x : c == 1 ? pp[0].y : pp[0].z) + __uint_as_float(c == 0 ? pp[1].x : c == 1 ? pp[1].y : pp[1].z);
            const float hi = __uint_as_float(c == 0 ? pp[2].x : c == 1 ? pp[2].y : pp[2].z) + __uint_as_float(c == 0 ? pp[3].x : c == 1 ? pp[3].y : pp[3].z);
            s3[c] = (rr ? hi : lo) + __shfl_xor_sync(0xffffffffu, rr ? lo : hi, 2);
            s3[c] += __shfl_xor_sync(0xffffffffu, s3[c], 1);
          }
          const float mu = s3[0] * (1.f / DM), var = fmaxf(fmaf(-mu, mu, s3[1] * (1.f / DM)), 0.f);
          const float mn = rbf(mu), iv = ln_inv(var);
          const uint32_t ky = router_key(rbf((s3[2] - mn * __uint_as_float(s_misc[M_WSUM])) * iv), grow + 8 * rr);
          const uint32_t wbest = __reduce_max_sync(0xffffffffu, ky);
          s_misc[M_KEYS + warp - 8] = wbest;
          named_bar(5, 256);
          if (__reduce_max_sync(0xffffffffu, s_misc[M_KEYS + (lane & 7)]) == wbest) {
            if (nb == 0 && ky == wbest && (q & 1) == 0) st_relaxed4(&g_slot[layer][mb * 8], make_uint4(ky, __float_as_uint(mn), __float_as_uint(iv), tag));
            const int r = ~wbest & 15;
            if ((r & 7) == g) {
#pragma unroll
              for (int j = 0; j < 4; j++) {
                const uint32_t* a = &xr[8 * j];
                st_relaxed4(&g_cand[layer][mb * 128 + nb * 16 + q * 4 + j],
                            r < 8 ? make_uint4(nosent(a[0]), nosent(a[2]), nosent(a[4]), nosent(a[6])) : make_uint4(nosent(a[1]), nosent(a[3]), nosent(a[5]), nosent(a[7])));
              }
            }
            __syncwarp();
          }
          if (warp == 9) PROF(14);
          if (layer == 0) {
            if ((q & 1) == 0) {
              g_rowln[nb][grow + 8 * rr] = make_float2(mn, iv);
              if (warp - 8 == nb) {
                const float mu2 = mu + (mu - mn) * iv, inv2 = ln_inv(var * (1.f + iv) * (1.f + iv));
                st_relaxed4(&g_rowab[1][grow + 8 * rr], make_uint4(__float_as_uint((1.f + iv) * inv2), __float_as_uint((mn * iv + rbf(mu2)) * inv2), tag, 0));
              }
            }
            __syncwarp();
          } else {
            const float mo = __shfl_xor_sync(0xffffffffu, mn, 2), io = __shfl_xor_sync(0xffffffffu, iv, 2);
            const uint32_t m0 = pack_bf16(rr ? mo : mn, rr ? mo : mn), m1 = pack_bf16(rr ? mn : mo, rr ? mn : mo);
            const float i0 = rr ? io : iv, i1 = rr ? iv : io;
#pragma unroll
            for (int j = 0; j < 8; j++)
              stsm_x4(zrow + (j >> 2) * 8192 + ((((2 * j + (mi >> 1)) & 7) ^ (srow & 7)) << 4), add_ln_pair(xr[4 * j], m0, i0),
                      add_ln_pair(xr[4 * j + 1], m1, i1), add_ln_pair(xr[4 * j + 2], m0, i0), add_ln_pair(xr[4 * j + 3], m1, i1));
            fence_async_smem();
          }
          if (warp == 15) asm volatile("bar.arrive 7, 512;" ::: "memory");
        }
        if (warp < 15) {
          uint32_t gu[64];
          mbar_wait(bar(B_GU + 1), layer);
#pragma unroll
          for (int j = 0; j < 16; j++) fetch_gu(gu + 4 * j, j, warp - 8);
          fence_async_smem();
          float d[4][4] = {};
          named_bar(7, 512);
#pragma unroll
          for (int hf = 0; hf < 2; hf++) {
            uint4 xv[4] = {};
            if (g == 0) {
#pragma unroll
              for (int j = 0; j < 4; j++) xv[j] = ((const uint4*)(smem + T_XS))[32 + hf * 16 + j * 4 + q];
            }
            __syncwarp();
#pragma unroll
            for (int j = 0; j < 4; j++) {
              const uint32_t* a = gu + hf * 32 + j * 8;
              mma_16816(d[(j & 1) * 2], a[0], a[1], a[2], a[3], xv[j].x, xv[j].y);
              mma_16816(d[(j & 1) * 2 + 1], a[4], a[5], a[6], a[7], xv[j].z, xv[j].w);
            }
          }
          send_gu((d[0][0] + d[1][0]) + (d[2][0] + d[3][0]), (d[0][2] + d[1][2]) + (d[2][2] + d[3][2]), warp - 8, 4);
          __syncwarp();
        }
        if (layer == 0) asm volatile("bar.arrive 9, 512;" ::: "memory");
        else {
        uint32_t wd[64];
        mbar_wait(bar(B_DN), layer);
#pragma unroll
        for (int j = 0; j < 16; j++) {
          const uint32_t row = sbase + ((warp - 8) * 2 + (j >> 3)) * 3584 + min((j & 1) * 16 + (mi >> 1) * 8 + (lane & 7), 27) * 128;
          ldsm_x4_t(row + ((((j & 6) + (mi & 1)) ^ ((row >> 7) & 7)) << 4), wd[4 * j], wd[4 * j + 1], wd[4 * j + 2], wd[4 * j + 3]);
        }
        fence_regs_u<64>(wd);
        mbar_wait_cluster(bar(B_HX), layer);
        uint32_t hf[4];
        {
          const float hv = hidden();
          const uint32_t hp2 = pack_bf16(hv, __shfl_down_sync(0xffffffffu, hv, 1));
#pragma unroll
          for (int j = 0; j < 4; j++) hf[j] = __shfl_sync(0xffffffffu, hp2, 8 * j + 2 * q);
        }
        if (warp == 9) PROF(19);
        float y[4][4] = {};
#pragma unroll
        for (int j = 0; j < 16; j++)
          mma_16816(y[j & 3], wd[4 * j], wd[4 * j + 1], wd[4 * j + 2], wd[4 * j + 3], g == j >> 1 ? hf[(j & 1) * 2] : 0u, g == j >> 1 ? hf[(j & 1) * 2 + 1] : 0u);
        {
          float e[4];
#pragma unroll
          for (int c = 0; c < 4; c++) { const int i = (c & 1) * 2 + (c >> 1); e[c] = (y[0][i] + y[1][i]) + (y[2][i] + y[3][i]); }
          const bool b0 = g & 1, b1 = g & 2;
          float t0 = __shfl_xor_sync(0xffffffffu, b0 ? e[0] : e[1], 4), t1 = __shfl_xor_sync(0xffffffffu, b0 ? e[2] : e[3], 4);
          const float f0 = b0 ? t0 : e[0], f1 = b0 ? e[1] : t0, f2 = b0 ? t1 : e[2], f3 = b0 ? e[3] : t1;
          t0 = __shfl_xor_sync(0xffffffffu, b1 ? f0 : f2, 8); t1 = __shfl_xor_sync(0xffffffffu, b1 ? f1 : f3, 8);
          st_relaxed4(&g_ypart[layer][bid * 256 + (warp - 8) * 32 + (q * 4 + (g & 3)) * 2 + (g >> 2)],
                      b1 ? make_uint4(f2u(t0), f2u(t1), f2u(f2), f2u(f3)) : make_uint4(f2u(f0), f2u(f1), f2u(t0), f2u(t1)));
        }
        if (warp == 9) PROF(20);
        asm volatile("bar.arrive 9, 384;" ::: "memory");
        cluster_arrive(); cluster_wait();
        return;
        }
      }
      const unsigned layer = pass;
      named_bar(1 + (fresh_tid() >> 7), 128);
      regs_inc<224>();
      float acc[2][96];
      {
        PHASE_IDS
        const uint32_t da0 = dlo(SOFF, 16) + (wg - 2) * 512;
        constexpr uint32_t db0 = dlo(SOFF + SL_W, 4096);
        mbar_wait(bar(B_FULL), 0);
        if (warp == 9) PROF(29);
        if (warp == 9) STEPT(0);
        wg_fence();
        wg_ss192t_z(acc[0], da0, db0); wg_ss192t_z(acc[1], da0 + 1024, db0);
#pragma unroll
        for (int kk = 1; kk < 4; kk++) {
          wg_ss192t(acc[0], da0 + kk * 2, db0 + (kk >> 1) * (SL_HD >> 4) + (kk & 1) * 128, 1);
          wg_ss192t(acc[1], da0 + 1024 + kk * 2, db0 + (kk >> 1) * (SL_HD >> 4) + (kk & 1) * 128, 1);
        }
        wg_commit();
        int s = 1, u = 0;
#pragma unroll 1
        for (int i = 1; i < 16; i++) {
          const uint32_t da = da0 + s * (STG >> 4), db = db0 + s * (STG >> 4);
          mbar_wait(bar(B_FULL + s), (u + (s ? layer : 0)) & 1);
          if (warp == 9) STEPT(i);
          wg_fence();
#pragma unroll
          for (int kk = 0; kk < 4; kk++) {
            wg_ss192t(acc[0], da + kk * 2, db + (kk >> 1) * (SL_HD >> 4) + (kk & 1) * 128, 1);
            wg_ss192t(acc[1], da + 1024 + kk * 2, db + (kk >> 1) * (SL_HD >> 4) + (kk & 1) * 128, 1);
          }
          wg_commit();
          wg_wait<1>();
          if (lane < 2 && i < 14) mbar_arrive_cluster(bar(B_EMPTY + (s == 0 ? 2 : s - 1)), lane);
          if (++s == 3) { s = 0; u++; }
        }
      }
      PHASE_IDS
      mbar_wait(bar(B_CS), layer);
      float pa[2][2], pb[2][2];
      {
        const uint32_t tag = s_misc[M_TAG];
        const uint4* src = &g_rowab[layer][rb * 256 + (wg - 2 + (lane >> 4) * 2) * 64 + wi * 16 + (lane & 15)];
        uint4 v;
        uint32_t spins = 0;
#pragma unroll 1
        do { v = ld_relaxed4(src); } while (!__all_sync(0xffffffffu, v.z == tag) && ++spins < SPIN_LIMIT);
#pragma unroll
        for (int j = 0; j < 4; j++) {
          pa[j >> 1][j & 1] = __uint_as_float(__shfl_sync(0xffffffffu, v.x, g + 8 * j));
          pb[j >> 1][j & 1] = __uint_as_float(__shfl_sync(0xffffffffu, v.y, g + 8 * j));
        }
      }
      const int prow = (int)s_misc[M_SEL0] - rb * 256;
      const bool patch = ((prow - (wg - 2) * 64 - wi * 16) & ~0x8F) == 0;
      const float* cs = (const float*)(smem + OFF_CS);
      auto finish = [&](int m, int b, float2 c, uint32_t* dst) {
        dst[0] = pack_bf16(acc[m][4 * b] * pa[m][0] - c.x * pb[m][0], acc[m][4 * b + 1] * pa[m][0] - c.y * pb[m][0]);
        dst[1] = pack_bf16(acc[m][4 * b + 2] * pa[m][1] - c.x * pb[m][1], acc[m][4 * b + 3] * pa[m][1] - c.y * pb[m][1]);
      };
      wg_wait<0>();
      fence_regs<96>(acc[0]); fence_regs<96>(acc[1]);
      if (warp != 9) STEPT(1);
      if (lane < 2) mbar_arrive_cluster(bar(B_QDONE), lane);
      if (warp == 9) PROF(2);
#pragma unroll
      for (int h = 0; h < 2; h++) {
        const uint32_t dst = sbase + (h * 8 + 2 + wg) * 8192 + srow * 64;
#pragma unroll
        for (int jj = 0; jj < 4; jj++) {
          const int b = 8 + (jj >> 1) * 8 + h * 4 + (jj & 1) * 2;
          const float2 c0 = *(const float2*)&cs[8 * b + 2 * q], c1 = *(const float2*)&cs[8 * b + 8 + 2 * q];
          uint32_t r[2][4];
#pragma unroll
          for (int m = 0; m < 2; m++) { finish(m, b, c0, r[m]); finish(m, b + 1, c1, r[m] + 2); }
          if (h == 0 && jj == 0) named_bar(5, 256);
#pragma unroll
          for (int m = 0; m < 2; m++)
            stsm_x4(dst + m * 16384 + (jj >> 1) * 4096 + ((((jj & 1) * 2 + (mi >> 1)) ^ ((srow >> 1) & 3)) << 4), r[m][0], r[m][1], r[m][2], r[m][3]);
        }
        if (patch) {
          __syncwarp();
          if (lane < 8)
            *(uint4*)(smem + (h * 8 + 4 + (prow >> 6)) * 8192 + g * 4096 + (prow & 63) * 64 + ((q ^ ((prow >> 1) & 3)) << 4)) =
                *(const uint4*)(smem + OFF_PATCH + 128 + g * 128 + h * 64 + q * 16);
        }
        fence_async_smem();
        __syncwarp();
        mbar_arrive_e(bar(B_KVREADY + h));
        if (warp != 9) STEPT(2 + h);
      }
#pragma unroll
      for (int j = 0; j < 4; j++) { pa[j >> 1][j & 1] *= SM_C; pb[j >> 1][j & 1] *= SM_C; }
#pragma unroll
      for (int jj = 0; jj < 4; jj++) {
        const float2 c0 = *(const float2*)&cs[16 * jj + 2 * q], c1 = *(const float2*)&cs[16 * jj + 8 + 2 * q];
#pragma unroll
        for (int m = 0; m < 2; m++) {
          uint32_t r[4];
          finish(m, 2 * jj, c0, r); finish(m, 2 * jj + 1, c1, r + 2);
          *(uint4*)(smem + AT_ST + ((jj >> 1) * 16 + warp - 8 + 8 * m) * 1024 + (jj & 1) * 512 + lane * 16) = make_uint4(r[0], r[1], r[2], r[3]);
        }
      }
      __syncwarp();
      if (patch) {
        *(uint32_t*)(smem + AT_ST + ((lane >> 4) * 16 + (prow >> 4)) * 1024 + (mi & 1) * 512 + ((prow & 7) * 4 + q) * 16 + ((g & 1) * 2 + ((prow >> 3) & 1)) * 4) =
            *(const uint32_t*)(smem + OFF_PATCH + lane * 4);
        __syncwarp();
      }
      if (warp == 9) PROF(3);
      mbar_arrive_e(bar(B_QREADY));
      regs_dec<120>();
    } else {
      if (pass > 0) {
        const unsigned layer = pass - 1;
        PHASE_IDS
        const uint32_t tag = s_misc[M_TAG];
        if (warp == 7) {
              uint32_t* tab = (uint32_t*)(smem + OFF_PATCH);
#pragma unroll
              for (int j = 0; j < 2; j++) { const int w = lane + 32 * j; tab[(w & 3) * 16 + (w >> 2)] = ((const uint32_t*)P.w_r)[nb * 64 + w]; }
              tab[64 + lane] = lane < 16 ? 0x3F803F80u : 0u;
              float tot = 0.f;
#pragma unroll
              for (int j = 0; j < 4; j++) {
                const uint4 u = ((const uint4*)P.w_r)[lane + 32 * j];
                tot += bf_lo(u.x) + bf_hi(u.x) + bf_lo(u.y) + bf_hi(u.y) + bf_lo(u.z) + bf_hi(u.z) + bf_lo(u.w) + bf_hi(u.w);
              }
              s_misc[M_WSUM] = __float_as_uint(warp_sum(tot));
        }
              if (layer == 1) {
                const float2 ln = g_rowln[nb][mb * 128 + tid - 128];
                const uint32_t m2 = pack_bf16(ln.x, ln.x);
                uint8_t* row = smem + AT_ST + (wi >> 1) * 16384 + (tid & 63) * 128;
                mbar_wait(bar(B_RES), 1);
#pragma unroll 1
                for (int j = 0; j < 8; j++) {
                  uint4* c = (uint4*)(row + (((j + lane) & 7) << 4));
                  const uint4 v = c[0], w = c[512];
                  c[0] = make_uint4(add_ln_pair(v.x, m2, ln.y), add_ln_pair(v.y, m2, ln.y), add_ln_pair(v.z, m2, ln.y), add_ln_pair(v.w, m2, ln.y));
                  c[512] = make_uint4(add_ln_pair(w.x, m2, ln.y), add_ln_pair(w.y, m2, ln.y), add_ln_pair(w.z, m2, ln.y), add_ln_pair(w.w, m2, ln.y));
                }
                const int prow = (int)s_misc[M_SEL0] - mb * 128;
                __syncwarp();
                if (prow >> 5 == wi && lane < 16)
                  *(uint4*)(smem + AT_ST + (prow >> 6) * 16384 + (lane >> 3) * 8192 + (prow & 63) * 128 + (((lane ^ prow) & 7) << 4)) = poll4(&g_x2row[(nb * 16 + lane) * 2]);
                PROF(30);
              }
              __syncwarp();
              mbar_arrive_e(bar(B_RST));
        if (warp == 4) {
            named_bar(6, 320);
            spin_cycles(DELAY_S);
            uint4 c, u0, u1;
            uint32_t u2, best = 0, spins = 0;
            int src;
#pragma unroll 1
            for (;;) {
              src = (~best & 0x7FFu) >> 7;
              const uint4* xsel = &g_cand[layer][src * 128];
              c = ld_relaxed4(&g_slot[layer][(lane & 15) * 8]);
              u0 = ld_relaxed4(xsel + rank * 64 + lane); u1 = ld_relaxed4(xsel + rank * 64 + 32 + lane);
              u2 = ld_relaxed((const uint32_t*)(xsel + (bid >> 4) * 16 + q * 4) + (bid & 15));
              const uint32_t prev = best;
              best = __reduce_max_sync(0xffffffffu, c.w == tag ? c.x : 0u);
              if ((__all_sync(0xffffffffu, c.w == tag && valid4(u0) && valid4(u1) && u2 != SENT) && best == prev) || ++spins > SPIN_LIMIT) break;
            }
            const float sel_m = __uint_as_float(__shfl_sync(0xffffffffu, c.y, src)), sel_inv = __uint_as_float(__shfl_sync(0xffffffffu, c.z, src));
            const uint32_t m2 = pack_bf16(sel_m, sel_m);
            uint4* xs = (uint4*)(smem + T_XS) + (lane & 16) + q * 4 + (g & 3);
            xs[0] = make_uint4(ln_pair(u0.x, m2, sel_inv), ln_pair(u0.y, m2, sel_inv), ln_pair(u0.z, m2, sel_inv), ln_pair(u0.w, m2, sel_inv));
            xs[32] = make_uint4(ln_pair(u1.x, m2, sel_inv), ln_pair(u1.y, m2, sel_inv), ln_pair(u1.z, m2, sel_inv), ln_pair(u1.w, m2, sel_inv));
            s_misc[M_KEY] = best; s_misc[M_MEAN] = __float_as_uint(sel_m); s_misc[M_INV] = __float_as_uint(sel_inv);
            s_misc[M_XQ + q] = u2;
            PROF(16);
        }
        if (layer == 1) {
          named_bar(7, 512);
          const int sel = SEQ - 1 - (int)(s_misc[M_KEY] & 0x7FFFu), skip = sel >> 7 == mb ? (sel >> 6) & 1 : -1;
          if (warp == 7) store_tile(1, skip, false);
#pragma unroll 1
          for (int c = tid - 128; c < 1024 && skip >= 0; c += 128) {
            const int r = c >> 4;
            if (r != (sel & 63))
              *(uint4*)(P.out + (size_t)(mb * 128 + skip * 64 + r) * DM + nb * 128 + (c & 15) * 8) =
                  *(const uint4*)(smem + AT_ST + skip * 16384 + ((c >> 3) & 1) * 8192 + r * 128 + (((c ^ r) & 7) << 4));
          }
          __syncwarp();
        } else asm volatile("bar.arrive 7, 512;" ::: "memory");
        if (warp == 5 && layer == 0) {
              named_bar(8, 288);
              if (nb > 0) spin_cycles(X_STAGGER);
              store_tile(0, -1, true);
              set_flag(&g_xflag[mb][nb].v[0], tag);
              PROF(17);
              poll_flag(&g_xflag[2 * rb + (lane & 1)][0].v[0], tag);
              fence_async_global();
              load_a(0, 0, 1);
              load_a(1, 1, 1);
              PROFL(1, 1);
        }
      }
      named_bar(1 + (fresh_tid() >> 7), 128);
      regs_dec<32>();
#pragma unroll 1
      for (;;) {
      const unsigned pass = __shfl_sync(0xffffffffu, pass_v, 0);
      if (pass > 0) {
        const unsigned layer = pass - 1;
        PHASE_IDS
        const uint32_t tag = s_misc[M_TAG], bkey = s_misc[M_KEY];
        const int sel = SEQ - 1 - (int)(bkey & 0x7FFFu);
        if (warp == 3) {
          if (layer == 1) {
            if (lane < 24) ((uint4*)g_cspart)[bid * 24 + lane] = make_uint4(0, 0, 0, 0);
          } else s_misc[M_SEL0] = sel;
          if (bid == 0 && lane == 0) g_sel[layer] = sel;
        }
        __syncwarp();
        if (layer == 0) {
          auto load_down = [&](int j) {
            mbar_expect_tx(bar(B_DN + j), 2 * FFN_PIECE);
            bulk_load_h(sbase + SL_F + j * 2 * FFN_PIECE, P.w_d + (size_t)(bid * 28 + j * 14) * DM, 2 * FFN_PIECE, bar(B_DN + j), FFN_POL);
          };
          if (warp == 0) {
            load_down(0);
            poll_flag(&g_xflag[2 * rb + (lane & 1)][(lane >> 1) & 7].v[0], tag);
          }
          float hv = 0.f;
          if (wg == 1) { mbar_wait_cluster(bar(B_HX), 0); hv = rbf(hidden()); fence_regs<1>(&hv); }
          named_bar(9, 512);
          if (warp == 0) {
            fence_async_global();
            fence_async_smem();
            if (lane < 16) mbar_arrive_cluster(bar(B_QFREE), lane & 1);
            mbar_wait(bar(B_QFREE), 1);
            load_w(2, 2); load_a(2, 2, 1);
          } else if (wg == 1) {
            if (warp == 4) { mbar_wait(bar(B_DN), 0); load_down(1); }
            float d[8] = {0.f, 0.f, 0.f, 0.f, 0.f, 0.f, 0.f, 0.f};
#pragma unroll 1
            for (int j = 0; j < 28; j += 2) {
              if (j == 0 || j == 14) mbar_wait(bar(B_DN + (j > 0)), 0);
              const uint4 w0 = *(const uint4*)(smem + SL_F + j * 2048 + (tid - 128) * 16), w1 = *(const uint4*)(smem + SL_F + j * 2048 + 2048 + (tid - 128) * 16);
              fma8(d, w0, __shfl_sync(0xffffffffu, hv, j));
              fma8(d, w1, __shfl_sync(0xffffffffu, hv, j + 1));
            }
            uint4* dst = &g_ypart[0][bid * 256 + (tid - 128) * 2];
            st_relaxed4(dst, make_uint4(f2u(d[0]), f2u(d[1]), f2u(d[2]), f2u(d[3])));
            st_relaxed4(dst + 1, make_uint4(f2u(d[4]), f2u(d[5]), f2u(d[6]), f2u(d[7])));
            named_bar(2, 128);
            PROF(20);
            if (warp == 5) {
              fence_async_smem();
              mbar_expect_tx(bar(B_WS), 4 * SL_HD);
#pragma unroll 1
              for (int j = 0; j < 4; j++) tma_load3(sbase + SL_F + j * SL_HD, &P.mapW, hp * 64, rb * 128 + j * 32, 0, bar(B_WS));
            }
          }
        } else {
          if (wg == 1) named_bar(9, 384);
        }
        if (wg == 1) {
          const int t_y = (int)clock();
          const uint32_t xw = s_misc[M_XQ + ((lane & 7) >> 1)];
          const float x = (lane & 1) ? bf_hi(xw) : bf_lo(xw);
          float xn = rbf(rbf(x - __uint_as_float(s_misc[M_MEAN])) * __uint_as_float(s_misc[M_INV]));
          uint32_t u = bkey & 0xFFFF0000u;
          u = (u & 0x80000000u) ? (u & 0x7FFFFFFFu) : (~u & 0xFFFF0000u);
          float sg = rbf(__fdividef(1.f, 1.f + __expf(-__uint_as_float(u))));
          uint32_t* dst = (layer == 0 ? (uint32_t*)&g_x2row[bid * 2] : (uint32_t*)(P.out + (size_t)sel * DM + bid * 8)) + (lane >> 1);
          asm volatile("" : "+f"(xn), "+f"(sg), "+l"(dst));
#pragma unroll 1
          while ((int)clock() - t_y < DELAY_Y) {}
          const uint4* src = &g_ypart[layer][((tid - 128) >> 1) * 256 + bid * 2 + (tid & 1)];
          uint4 v, w;
          uint32_t spins = 0;
#pragma unroll 1
          do { v = ld_relaxed4(src); w = ld_relaxed4(src + 64 * 256); } while (!__all_sync(0xffffffffu, valid4(v) && valid4(w)) && ++spins < SPIN_LIMIT);
          float a[4] = {__uint_as_float(v.x) + __uint_as_float(w.x), __uint_as_float(v.y) + __uint_as_float(w.y),
                        __uint_as_float(v.z) + __uint_as_float(w.z), __uint_as_float(v.w) + __uint_as_float(w.w)};
          const bool b1 = lane & 2, b2 = lane & 4;
          float c0 = (b1 ? a[1] : a[0]) + __shfl_xor_sync(0xffffffffu, b1 ? a[0] : a[1], 2);
          float c1 = (b1 ? a[3] : a[2]) + __shfl_xor_sync(0xffffffffu, b1 ? a[2] : a[3], 2);
          float y = (b2 ? c1 : c0) + __shfl_xor_sync(0xffffffffu, b2 ? c0 : c1, 4);
          y += __shfl_xor_sync(0xffffffffu, y, 8);
          y += __shfl_xor_sync(0xffffffffu, y, 16);
          float* red = (float*)(smem + OFF_PATCH);
          red[wi * 8 + (lane & 1) * 4 + ((lane >> 1) & 3)] = y;
          named_bar(2, 128);
          if (warp == 4) {
            PROF(21);
            y = (red[lane & 7] + red[8 + (lane & 7)]) + (red[16 + (lane & 7)] + red[24 + (lane & 7)]);
            const float res = x + rbf(xn + rbf(rbf(y) * sg));
            const uint32_t pr = nosent(pack_bf16(res, __shfl_down_sync(0xffffffffu, res, 1)));
            if (lane < 8 && (lane & 1) == 0) st_relaxed(dst, pr);
            PROF(22);
          }
        }
        if (pass == 2) {
          if (bid == 0 && tid == 128) g_epoch = tag;
          bulk_wait_all();
          __syncwarp();
          cluster_arrive(); cluster_wait();
          return;
        }
      }
      const unsigned layer = pass;
      if (layer == 1 && __shfl_sync(0xffffffffu, fresh_tid() >> 5, 0) > 0) {
        PHASE_IDS
        uint4* xrow = (uint4*)(smem + SL_F + 4 * SL_HD);
        if (wg == 1) { xrow[tid - 128] = poll4(&g_x2row[(tid - 128) * 2]); PROF(23); }
        named_bar(12, 224);
        if (warp == 7) {
          float mean = 0.f;
#pragma unroll 1
          for (int pass2 = 0; pass2 < 2; pass2++) {
            float acc = 0.f;
#pragma unroll 1
            for (int j = lane; j < 512; j += 32) {
              const uint32_t w = ((const uint32_t*)xrow)[j];
              const float d0 = bf_lo(w) - mean, d1 = bf_hi(w) - mean;
              acc += pass2 ? d0 * d0 + d1 * d1 : d0 + d1;
            }
            acc = warp_sum(acc) * (1.f / DM);
            if (pass2 == 0) mean = acc;
            else { s_misc[M_PMEAN] = __float_as_uint(rbf(mean)); s_misc[M_PINV] = __float_as_uint(ln_inv(acc)); }
          }
        } else {
          mbar_wait(bar(B_WS), 0);
          const uint8_t* wa = smem + SL_F + (g >> 1) * SL_HD + ((warp - 1) >> 1) * 4096 + (g & 1) * 2048;
          const uint32_t* xs = (const uint32_t*)xrow + rb * 64 + g * 8;
          const int ch = ((warp - 1) & 1) * 4 + q;
          float d[8] = {0.f, 0.f, 0.f, 0.f, 0.f, 0.f, 0.f, 0.f};
#pragma unroll 1
          for (int j0 = 0; j0 < 16; j0 += 2) {
            const int j = j0 ^ ((g & 1) * 4);
            const uint4 w0 = *(const uint4*)(wa + j * 128 + (((ch ^ j) & 7) << 4)), w1 = *(const uint4*)(wa + j * 128 + 128 + (((ch ^ (j + 1)) & 7) << 4));
            const uint32_t xx = xs[j >> 1];
            fma8(d, w0, bf_lo(xx)); fma8(d, w1, bf_hi(xx));
          }
#pragma unroll
          for (int c = 0; c < 4; c++) d[c] = ((g & 4) ? d[c + 4] : d[c]) + __shfl_xor_sync(0xffffffffu, (g & 4) ? d[c] : d[c + 4], 16);
#pragma unroll
          for (int c = 0; c < 2; c++) d[c] = ((g & 2) ? d[c + 2] : d[c]) + __shfl_xor_sync(0xffffffffu, (g & 2) ? d[c] : d[c + 2], 8);
          d[0] = ((g & 1) ? d[1] : d[0]) + __shfl_xor_sync(0xffffffffu, (g & 1) ? d[0] : d[1], 4);
          st_relaxed(&g_patch[rb][((warp - 1) >> 1) * DM + hp * 64 + ch * 8 + g], f2u(d[0]));
        }
        named_bar(12, 224);
        PROF(24);
      }
      PHASE_IDS
      if (wg == 0) {
        if (warp == 0) {
          int s = 0, u = 0;
#pragma unroll 1
          for (int i = 3; i < 16; i++) {
            if (layer == 1) mbar_arrive_e(bar(B_EMPTY + s));
            mbar_wait(bar(B_EMPTY + s), (u + (s ? 0 : layer)) & 1);
            load_w(s, i);
            load_a(s, i, layer);
            if (++s == 3) { s = 0; u++; }
          }
        } else if (warp == 1) {
          if (layer == 0) {
            const uint32_t tag = ld_relaxed(&g_epoch) + 1;
            float shift = 0.f, sum = 0.f, sq = 0.f;
            const int r = hp * 16 + (lane >> 1);
#pragma unroll 1
            for (int i = 0; i < 16; i++) {
              mbar_wait(bar(B_FULL + i % 3), (i / 3) & 1);
              const uint8_t* base = smem + (i % 3) * STG + r * 128;
#pragma unroll 1
              for (int j0 = 0; j0 < 4; j0 += 2) {
                uint4 v[2];
#pragma unroll
                for (int j = 0; j < 2; j++) v[j] = *(const uint4*)(base + ((((lane & 1) * 4 + j0 + j) ^ (r & 7)) << 4));
                if (i == 0 && j0 == 0) shift = __shfl_sync(0xffffffffu, bf_lo(v[0].x), lane & ~1);
#pragma unroll
                for (int j = 0; j < 2; j++) {
                  const uint32_t w[4] = {v[j].x, v[j].y, v[j].z, v[j].w};
#pragma unroll
                  for (int c = 0; c < 4; c++) {
                    const float d0 = bf_lo(w[c]) - shift, d1 = bf_hi(w[c]) - shift;
                    sum += d0 + d1; sq = fmaf(d0, d0, fmaf(d1, d1, sq));
                  }
                }
              }
              __syncwarp();
              if (i < 13) mbar_arrive_e(bar(B_EMPTY + i % 3));
            }
            sum += __shfl_xor_sync(0xffffffffu, sum, 1); sq += __shfl_xor_sync(0xffffffffu, sq, 1);
            const float dm = sum * (1.f / DM), var = fmaxf(sq * (1.f / DM) - dm * dm, 0.f), mean = shift + dm;
            const float inv = ln_inv(var);
            if ((lane & 1) == 0) st_relaxed4(&g_rowab[0][rb * 256 + r], make_uint4(__float_as_uint(inv), __float_as_uint(rbf(mean) * inv), tag, 0));
          }
          if (rb == 0) {
            mbar_wait(bar(B_QDONE), layer);
#pragma unroll 1
            for (int j = lane; j < 512; j += 32) ((uint4*)(smem + 65536))[j] = make_uint4(0, 0, 0, 0);
            fence_async_smem();
            __syncwarp();
            if (lane < 3) mbar_arrive(bar(B_HALO + lane));
          }
        } else if (warp == 3) {
          if (layer == 0) {
#pragma unroll 1
            for (int u = 0; u < GUA_AT; u++) mbar_wait(bar(B_FULL), u & 1);
          }
          fence_async_smem();
          load_gu(0, layer ? GU_PACE1 : GU_PACE);
          PROF(27);
        } else {
#pragma unroll 1
          for (int u = 4 * layer; u < 4; u++) mbar_wait(bar(B_FULL), u & 1);
          const uint4 sent = make_uint4(SENT, SENT, SENT, SENT), zero = make_uint4(0, 0, 0, 0);
#pragma unroll 1
          for (int t = lane; t < 128; t += 32) {
            g_ypart[layer][bid * 256 + t] = sent; g_ypart[layer][bid * 256 + 128 + t] = sent;
            g_part[layer][nb * SEQ + mb * 128 + t] = zero;
            if (t < 16) g_cand[layer][mb * 128 + nb * 16 + t] = sent;
            else if (t < 18) { if (nb == 0) g_slot[layer][mb * 8 + t - 16] = zero; }
            else if (t < 20) { if (layer == 0) g_x2row[bid * 2 + t - 18] = sent; }
            else if (t >= 80 && layer == 0) *(uint4*)&g_patch[rb][((t - 80) >> 4) * DM + hp * 64 + (t & 15) * 4] = sent;
          }
        }
        __syncwarp();
        if (rank == 0) {
          if (warp == 0) {
            mbar_wait(bar(B_QDONE), layer);
#pragma unroll 1
            for (int j = 0; j < 3; j++) {
              const int o = j == 0 ? 16384 : (j == 1 ? 0 : 65536);
              mbar_wait(bar(B_KVREADY + (j >> 1)), layer);
              bulk_push(mapa(sbase + o, 1), sbase + 32768 + o, j == 2 ? 32768 : 16384, mapa(bar(B_HALO + j), 1));
            }
          } else if (warp < 3 && rb > 0) {
            mbar_wait(bar(B_QREADY), layer);
            if (warp == 2) spin_cycles(1000);
            import_halo(layer, warp - 1);
            if (warp == 1) PROF(5);
          }
        } else if (warp == 2) {
          mbar_expect_tx(bar(B_HALO), 16384); mbar_expect_tx(bar(B_HALO + 1), 16384); mbar_expect_tx(bar(B_HALO + 2), 32768);
        } else if (warp < 2 && rb < 7) {
          mbar_wait(bar(B_KVREADY + warp), layer);
          if (warp == 1) named_bar(13, 64);
          bulk_store(g_kv + (size_t)((rb >> 1) * 16 + hp) * 65536 + warp * 32768, sbase + 32768 + warp * 65536, 32768);
          bulk_commit();
          bulk_wait_all();
          if (warp == 0) asm volatile("bar.arrive 13, 64;" ::: "memory");
          set_flag(&g_kvflag[rb >> 1][hp][warp].v[layer], s_misc[M_TAG]);
          if (warp == 0) PROF(4);
        }
      } else {
        const int t = tid - 128, go = (t >> 5) * DM + hp * 64 + (t & 31) * 2;
        if (layer == 0) {
          if (t == 0) { s_misc[M_TAG] = ld_relaxed(&g_epoch) + 1; s_misc[M_SEL0] = 0xFFFFFFFFu; s_misc[M_PROG] = 0; }
#pragma unroll 1
          for (int u = 0; u < 5; u++) mbar_wait(bar(B_FULL + 2), u & 1);
          if (warp < 7) {
            uint2 v[4];
            uint32_t spins = 0;
#pragma unroll 1
            do {
#pragma unroll
              for (int j = 0; j < 4; j++) v[j] = ld_relaxed2(&g_cspart[j][go]);
            } while (!__all_sync(0xffffffffu, v[0].x && v[0].y && v[1].x && v[1].y && v[2].x && v[2].y && v[3].x && v[3].y) && ++spins < SPIN_LIMIT);
            ((float2*)(smem + OFF_CS))[t] = make_float2((dec(v[0].x) + dec(v[1].x)) + (dec(v[2].x) + dec(v[3].x)), (dec(v[0].y) + dec(v[1].y)) + (dec(v[2].y) + dec(v[3].y)));
          }
        } else {
          if ((int)s_misc[M_SEL0] >> 8 == rb && warp < 7) {
            float s0 = 0.f, s1 = 0.f;
#pragma unroll 1
            for (int hf = 0; hf < 8; hf += 4) {
              uint2 w[4];
              uint32_t spins = 0;
#pragma unroll 1
              do {
#pragma unroll
                for (int j = 0; j < 4; j++) w[j] = ld_relaxed2(&g_patch[hf + j][go]);
              } while (!__all_sync(0xffffffffu, valid4(make_uint4(w[0].x, w[0].y, w[1].x, w[1].y)) && valid4(make_uint4(w[2].x, w[2].y, w[3].x, w[3].y))) && ++spins < SPIN_LIMIT);
              s0 += (__uint_as_float(w[0].x) + __uint_as_float(w[1].x)) + (__uint_as_float(w[2].x) + __uint_as_float(w[3].x));
              s1 += (__uint_as_float(w[0].y) + __uint_as_float(w[1].y)) + (__uint_as_float(w[2].y) + __uint_as_float(w[3].y));
            }
            const float2 c = ((const float2*)(smem + OFF_CS))[t];
            const float a = __uint_as_float(s_misc[M_PINV]) * (warp == 4 ? SM_C : 1.f), b = __uint_as_float(s_misc[M_PMEAN]) * a;
            ((uint32_t*)(smem + OFF_PATCH))[t] = pack_bf16(s0 * a - c.x * b, s1 * a - c.y * b);
            PROF(25);
          }
        }
        __syncwarp();
        mbar_arrive_e(bar(B_CS));
      }
      __syncwarp();
      mbar_wait(bar(B_QREADY), layer);
      named_bar(1 + (fresh_tid() >> 7), 128);
      if (__shfl_sync(0xffffffffu, fresh_tid() >> 7, 0) == 0) {
        regs_inc<152>();
        uint32_t gu[112];
        {
          PHASE_IDS
          const uint32_t tag = s_misc[M_TAG];
          mbar_wait(bar(B_GU), layer);
#pragma unroll
          for (int j = 0; j < 28; j++) fetch_gu(gu + 4 * j, warp * 4 + (j & 3), j >> 2);
          fence_async_smem();
          named_bar(1, 128);
          if (warp == 0) {
            mbar_wait(bar(B_WGO), layer);
            mbar_wait(bar(B_ADONE), layer);
#pragma unroll 1
            for (int k = 2; k < 16; k++) {
              if (HOLD_K && k == HOLD_K) named_bar(14, 64);
              if (PROG) {
#pragma unroll 1
                for (uint32_t spins = 0; k >= 8 && (int)s_misc[M_PROG] <= k + 16 * (int)layer && spins < SPIN_LIMIT; spins++) {}
              } else if (k == 8) mbar_wait(bar(B_WGO + 1), layer);
              if (k >= 4) mbar_wait(bar(B_WEMPTY + (k & 3)), ((k >> 2) - 1 + ((k & 2) ? layer : 0)) & 1);
              load_o(k); load_wo(k);
              STEPT(16 + k);
              if (k == RES_K) { mbar_wait(bar(B_OST + 1), layer); load_res(1, layer); }
            }
            if (layer == 1) {
              mbar_wait(bar(B_WEMPTY + 1), 1);
              if (FAKE & 2) mbar_arrive_e(bar(B_DN)); else mbar_expect_tx(bar(B_DN), 4 * FFN_PIECE);
              if (!(FAKE & 2)) tma_load3_h(sbase, &P.mapD, 0, bid * 28, 0, bar(B_DN), FFN_POL);
              if (D_SPLIT == 0) tma_load3_h(sbase + 2 * FFN_PIECE, &P.mapD, 0, bid * 28, 8, bar(B_DN), FFN_POL);
            }
            named_bar(6, 320);
            if (layer == 0) {
              mbar_wait(bar(B_QFREE), 0);
              load_w(0, 0); load_w(1, 1);
            } else if (D_SPLIT == 1 && !(FAKE & 2)) tma_load3_h(sbase + 2 * FFN_PIECE, &P.mapD, 0, bid * 28, 8, bar(B_DN), FFN_POL);
          } else if (warp < 3) {
            const int h = warp - 1;
#pragma unroll 1
            for (int qb = 3; qb >= 0; qb--) {
              mbar_wait(bar(B_UNIT + h * 4 + 3 - qb), layer);
              bulk_store(g_o + (size_t)((((rb * 2 + (qb >> 1)) * 2 + h) * 16 + hp) * 2 + (qb & 1)) * 4096, sbase + AT_ST + (h * 4 + qb) * 4096, 4096);
            }
            bulk_commit();
            if (h == 0 && lane < 2) mbar_arrive_cluster(bar(B_OST), lane);
            bulk_wait_all();
            if (h == 1) mbar_arrive_e(bar(B_OST + 1));
            set_flag(&g_oflag[rb][h][hp].v[layer], tag);
            if (HOLD_K && h == 1) asm volatile("bar.arrive 14, 64;" ::: "memory");
            PROF(28 + 3 * h);
            if (h == 0) {
              load_res(0, layer);
              mbar_wait(bar(B_OST), layer);
              load_wo(0); load_wo(1);
            }
            if (PROG && h == 1) {
              int n = 0;
#pragma unroll 1
              for (uint32_t spins = 0; n < 8 && spins < SPIN_LIMIT; spins++) {
                n = (__ffs(__ballot_sync(0xffffffffu, ld_relaxed(&g_oflag[rb][1][lane & 15].v[layer]) != tag || lane == 16)) - 1) >> 1;
                asm volatile("fence.acquire.gpu;" ::: "memory");
                fence_async_global();
                s_misc[M_PROG] = 8 + n + 16 * layer;
              }
            } else {
            poll_flag(&g_oflag[rb][h][lane & 15].v[layer], tag);
            fence_async_global();
            }
            PROF(15 + 11 * h);
            if (h == 0) { load_o(0); load_o(1); }
            mbar_arrive_e(bar(B_WGO + h));
          } else {
            mbar_expect_tx(bar(B_HX), 2240);
            mbar_wait(bar(B_HALO + 2), layer);
            if (rb == 0) spin_cycles(2000);
            PROF(6);
            load_gu(1, GUB_PACE);
          }
        }
        PHASE_IDS
        uint4 xa = {}, xb = {};
        named_bar(7, 512);
        if (g == 0) { xa = ((const uint4*)(smem + T_XS))[warp * 8 + q]; xb = ((const uint4*)(smem + T_XS))[warp * 8 + 4 + q]; }
        __syncwarp();
        float d[7][4] = {};
#pragma unroll
        for (int j = 0; j < 28; j++) {
          const int ks = j / 7, ct = j % 7;
          const uint32_t* a = gu + ct * 16 + ks * 4;
          mma_16816(d[ct], a[0], a[1], a[2], a[3], ks == 0 ? xa.x : ks == 1 ? xa.z : ks == 2 ? xb.x : xb.z, ks == 0 ? xa.y : ks == 1 ? xa.w : ks == 2 ? xb.y : xb.w);
        }
#pragma unroll
        for (int ct = 0; ct < 7; ct++) send_gu(d[ct][0], d[ct][2], ct, warp);
        __syncwarp();
        if (warp == 2) PROF(18);
        regs_dec<32>();
        pass_v = pass + 1;
        continue;
      }
      break;
      }
      regs_inc<120>();
    }
    const unsigned layer = pass;
    {
      PHASE_IDS
      mbar_wait(bar(B_QREADY), layer);
      if (warp != 9) STEPT(7);
      auto kdesc = [&](int h, int b) { return dlo(SOFF, 16) + (rb == 0 && b < 4 ? 4096 : h * 4096 + b * 512); };
      auto vdesc = [&](int h, int b) { return rb == 0 && b < 4 ? dlo(SOFF + 65536, 4096) : dlo(SOFF + 4096, OFF_ONES - 4096) + (h * 8 + b) * 8 * VSTEP; };
      const int units = wg == 3 ? 0x8630 : (wg == 2 ? ULIST2 : ULIST1);
      auto need = [&](int h, int b) { if (b == 3 || b == 1) mbar_wait(bar(B_HALO + (h ? 2 : b == 1)), layer); };
      auto load_q = [&](uint32_t* qf, int u) {
        *(uint4*)&qf[0] = *(const uint4*)(smem + AT_ST + ((u ^ 3) * 4 + wi) * 1024 + lane * 16);
        *(uint4*)&qf[4] = *(const uint4*)(smem + AT_ST + ((u ^ 3) * 4 + wi) * 1024 + 512 + lane * 16);
      };
      auto store_o = [&](const float* o, int u) {
        const float i0 = __fdividef(1.f, o[16]), i1 = __fdividef(1.f, o[18]);
        const int v = u ^ 3;
        if (u >= 4 && lane < 2) mbar_arrive_cluster(bar(B_ADONE), lane);
#pragma unroll
        for (int j = 0; j < 2; j++)
          stsm_x4(sbase + AT_ST + v * 4096 + srow * 64 + (((2 * j + (mi >> 1)) ^ ((srow >> 1) & 3)) << 4),
                  pack_bf16(o[8 * j] * i0, o[8 * j + 1] * i0), pack_bf16(o[8 * j + 2] * i1, o[8 * j + 3] * i1),
                  pack_bf16(o[8 * j + 4] * i0, o[8 * j + 5] * i0), pack_bf16(o[8 * j + 6] * i1, o[8 * j + 7] * i1));
        fence_async_smem();
        __syncwarp();
        mbar_arrive_e(bar(B_UNIT + u));
      };
      int redo = 0;
      {
        const int dl = g - 2 * q;
        const uint32_t mt = shl_clamp(0xFFFFFFFFu, max(16 * dl + 16, 0));
        uint32_t qf[8];
        float s[32];
        load_q(qf, units & 7);
        wg_fence();
        qk64(s, qf, kdesc((units >> 2) & 1, 6 - (units & 3)));
        wg_commit();
        wg_wait<0>();
        fence_regs<32>(s);
#pragma unroll 1
        for (int ul = units; ul != 8; ul >>= 4) {
          const int u = ul & 7, h = u >> 2, qb = 3 - (u & 3);
          float o[20];
          uint32_t p1[16], p2[16], p3[16], p4[16], p5[16];
          if (warp != 9) STEPT(8 + nu * 8);
          exp_pack<8>(s, p1);
          fence_regs_u<16>(p1);
          need(h, qb + 2);
          {
            float s2[32];
            const uint32_t vd = vdesc(h, qb + 3);
            wg_fence();
            qk64(s2, qf, kdesc(h, qb + 2));
            wg_commit();
            wg_rs40t_z<H64>(o, p1[0], p1[1], p1[2], p1[3], vd);
            wg_rs40t<H64>(o, p1[4], p1[5], p1[6], p1[7], vd + VSTEP, 1);
            pv32(o, p1 + 8, vd + 2 * VSTEP);
            wg_commit();
            wg_wait<1>();
            fence_regs<32>(s2);
            if (warp != 9) STEPT(9 + nu * 8);
            exp_pack<8>(s2, p2);
            fence_regs_u<16>(p2);
            wg_wait<0>();
            fence_regs<20>(o);
          }
          need(h, qb + 1);
          {
            float s3[32];
            wg_fence();
            qk64(s3, qf, kdesc(h, qb + 1));
            wg_commit();
            pv32(o, p2, vdesc(h, qb + 2)); pv32(o, p2 + 8, vdesc(h, qb + 2) + 2 * VSTEP);
            wg_commit();
            wg_wait<1>();
            fence_regs<32>(s3);
            if (warp != 9) STEPT(10 + nu * 8);
            exp_pack<8>(s3, p3);
            fence_regs_u<16>(p3);
            wg_wait<0>();
            fence_regs<20>(o);
          }
          need(h, qb);
          const uint32_t kd = kdesc(h, qb + 4), kt = kdesc(h, qb), vd = vdesc(h, qb + 4), vt = vdesc(h, qb);
          {
            float sd[16], st[16];
            wg_fence();
            qk32x2(sd, st, qf, kd, kt);
            wg_commit();
            pv32(o, p3, vdesc(h, qb + 1)); pv32(o, p3 + 8, vdesc(h, qb + 1) + 2 * VSTEP);
            wg_commit();
            wg_wait<1>();
            fence_regs<16>(sd); fence_regs<16>(st);
            if (warp != 9) STEPT(11 + nu * 8);
            edge32(sd, st, p4, p4 + 8, wi, dl, mt);
            fence_regs_u<16>(p4);
            wg_wait<0>();
            fence_regs<20>(o);
          }
          const int un = (ul >> 4) == 8 ? 4 : (ul >> 4) & 7;
          {
            float sd[16], st[16];
            wg_fence();
            qk32x2(sd, st, qf, kd + 128, kt + 128);
            wg_commit();
            pv32(o, p4, vd); pv32(o, p4 + 8, vt);
            wg_commit();
            wg_wait<1>();
            fence_regs<16>(sd); fence_regs<16>(st);
            load_q(qf, un);
            edge32(sd, st, p5, p5 + 8, wi - 2, dl, mt);
            fence_regs_u<16>(p5);
          }
          need(un >> 2, 6 - (un & 3));
          wg_fence();
          pv32(o, p5, vd + 2 * VSTEP); pv32(o, p5 + 8, vt + 2 * VSTEP);
          wg_commit();
          qk64(s, qf, kdesc(un >> 2, 6 - (un & 3)));
          wg_commit();
          wg_wait<1>();
          fence_regs<20>(o);
          if (warp != 9) STEPT(12 + nu * 8);
          const bool unsafe = !(o[16] >= LSUM_MIN && o[16] <= LSUM_MAX && o[18] >= LSUM_MIN && o[18] <= LSUM_MAX);
          if (__any_sync(0xffffffffu, unsafe)) redo |= 1 << u;
          else store_o(o, u);
          wg_wait<0>();
          fence_regs<32>(s);
        }
      }
      if (warp != 9) STEPT(31);
      if (bar_red_or(1 + wg, 128, redo)) {
#pragma unroll 1
        for (int ul = units; ul != 8; ul >>= 4) {
          const int u = ul & 7;
          if (!bar_red_or(1 + wg, 128, redo >> u & 1)) continue;
          const int h = u >> 2, qb = 3 - (u & 3);
          uint32_t qf[8], p[16];
          float o[20], m0 = -INFINITY, m1 = -INFINITY;
          load_q(qf, u);
#pragma unroll
          for (int i = 0; i < 20; i++) o[i] = 0.f;
#pragma unroll 1
          for (int j = 0; j <= (rb == 0 ? qb : 4); j++) {
            const int b = qb + 4 - j;
            float s[32];
            wg_fence();
            qk64(s, qf, kdesc(h, b));
            wg_commit();
            wg_wait<0>();
            fence_regs<32>(s);
            float mx0 = m0, mx1 = m1;
#pragma unroll
            for (int c = 0; c < 8; c++) {
#pragma unroll
              for (int i = 0; i < 4; i++) {
                const int diff = j * 64 + (16 * wi + g + (i >> 1) * 8) - (8 * c + 2 * q + (i & 1));
                if (diff < 0 || diff > 255) s[4 * c + i] = -INFINITY;
              }
              mx0 = fmaxf(mx0, fmaxf(s[4 * c], s[4 * c + 1]));
              mx1 = fmaxf(mx1, fmaxf(s[4 * c + 2], s[4 * c + 3]));
            }
            mx0 = fmaxf(mx0, __shfl_xor_sync(0xffffffffu, mx0, 1)); mx1 = fmaxf(mx1, __shfl_xor_sync(0xffffffffu, mx1, 1));
            mx0 = fmaxf(mx0, __shfl_xor_sync(0xffffffffu, mx0, 2)); mx1 = fmaxf(mx1, __shfl_xor_sync(0xffffffffu, mx1, 2));
            const float r0 = j == 0 ? 0.f : ex2(m0 - mx0), r1 = j == 0 ? 0.f : ex2(m1 - mx1);
            m0 = mx0; m1 = mx1;
#pragma unroll
            for (int i = 0; i < 5; i++) { o[4 * i] *= r0; o[4 * i + 1] *= r0; o[4 * i + 2] *= r1; o[4 * i + 3] *= r1; }
#pragma unroll
            for (int c = 0; c < 8; c++) { s[4 * c] -= m0; s[4 * c + 1] -= m0; s[4 * c + 2] -= m1; s[4 * c + 3] -= m1; }
            exp_pack<8>(s, p);
            fence_regs<20>(o); fence_regs_u<16>(p);
            wg_fence();
            pv32(o, p, vdesc(h, b)); pv32(o, p + 8, vdesc(h, b) + 2 * VSTEP);
            wg_commit();
            wg_wait<0>();
            fence_regs<20>(o);
          }
          named_bar(1 + wg, 128);
          if (redo >> u & 1) store_o(o, u);
          __syncwarp();
        }
      }
      if (wi == 0) PROF(6 + wg);
    }
    pass_v = pass + 1;
  }
}

}

typedef CUresult (*EncodeFn)(CUtensorMap*, CUtensorMapDataType, cuuint32_t, void*, const cuuint64_t*, const cuuint64_t*,
                             const cuuint32_t*, const cuuint32_t*, CUtensorMapInterleave, CUtensorMapSwizzle,
                             CUtensorMapL2promotion, CUtensorMapFloatOOBfill);
static EncodeFn g_encode = nullptr;
struct Dim { uint64_t size, stride; uint32_t box; };
template <int N> static CUtensorMap make_map(const void* ptr, const Dim (&d)[N], int swizzle) {
  CUtensorMap m;
  cuuint64_t dims[N], strides[N];
  cuuint32_t box[N], es[N];
  for (int i = 0; i < N; i++) { dims[i] = d[i].size; strides[i] = d[i].stride; box[i] = d[i].box; es[i] = 1; }
  g_encode(&m, CU_TENSOR_MAP_DATA_TYPE_BFLOAT16, N, const_cast<void*>(ptr), dims, strides + 1, box, es, CU_TENSOR_MAP_INTERLEAVE_NONE,
           swizzle == 128 ? CU_TENSOR_MAP_SWIZZLE_128B : (swizzle == 64 ? CU_TENSOR_MAP_SWIZZLE_64B : CU_TENSOR_MAP_SWIZZLE_NONE),
           swizzle ? CU_TENSOR_MAP_L2_PROMOTION_L2_256B : CU_TENSOR_MAP_L2_PROMOTION_L2_128B, CU_TENSOR_MAP_FLOAT_OOB_FILL_NONE);
  return m;
}
static CUtensorMap map2(const void* ptr, uint64_t inner, uint64_t outer, uint32_t bi, uint32_t bo, int swizzle) {
  const Dim d[2] = {{inner, 0, bi}, {outer, inner * 2, bo}};
  return make_map(ptr, d, swizzle);
}
template <class T> static void* sym_addr(T& sym) { void* p = nullptr; cudaGetSymbolAddress(&p, sym); return p; }

static Params h_p, h_p_helper;
static const void* h_key[9];
static bool h_helpers_fit = true;

static cudaLaunchConfig_t launch_cfg(int grid, cudaLaunchAttribute* at) {
  cudaLaunchConfig_t cfg = {};
  cfg.gridDim = dim3(grid); cfg.blockDim = dim3(512); cfg.dynamicSmemBytes = SMEM_BYTES; cfg.stream = cudaStreamPerThread;
  at[0].id = cudaLaunchAttributeClusterDimension;
  at[0].val.clusterDim.x = 2; at[0].val.clusterDim.y = 1; at[0].val.clusterDim.z = 1;
  cfg.attrs = at; cfg.numAttrs = 1;
  return cfg;
}

extern "C" void kernel_launch(void* const* d_in, const int* in_sizes, int n_in, void* d_out, int out_size) {
  const bf16* x = (const bf16*)d_in[0];
  const bf16* wqkv = (const bf16*)d_in[1];
  const bf16* wo = (const bf16*)d_in[2];
  cudaLaunchAttribute at[1];
  bool fresh = g_encode != nullptr && h_key[8] == d_out;
  for (int i = 0; i < 8; i++) fresh = fresh && h_key[i] == d_in[i];
  if (!fresh) {
    if (!g_encode) {
      void* fn = nullptr;
      cudaDriverEntryPointQueryResult st;
      cudaGetDriverEntryPoint("cuTensorMapEncodeTiled", &fn, cudaEnableDefault, &st);
      g_encode = (EncodeFn)fn;
      cudaFuncSetAttribute(mega_kernel, cudaFuncAttributeMaxDynamicSharedMemorySize, SMEM_BYTES);
      cudaLaunchConfig_t cfg = launch_cfg(132, at);
      int nclusters = 0;
      if (cudaOccupancyMaxActiveClusters(&nclusters, mega_kernel, &cfg) != cudaSuccess) { nclusters = 0; (void)cudaGetLastError(); }
      h_helpers_fit = nclusters >= 66;
    }
    bf16* x1 = (bf16*)sym_addr(g_x1);
    Params& p = h_p;
    p.x = x; p.wqkv = wqkv; p.wo = wo; p.w_r = (const bf16*)d_in[4]; p.w_g = (const bf16*)d_in[5]; p.w_u = (const bf16*)d_in[6]; p.w_d = (const bf16*)d_in[7];
    p.out = (bf16*)d_out;
    p.mapA[0] = map2(x, DM, SEQ, 64, 256, 128);
    p.mapA[1] = map2(x1, DM, SEQ, 64, 256, 128);
    { const Dim d[3] = {{DM, 0, 64}, {DM, 3 * DM * 2, 32}, {3, DM * 2, 3}}; p.mapW = make_map(wqkv, d, 128); }
    { const Dim d[3] = {{DM, 0, 64}, {64, DM * 2, 32}, {16, 64 * DM * 2, 2}}; p.mapWo = make_map(wo, d, 128); }
    p.mapRes[0] = map2(x, DM, SEQ, 64, 64, 128);
    p.mapRes[1] = p.mapXst[0] = map2(x1, DM, SEQ, 64, 64, 128);
    p.mapXst[1] = map2(d_out, DM, SEQ, 64, 64, 128);
    p.mapG = map2(p.w_g, FF, DM, 56, 128, 0);
    p.mapU = map2(p.w_u, FF, DM, 56, 128, 0);
    { const Dim d[3] = {{64, 0, 64}, {FF, DM * 2, 28}, {DM / 64, 128, 8}}; p.mapD = make_map(p.w_d, d, 128); }
    p.helper_first = 128;
    h_p_helper = p;
    h_p_helper.helper_first = 0;
    for (int i = 0; i < 8; i++) h_key[i] = d_in[i];
    h_key[8] = d_out;
  }
  if (!h_helpers_fit) {
    void* ah[] = {&h_p_helper};
    cudaLaunchConfig_t cfg = launch_cfg(4, at);
    cudaLaunchKernelExC(&cfg, (const void*)mega_kernel, ah);
  }
  void* a0[] = {&h_p};
  cudaLaunchConfig_t cfg = launch_cfg(h_helpers_fit ? 132 : 128, at);
  cudaLaunchKernelExC(&cfg, (const void*)mega_kernel, a0);
}
```

```cpp
#include <cuda_runtime.h>
#include <cuda_bf16.h>
#include <cuda.h>
#include <stdint.h>

namespace {

constexpr int SEQ = 2048, DM = 1024, FF = 3584;
constexpr float LN_EPS = 1e-5f;
typedef __nv_bfloat16 bf16;

__device__ __align__(1024) uint8_t g_kv[3 * 16 * 65536];
__device__ __align__(1024) uint8_t g_o[SEQ * DM * 2];
__device__ __align__(1024) bf16 g_x1[SEQ * DM];
__device__ unsigned g_epoch;
struct __align__(128) Flag { unsigned v[32]; };
__device__ Flag g_kvflag[3][16][2], g_oflag[8][2][16], g_xflag[16][8];
__device__ uint4 g_rowab[2][SEQ];
__device__ __align__(16) uint32_t g_vw[2][8][3 * DM];
constexpr uint32_t SENT = 0xFFFFFFFFu;
__device__ uint4 g_part[2][8 * SEQ];
__device__ uint4 g_slot[2][16 * 8];
__device__ uint4 g_cand[2][16 * 128];
__device__ uint4 g_ypart[2][128 * DM / 4];
__device__ uint4 g_x2row[128 * 2];
__device__ float2 g_rowln[8][SEQ];
__device__ int g_sel[2];

#define PROFL(l, e)
#define PROF(e) PROFL(layer, e)
#define STEPT(i)
#define SPIN_LIMIT 4000000u
__device__ __forceinline__ uint32_t smem_u32(const void* p) { return (uint32_t)__cvta_generic_to_shared(p); }
__device__ __forceinline__ void mbar_init(uint32_t bar, uint32_t cnt) {
  asm volatile("mbarrier.init.shared::cta.b64 [%0], %1;" ::"r"(bar), "r"(cnt) : "memory");
}
#define ELECT "{\n.reg .pred e;\nelect.sync _|e, 0xffffffff;\n@e "
__device__ __forceinline__ void mbar_expect_tx(uint32_t bar, uint32_t bytes) {
  asm volatile(ELECT "mbarrier.arrive.expect_tx.shared::cta.b64 _, [%0], %1;\n}" ::"r"(bar), "r"(bytes) : "memory");
}
__device__ __forceinline__ void mbar_arrive(uint32_t bar) {
  asm volatile("mbarrier.arrive.shared::cta.b64 _, [%0];" ::"r"(bar) : "memory");
}
__device__ __forceinline__ void mbar_arrive_e(uint32_t bar) {
  asm volatile(ELECT "mbarrier.arrive.shared::cta.b64 _, [%0];\n}" ::"r"(bar) : "memory");
}
__device__ __forceinline__ uint32_t mapa(uint32_t addr, uint32_t cta) {
  uint32_t r; asm("mapa.shared::cluster.u32 %0, %1, %2;" : "=r"(r) : "r"(addr), "r"(cta)); return r;
}
__device__ __forceinline__ void mbar_arrive_cluster(uint32_t bar, uint32_t cta) {
  asm volatile("mbarrier.arrive.shared::cluster.b64 _, [%0];" ::"r"(mapa(bar, cta)) : "memory");
}
#define MBAR_WAIT_ASM(QUAL)                                                                                                \
  asm volatile("{\n.reg .pred p;\n.reg .u32 n;\nmov.u32 n, 0;\nWAIT_LOOP:\n.pragma \"nounroll\";\n"                         \
               "mbarrier.try_wait.parity" QUAL ".shared::cta.b64 p, [%0], %1;\n@p bra WAIT_DONE;\n"                        \
               "add.u32 n, n, 1;\nsetp.lt.u32 p, n, %2;\n@p bra WAIT_LOOP;\nWAIT_DONE:\n}" ::"r"(bar), "r"(parity), "n"(SPIN_LIMIT) : "memory")
__device__ __forceinline__ void mbar_wait(uint32_t bar, uint32_t parity) { MBAR_WAIT_ASM(""); }
__device__ __forceinline__ void mbar_wait_cluster(uint32_t bar, uint32_t parity) { MBAR_WAIT_ASM(".acquire.cluster"); }
__device__ __forceinline__ bool mbar_wait_brief(uint32_t bar, uint32_t parity) {
  uint32_t ok;
  asm volatile("{\n.reg .pred p;\nmbarrier.try_wait.parity.shared::cta.b64 p, [%1], %2, 1000;\nselp.u32 %0, 1, 0, p;\n}"
               : "=r"(ok) : "r"(bar), "r"(parity) : "memory");
  return __all_sync(0xffffffffu, ok);
}
__device__ __forceinline__ void st_async2(uint32_t addr, float a, float b, uint32_t bar) {
  asm volatile("st.async.weak.shared::cluster.mbarrier::complete_tx::bytes.v2.f32 [%0], {%1, %2}, [%3];"
               ::"r"(addr), "f"(a), "f"(b), "r"(bar) : "memory");
}
__device__ __forceinline__ uint64_t policy_evict_first() {
  uint64_t p; asm volatile("createpolicy.fractional.L2::evict_first.b64 %0, 1.0;" : "=l"(p)); return p;
}
__device__ __forceinline__ uint64_t policy_normal() {
  uint64_t p; asm volatile("createpolicy.fractional.L2::evict_normal.b64 %0, 1.0;" : "=l"(p)); return p;
}
__device__ __forceinline__ void tma_load2(uint32_t dst, const CUtensorMap* m, int c0, int c1, uint32_t bar) {
  asm volatile(ELECT "cp.async.bulk.tensor.2d.shared::cluster.global.mbarrier::complete_tx::bytes [%0], [%1, {%3, %4}], [%2];\n}"
               ::"r"(dst), "l"(m), "r"(bar), "r"(c0), "r"(c1) : "memory");
}
__device__ __forceinline__ void tma_load2_h(uint32_t dst, const CUtensorMap* m, int c0, int c1, uint32_t bar, uint64_t pol) {
  asm volatile(ELECT "cp.async.bulk.tensor.2d.shared::cluster.global.mbarrier::complete_tx::bytes.L2::cache_hint [%0], [%1, {%3, %4}], [%2], %5;\n}"
               ::"r"(dst), "l"(m), "r"(bar), "r"(c0), "r"(c1), "l"(pol) : "memory");
}
__device__ __forceinline__ void tma_load3(uint32_t dst, const CUtensorMap* m, int c0, int c1, int c2, uint32_t bar) {
  asm volatile(ELECT "cp.async.bulk.tensor.3d.shared::cluster.global.mbarrier::complete_tx::bytes [%0], [%1, {%3, %4, %5}], [%2];\n}"
               ::"r"(dst), "l"(m), "r"(bar), "r"(c0), "r"(c1), "r"(c2) : "memory");
}
__device__ __forceinline__ void tma_load3_h(uint32_t dst, const CUtensorMap* m, int c0, int c1, int c2, uint32_t bar, uint64_t pol) {
  asm volatile(ELECT "cp.async.bulk.tensor.3d.shared::cluster.global.mbarrier::complete_tx::bytes.L2::cache_hint [%0], [%1, {%3, %4, %5}], [%2], %6;\n}"
               ::"r"(dst), "l"(m), "r"(bar), "r"(c0), "r"(c1), "r"(c2), "l"(pol) : "memory");
}
__device__ __forceinline__ void tma_load3_mc(uint32_t dst, const CUtensorMap* m, int c0, int c1, int c2, uint32_t bar) {
  asm volatile(ELECT "cp.async.bulk.tensor.3d.shared::cluster.global.mbarrier::complete_tx::bytes.multicast::cluster [%0], [%1, {%3, %4, %5}], [%2], %6;\n}"
               ::"r"(dst), "l"(m), "r"(bar), "r"(c0), "r"(c1), "r"(c2), "h"((uint16_t)3) : "memory");
}
__device__ __forceinline__ void bulk_push(uint32_t dst, uint32_t src, uint32_t bytes, uint32_t bar) {
  asm volatile(ELECT "cp.async.bulk.shared::cluster.shared::cta.mbarrier::complete_tx::bytes [%0], [%1], %2, [%3];\n}"
               ::"r"(dst), "r"(src), "r"(bytes), "r"(bar) : "memory");
}
template <int N> __device__ __forceinline__ void regs_inc() { asm volatile("setmaxnreg.inc.sync.aligned.u32 %0;" ::"n"(N)); }
template <int N> __device__ __forceinline__ void regs_dec() { asm volatile("setmaxnreg.dec.sync.aligned.u32 %0;" ::"n"(N)); }
__device__ __forceinline__ void tma_prefetch2(const CUtensorMap* m, int c0, int c1) {
  asm volatile(ELECT "cp.async.bulk.prefetch.tensor.2d.L2.global [%0, {%1, %2}];\n}" ::"l"(m), "r"(c0), "r"(c1) : "memory");
}
__device__ __forceinline__ void bulk_prefetch(const void* p, uint32_t bytes) {
  asm volatile(ELECT "cp.async.bulk.prefetch.L2.global [%0], %1;\n}" ::"l"(p), "r"(bytes) : "memory");
}
__device__ __forceinline__ void tma_store(const CUtensorMap* m, uint32_t src, int c0, int c1) {
  asm volatile(ELECT "cp.async.bulk.tensor.2d.global.shared::cta.bulk_group [%0, {%2, %3}], [%1];\n}"
               ::"l"(m), "r"(src), "r"(c0), "r"(c1) : "memory");
}
__device__ __forceinline__ void bulk_load(uint32_t dst, const void* src, uint32_t bytes, uint32_t bar) {
  asm volatile(ELECT "cp.async.bulk.shared::cluster.global.mbarrier::complete_tx::bytes [%0], [%1], %2, [%3];\n}"
               ::"r"(dst), "l"(src), "r"(bytes), "r"(bar) : "memory");
}
__device__ __forceinline__ void bulk_load_h(uint32_t dst, const void* src, uint32_t bytes, uint32_t bar, uint64_t pol) {
  asm volatile(ELECT "cp.async.bulk.shared::cluster.global.mbarrier::complete_tx::bytes.L2::cache_hint [%0], [%1], %2, [%3], %4;\n}"
               ::"r"(dst), "l"(src), "r"(bytes), "r"(bar), "l"(pol) : "memory");
}
__device__ __forceinline__ void bulk_store(void* dst, uint32_t src, uint32_t bytes) {
  asm volatile(ELECT "cp.async.bulk.global.shared::cta.bulk_group [%0], [%1], %2;\n}" ::"l"(dst), "r"(src), "r"(bytes) : "memory");
}
__device__ __forceinline__ void bulk_commit() { asm volatile("cp.async.bulk.commit_group;" ::: "memory"); }
__device__ __forceinline__ void bulk_wait_all() { asm volatile("cp.async.bulk.wait_group 0;" ::: "memory"); }
__device__ __forceinline__ void fence_async_smem() { asm volatile("fence.proxy.async.shared::cta;" ::: "memory"); }
__device__ __forceinline__ void fence_async_global() { asm volatile("fence.proxy.async.global;" ::: "memory"); }
__device__ __forceinline__ void fence_release() { asm volatile("fence.release.gpu;" ::: "memory"); }
__device__ __forceinline__ void l2_prefetch_line(const void* p) { asm volatile("prefetch.global.L2 [%0];" ::"l"(p) : "memory"); }
__device__ __forceinline__ void prefetch_tmap(const CUtensorMap* m) { asm volatile("prefetch.tensormap [%0];" ::"l"(m) : "memory"); }
__device__ __forceinline__ void named_bar(int id, int n) { asm volatile("bar.sync %0, %1;" ::"r"(id), "r"(n) : "memory"); }
__device__ __forceinline__ bool bar_red_or(int id, int n, bool v) {
  uint32_t r;
  asm volatile("{\n.reg .pred p, q;\nsetp.ne.u32 q, %3, 0;\nbarrier.cta.red.or.pred p, %1, %2, q;\nselp.u32 %0, 1, 0, p;\n}"
               : "=r"(r) : "r"(id), "r"(n), "r"((uint32_t)v) : "memory");
  return r != 0;
}
__device__ __forceinline__ void cluster_arrive() { asm volatile("barrier.cluster.arrive.relaxed.aligned;" ::: "memory"); }
__device__ __forceinline__ void cluster_wait() { asm volatile("barrier.cluster.wait.aligned;" ::: "memory"); }
__device__ __forceinline__ uint32_t cluster_rank() { uint32_t r; asm volatile("mov.u32 %0, %%cluster_ctarank;" : "=r"(r)); return r; }
__device__ __forceinline__ unsigned ld_relaxed(const unsigned* p) {
  unsigned v; asm volatile("ld.relaxed.gpu.global.u32 %0, [%1];" : "=r"(v) : "l"(p) : "memory"); return v;
}
__device__ __forceinline__ uint4 ld_relaxed4(const uint4* p) {
  uint4 v; asm volatile("ld.relaxed.gpu.global.v4.u32 {%0, %1, %2, %3}, [%4];" : "=r"(v.x), "=r"(v.y), "=r"(v.z), "=r"(v.w) : "l"(p) : "memory"); return v;
}
__device__ __forceinline__ void st_relaxed(unsigned* p, unsigned v) {
  asm volatile("st.relaxed.gpu.global.u32 [%0], %1;" ::"l"(p), "r"(v) : "memory");
}
__device__ __forceinline__ uint2 ld_relaxed2(const void* p) {
  uint2 v; asm volatile("ld.relaxed.gpu.global.v2.u32 {%0, %1}, [%2];" : "=r"(v.x), "=r"(v.y) : "l"(p) : "memory"); return v;
}
__device__ __forceinline__ void st_relaxed4(uint4* p, uint4 v) {
  asm volatile("st.relaxed.gpu.global.v4.u32 [%0], {%1, %2, %3, %4};" ::"l"(p), "r"(v.x), "r"(v.y), "r"(v.z), "r"(v.w) : "memory");
}
__device__ __forceinline__ bool valid4(uint4 v) { return v.x != SENT && v.y != SENT && v.z != SENT && v.w != SENT; }
__device__ __forceinline__ uint4 poll4(const uint4* p) {
  uint4 v;
  uint32_t spins = 0;
#pragma unroll 1
  do { v = ld_relaxed4(p); } while (!valid4(v) && ++spins < SPIN_LIMIT);
  return v;
}
__device__ __forceinline__ void set_flag(unsigned* p, unsigned tag) {
  asm volatile(ELECT "st.release.gpu.global.u32 [%0], %1;\n}" ::"l"(p), "r"(tag) : "memory");
}
__device__ __forceinline__ void poll_flag(const unsigned* p, unsigned tag) {
#pragma unroll 1
  for (uint32_t spins = 0; !__all_sync(0xffffffffu, ld_relaxed(p) == tag) && spins < SPIN_LIMIT; spins++) {}
  asm volatile("fence.acquire.gpu;" ::: "memory");
}
__device__ __forceinline__ uint32_t enc(float x) { return __float_as_uint(x + 0.0f) ^ 0x80000000u; }
__device__ __forceinline__ float dec(uint32_t u) { return __uint_as_float(u ^ 0x80000000u); }
__device__ __forceinline__ uint32_t f2u(float x) { uint32_t u = __float_as_uint(x); return u == SENT ? 0x7FFFFFFFu : u; }
__device__ __forceinline__ uint32_t nosent(uint32_t u) { return u == SENT ? 0x7FFF7FFFu : u; }
__device__ __forceinline__ uint32_t hadd_bf2(uint32_t a, uint32_t b) {
  uint32_t r; asm("add.rn.bf16x2 %0, %1, %2;" : "=r"(r) : "r"(a), "r"(b)); return r;
}
__device__ __forceinline__ uint32_t hsub_bf2(uint32_t a, uint32_t b) {
  uint32_t r; asm("sub.rn.bf16x2 %0, %1, %2;" : "=r"(r) : "r"(a), "r"(b)); return r;
}
__device__ __forceinline__ void wg_fence() { asm volatile("wgmma.fence.sync.aligned;" ::: "memory"); }
__device__ __forceinline__ void wg_commit() { asm volatile("wgmma.commit_group.sync.aligned;" ::: "memory"); }
template <int N> __device__ __forceinline__ void wg_wait() { asm volatile("wgmma.wait_group.sync.aligned %0;" ::"n"(N) : "memory"); }
template <int R> __device__ __forceinline__ void fence_regs(float* d) {
#pragma unroll
  for (int i = 0; i < R; i++) asm volatile("" : "+f"(d[i])::"memory");
}
template <int R> __device__ __forceinline__ void fence_regs_u(uint32_t* d) {
#pragma unroll
  for (int i = 0; i < R; i++) asm volatile("" : "+r"(d[i])::"memory");
}
__host__ __device__ constexpr uint32_t dlo(uint32_t addr, uint32_t lbo) { return ((addr & 0x3FFFF) >> 4) | ((lbo >> 4) << 16); }
constexpr uint32_t H128 = 0x40000040u, H64 = 0x80000020u;
__device__ __forceinline__ void stsm_x4(uint32_t addr, uint32_t r0, uint32_t r1, uint32_t r2, uint32_t r3) {
  asm volatile("stmatrix.sync.aligned.m8n8.x4.shared.b16 [%0], {%1, %2, %3, %4};"
               ::"r"(addr), "r"(r0), "r"(r1), "r"(r2), "r"(r3) : "memory");
}
__device__ __forceinline__ void ldsm_x4(uint32_t addr, uint32_t& r0, uint32_t& r1, uint32_t& r2, uint32_t& r3) {
  asm volatile("ldmatrix.sync.aligned.m8n8.x4.shared.b16 {%0, %1, %2, %3}, [%4];"
               : "=r"(r0), "=r"(r1), "=r"(r2), "=r"(r3) : "r"(addr) : "memory");
}
__device__ __forceinline__ void ldsm_x4_t(uint32_t addr, uint32_t& r0, uint32_t& r1, uint32_t& r2, uint32_t& r3) {
  asm volatile("ldmatrix.sync.aligned.m8n8.x4.trans.shared.b16 {%0, %1, %2, %3}, [%4];"
               : "=r"(r0), "=r"(r1), "=r"(r2), "=r"(r3) : "r"(addr) : "memory");
}
__device__ __forceinline__ void mma_16816(float* d, uint32_t a0, uint32_t a1, uint32_t a2, uint32_t a3, uint32_t b0, uint32_t b1) {
  asm volatile("mma.sync.aligned.m16n8k16.row.col.f32.bf16.bf16.f32 {%0, %1, %2, %3}, {%4, %5, %6, %7}, {%8, %9}, {%0, %1, %2, %3};"
               : "+f"(d[0]), "+f"(d[1]), "+f"(d[2]), "+f"(d[3]) : "r"(a0), "r"(a1), "r"(a2), "r"(a3), "r"(b0), "r"(b1));
}
__device__ __forceinline__ void spin_cycles(int n) {
  const int t0 = (int)clock();
#pragma unroll 1
  while ((int)clock() - t0 < n) {}
}
__device__ __forceinline__ uint32_t pack_bf16(float lo, float hi) {
  uint32_t r; asm("cvt.rn.bf16x2.f32 %0, %1, %2;" : "=r"(r) : "f"(hi), "f"(lo)); return r;
}
__device__ __forceinline__ float bf_lo(uint32_t v) { return __uint_as_float(v << 16); }
__device__ __forceinline__ float bf_hi(uint32_t v) { return __uint_as_float(v & 0xffff0000u); }
__device__ __forceinline__ float rbf(float x) { return __bfloat162float(__float2bfloat16_rn(x)); }
__device__ __forceinline__ float ex2(float x) { float y; asm("ex2.approx.ftz.f32 %0, %1;" : "=f"(y) : "f"(x)); return y; }
__device__ __forceinline__ uint32_t shl_clamp(uint32_t v, uint32_t n) {
  uint32_t r; asm("shl.b32 %0, %1, %2;" : "=r"(r) : "r"(v), "r"(n)); return r;
}
__device__ __forceinline__ float warp_sum(float v) {
#pragma unroll
  for (int o = 16; o > 0; o >>= 1) v += __shfl_xor_sync(0xffffffffu, v, o);
  return v;
}
__device__ __forceinline__ float ln_inv(float var) {
  float r;
  asm("sqrt.approx.ftz.f32 %0, %1;" : "=f"(r) : "f"(rbf(rbf(var) + LN_EPS)));
  asm("rcp.approx.ftz.f32 %0, %1;" : "=f"(r) : "f"(rbf(r)));
  return r;
}
__device__ __forceinline__ uint32_t ln_pair(uint32_t x, uint32_t mean2, float inv) {
  const uint32_t d = hsub_bf2(x, mean2);
  return pack_bf16(bf_lo(d) * inv, bf_hi(d) * inv);
}
__device__ __forceinline__ uint32_t add_ln_pair(uint32_t x, uint32_t mean2, float inv) { return hadd_bf2(x, ln_pair(x, mean2, inv)); }
__device__ __forceinline__ uint32_t router_key(float r_bf, int row) {
  uint32_t u = __float_as_uint(r_bf);
  u = (u & 0x80000000u) ? ~u : (u | 0x80000000u);
  return (u & 0xFFFF0000u) | 0x8000u | (uint32_t)(SEQ - 1 - row);
}

template <uint32_t HA = 0x40000040u, uint32_t HB = 0x40000040u>
__device__ __forceinline__ void wg_ss192t(float* d, uint32_t da, uint32_t db, int scale_d) {
  asm volatile("{\n.reg .pred p;\n.reg .b64 dA, dB;\nmov.b64 dA, {%96, %99};\nmov.b64 dB, {%97, %100};\nsetp.ne.b32 p, %98, 0;\n"
    "wgmma.mma_async.sync.aligned.m64n192k16.f32.bf16.bf16 "
    "{%0, %1, %2, %3, %4, %5, %6, %7, %8, %9, %10, %11, %12, %13, %14, %15, "
    "%16, %17, %18, %19, %20, %21, %22, %23, %24, %25, %26, %27, %28, %29, %30, %31, "
    "%32, %33, %34, %35, %36, %37, %38, %39, %40, %41, %42, %43, %44, %45, %46, %47, "
    "%48, %49, %50, %51, %52, %53, %54, %55, %56, %57, %58, %59, %60, %61, %62, %63, "
    "%64, %65, %66, %67, %68, %69, %70, %71, %72, %73, %74, %75, %76, %77, %78, %79, "
    "%80, %81, %82, %83, %84, %85, %86, %87, %88, %89, %90, %91, %92, %93, %94, %95}, "
    "dA, dB, p, 1, 1, 0, 1;\n}\n"
    : "+f"(d[0]), "+f"(d[1]), "+f"(d[2]), "+f"(d[3]), "+f"(d[4]), "+f"(d[5]), "+f"(d[6]), "+f"(d[7]),
      "+f"(d[8]), "+f"(d[9]), "+f"(d[10]), "+f"(d[11]), "+f"(d[12]), "+f"(d[13]), "+f"(d[14]), "+f"(d[15]),
      "+f"(d[16]), "+f"(d[17]), "+f"(d[18]), "+f"(d[19]), "+f"(d[20]), "+f"(d[21]), "+f"(d[22]), "+f"(d[23]),
      "+f"(d[24]), "+f"(d[25]), "+f"(d[26]), "+f"(d[27]), "+f"(d[28]), "+f"(d[29]), "+f"(d[30]), "+f"(d[31]),
      "+f"(d[32]), "+f"(d[33]), "+f"(d[34]), "+f"(d[35]), "+f"(d[36]), "+f"(d[37]), "+f"(d[38]), "+f"(d[39]),
      "+f"(d[40]), "+f"(d[41]), "+f"(d[42]), "+f"(d[43]), "+f"(d[44]), "+f"(d[45]), "+f"(d[46]), "+f"(d[47]),
      "+f"(d[48]), "+f"(d[49]), "+f"(d[50]), "+f"(d[51]), "+f"(d[52]), "+f"(d[53]), "+f"(d[54]), "+f"(d[55]),
      "+f"(d[56]), "+f"(d[57]), "+f"(d[58]), "+f"(d[59]), "+f"(d[60]), "+f"(d[61]), "+f"(d[62]), "+f"(d[63]),
      "+f"(d[64]), "+f"(d[65]), "+f"(d[66]), "+f"(d[67]), "+f"(d[68]), "+f"(d[69]), "+f"(d[70]), "+f"(d[71]),
      "+f"(d[72]), "+f"(d[73]), "+f"(d[74]), "+f"(d[75]), "+f"(d[76]), "+f"(d[77]), "+f"(d[78]), "+f"(d[79]),
      "+f"(d[80]), "+f"(d[81]), "+f"(d[82]), "+f"(d[83]), "+f"(d[84]), "+f"(d[85]), "+f"(d[86]), "+f"(d[87]),
      "+f"(d[88]), "+f"(d[89]), "+f"(d[90]), "+f"(d[91]), "+f"(d[92]), "+f"(d[93]), "+f"(d[94]), "+f"(d[95])
    : "r"(da), "r"(db), "r"(scale_d), "n"(HA), "n"(HB));
}
template <uint32_t HA = 0x40000040u, uint32_t HB = 0x40000040u>
__device__ __forceinline__ void wg_ss192t_z(float* d, uint32_t da, uint32_t db) {
  asm volatile("{\n.reg .pred p;\n.reg .b64 dA, dB;\nmov.b64 dA, {%96, %98};\nmov.b64 dB, {%97, %99};\nsetp.ne.b32 p, 0, 0;\n"
    "wgmma.mma_async.sync.aligned.m64n192k16.f32.bf16.bf16 "
    "{%0, %1, %2, %3, %4, %5, %6, %7, %8, %9, %10, %11, %12, %13, %14, %15, "
    "%16, %17, %18, %19, %20, %21, %22, %23, %24, %25, %26, %27, %28, %29, %30, %31, "
    "%32, %33, %34, %35, %36, %37, %38, %39, %40, %41, %42, %43, %44, %45, %46, %47, "
    "%48, %49, %50, %51, %52, %53, %54, %55, %56, %57, %58, %59, %60, %61, %62, %63, "
    "%64, %65, %66, %67, %68, %69, %70, %71, %72, %73, %74, %75, %76, %77, %78, %79, "
    "%80, %81, %82, %83, %84, %85, %86, %87, %88, %89, %90, %91, %92, %93, %94, %95}, "
    "dA, dB, p, 1, 1, 0, 1;\n}\n"
    : "=f"(d[0]), "=f"(d[1]), "=f"(d[2]), "=f"(d[3]), "=f"(d[4]), "=f"(d[5]), "=f"(d[6]), "=f"(d[7]),
      "=f"(d[8]), "=f"(d[9]), "=f"(d[10]), "=f"(d[11]), "=f"(d[12]), "=f"(d[13]), "=f"(d[14]), "=f"(d[15]),
      "=f"(d[16]), "=f"(d[17]), "=f"(d[18]), "=f"(d[19]), "=f"(d[20]), "=f"(d[21]), "=f"(d[22]), "=f"(d[23]),
      "=f"(d[24]), "=f"(d[25]), "=f"(d[26]), "=f"(d[27]), "=f"(d[28]), "=f"(d[29]), "=f"(d[30]), "=f"(d[31]),
      "=f"(d[32]), "=f"(d[33]), "=f"(d[34]), "=f"(d[35]), "=f"(d[36]), "=f"(d[37]), "=f"(d[38]), "=f"(d[39]),
      "=f"(d[40]), "=f"(d[41]), "=f"(d[42]), "=f"(d[43]), "=f"(d[44]), "=f"(d[45]), "=f"(d[46]), "=f"(d[47]),
      "=f"(d[48]), "=f"(d[49]), "=f"(d[50]), "=f"(d[51]), "=f"(d[52]), "=f"(d[53]), "=f"(d[54]), "=f"(d[55]),
      "=f"(d[56]), "=f"(d[57]), "=f"(d[58]), "=f"(d[59]), "=f"(d[60]), "=f"(d[61]), "=f"(d[62]), "=f"(d[63]),
      "=f"(d[64]), "=f"(d[65]), "=f"(d[66]), "=f"(d[67]), "=f"(d[68]), "=f"(d[69]), "=f"(d[70]), "=f"(d[71]),
      "=f"(d[72]), "=f"(d[73]), "=f"(d[74]), "=f"(d[75]), "=f"(d[76]), "=f"(d[77]), "=f"(d[78]), "=f"(d[79]),
      "=f"(d[80]), "=f"(d[81]), "=f"(d[82]), "=f"(d[83]), "=f"(d[84]), "=f"(d[85]), "=f"(d[86]), "=f"(d[87]),
      "=f"(d[88]), "=f"(d[89]), "=f"(d[90]), "=f"(d[91]), "=f"(d[92]), "=f"(d[93]), "=f"(d[94]), "=f"(d[95])
    : "r"(da), "r"(db), "n"(HA), "n"(HB));
}
template <uint32_t HA = 0x40000040u, uint32_t HB = 0x40000040u>
__device__ __forceinline__ void wg_ss128t(float* d, uint32_t da, uint32_t db, int scale_d) {
  asm volatile("{\n.reg .pred p;\n.reg .b64 dA, dB;\nmov.b64 dA, {%64, %67};\nmov.b64 dB, {%65, %68};\nsetp.ne.b32 p, %66, 0;\n"
    "wgmma.mma_async.sync.aligned.m64n128k16.f32.bf16.bf16 "
    "{%0, %1, %2, %3, %4, %5, %6, %7, %8, %9, %10, %11, %12, %13, %14, %15, "
    "%16, %17, %18, %19, %20, %21, %22, %23, %24, %25, %26, %27, %28, %29, %30, %31, "
    "%32, %33, %34, %35, %36, %37, %38, %39, %40, %41, %42, %43, %44, %45, %46, %47, "
    "%48, %49, %50, %51, %52, %53, %54, %55, %56, %57, %58, %59, %60, %61, %62, %63}, "
    "dA, dB, p, 1, 1, 0, 1;\n}\n"
    : "+f"(d[0]), "+f"(d[1]), "+f"(d[2]), "+f"(d[3]), "+f"(d[4]), "+f"(d[5]), "+f"(d[6]), "+f"(d[7]),
      "+f"(d[8]), "+f"(d[9]), "+f"(d[10]), "+f"(d[11]), "+f"(d[12]), "+f"(d[13]), "+f"(d[14]), "+f"(d[15]),
      "+f"(d[16]), "+f"(d[17]), "+f"(d[18]), "+f"(d[19]), "+f"(d[20]), "+f"(d[21]), "+f"(d[22]), "+f"(d[23]),
      "+f"(d[24]), "+f"(d[25]), "+f"(d[26]), "+f"(d[27]), "+f"(d[28]), "+f"(d[29]), "+f"(d[30]), "+f"(d[31]),
      "+f"(d[32]), "+f"(d[33]), "+f"(d[34]), "+f"(d[35]), "+f"(d[36]), "+f"(d[37]), "+f"(d[38]), "+f"(d[39]),
      "+f"(d[40]), "+f"(d[41]), "+f"(d[42]), "+f"(d[43]), "+f"(d[44]), "+f"(d[45]), "+f"(d[46]), "+f"(d[47]),
      "+f"(d[48]), "+f"(d[49]), "+f"(d[50]), "+f"(d[51]), "+f"(d[52]), "+f"(d[53]), "+f"(d[54]), "+f"(d[55]),
      "+f"(d[56]), "+f"(d[57]), "+f"(d[58]), "+f"(d[59]), "+f"(d[60]), "+f"(d[61]), "+f"(d[62]), "+f"(d[63])
    : "r"(da), "r"(db), "r"(scale_d), "n"(HA), "n"(HB));
}
template <uint32_t HB = 0x40000040u>
__device__ __forceinline__ void wg_rs64(float* d, uint32_t a0, uint32_t a1, uint32_t a2, uint32_t a3, uint32_t db, int scale_d) {
  asm volatile("{\n.reg .pred p;\n.reg .b64 dB;\nmov.b64 dB, {%36, %38};\nsetp.ne.b32 p, %37, 0;\n"
    "wgmma.mma_async.sync.aligned.m64n64k16.f32.bf16.bf16 "
    "{%0, %1, %2, %3, %4, %5, %6, %7, %8, %9, %10, %11, %12, %13, %14, %15, "
    "%16, %17, %18, %19, %20, %21, %22, %23, %24, %25, %26, %27, %28, %29, %30, %31}, "
    "{%32, %33, %34, %35}, dB, p, 1, 1, 0;\n}\n"
    : "+f"(d[0]), "+f"(d[1]), "+f"(d[2]), "+f"(d[3]), "+f"(d[4]), "+f"(d[5]), "+f"(d[6]), "+f"(d[7]),
      "+f"(d[8]), "+f"(d[9]), "+f"(d[10]), "+f"(d[11]), "+f"(d[12]), "+f"(d[13]), "+f"(d[14]), "+f"(d[15]),
      "+f"(d[16]), "+f"(d[17]), "+f"(d[18]), "+f"(d[19]), "+f"(d[20]), "+f"(d[21]), "+f"(d[22]), "+f"(d[23]),
      "+f"(d[24]), "+f"(d[25]), "+f"(d[26]), "+f"(d[27]), "+f"(d[28]), "+f"(d[29]), "+f"(d[30]), "+f"(d[31])
    : "r"(a0), "r"(a1), "r"(a2), "r"(a3), "r"(db), "r"(scale_d), "n"(HB));
}
template <uint32_t HB = 0x40000040u>
__device__ __forceinline__ void wg_rs64_z(float* d, uint32_t a0, uint32_t a1, uint32_t a2, uint32_t a3, uint32_t db) {
  asm volatile("{\n.reg .pred p;\n.reg .b64 dB;\nmov.b64 dB, {%36, %37};\nsetp.ne.b32 p, 0, 0;\n"
    "wgmma.mma_async.sync.aligned.m64n64k16.f32.bf16.bf16 "
    "{%0, %1, %2, %3, %4, %5, %6, %7, %8, %9, %10, %11, %12, %13, %14, %15, "
    "%16, %17, %18, %19, %20, %21, %22, %23, %24, %25, %26, %27, %28, %29, %30, %31}, "
    "{%32, %33, %34, %35}, dB, p, 1, 1, 0;\n}\n"
    : "=f"(d[0]), "=f"(d[1]), "=f"(d[2]), "=f"(d[3]), "=f"(d[4]), "=f"(d[5]), "=f"(d[6]), "=f"(d[7]),
      "=f"(d[8]), "=f"(d[9]), "=f"(d[10]), "=f"(d[11]), "=f"(d[12]), "=f"(d[13]), "=f"(d[14]), "=f"(d[15]),
      "=f"(d[16]), "=f"(d[17]), "=f"(d[18]), "=f"(d[19]), "=f"(d[20]), "=f"(d[21]), "=f"(d[22]), "=f"(d[23]),
      "=f"(d[24]), "=f"(d[25]), "=f"(d[26]), "=f"(d[27]), "=f"(d[28]), "=f"(d[29]), "=f"(d[30]), "=f"(d[31])
    : "r"(a0), "r"(a1), "r"(a2), "r"(a3), "r"(db), "n"(HB));
}
template <uint32_t HB = 0x40000040u>
__device__ __forceinline__ void wg_rs32(float* d, uint32_t a0, uint32_t a1, uint32_t a2, uint32_t a3, uint32_t db, int scale_d) {
  asm volatile("{\n.reg .pred p;\n.reg .b64 dB;\nmov.b64 dB, {%20, %22};\nsetp.ne.b32 p, %21, 0;\n"
    "wgmma.mma_async.sync.aligned.m64n32k16.f32.bf16.bf16 "
    "{%0, %1, %2, %3, %4, %5, %6, %7, %8, %9, %10, %11, %12, %13, %14, %15}, "
    "{%16, %17, %18, %19}, dB, p, 1, 1, 0;\n}\n"
    : "+f"(d[0]), "+f"(d[1]), "+f"(d[2]), "+f"(d[3]), "+f"(d[4]), "+f"(d[5]), "+f"(d[6]), "+f"(d[7]),
      "+f"(d[8]), "+f"(d[9]), "+f"(d[10]), "+f"(d[11]), "+f"(d[12]), "+f"(d[13]), "+f"(d[14]), "+f"(d[15])
    : "r"(a0), "r"(a1), "r"(a2), "r"(a3), "r"(db), "r"(scale_d), "n"(HB));
}
template <uint32_t HB = 0x40000040u>
__device__ __forceinline__ void wg_rs32_z(float* d, uint32_t a0, uint32_t a1, uint32_t a2, uint32_t a3, uint32_t db) {
  asm volatile("{\n.reg .pred p;\n.reg .b64 dB;\nmov.b64 dB, {%20, %21};\nsetp.ne.b32 p, 0, 0;\n"
    "wgmma.mma_async.sync.aligned.m64n32k16.f32.bf16.bf16 "
    "{%0, %1, %2, %3, %4, %5, %6, %7, %8, %9, %10, %11, %12, %13, %14, %15}, "
    "{%16, %17, %18, %19}, dB, p, 1, 1, 0;\n}\n"
    : "=f"(d[0]), "=f"(d[1]), "=f"(d[2]), "=f"(d[3]), "=f"(d[4]), "=f"(d[5]), "=f"(d[6]), "=f"(d[7]),
      "=f"(d[8]), "=f"(d[9]), "=f"(d[10]), "=f"(d[11]), "=f"(d[12]), "=f"(d[13]), "=f"(d[14]), "=f"(d[15])
    : "r"(a0), "r"(a1), "r"(a2), "r"(a3), "r"(db), "n"(HB));
}
template <uint32_t HB = 0x40000040u>
__device__ __forceinline__ void wg_rs40t(float* d, uint32_t a0, uint32_t a1, uint32_t a2, uint32_t a3, uint32_t db, int scale_d) {
  asm volatile("{\n.reg .pred p;\n.reg .b64 dB;\nmov.b64 dB, {%24, %26};\nsetp.ne.b32 p, %25, 0;\n"
    "wgmma.mma_async.sync.aligned.m64n40k16.f32.bf16.bf16 "
    "{%0, %1, %2, %3, %4, %5, %6, %7, %8, %9, %10, %11, %12, %13, %14, %15, "
    "%16, %17, %18, %19}, "
    "{%20, %21, %22, %23}, dB, p, 1, 1, 1;\n}\n"
    : "+f"(d[0]), "+f"(d[1]), "+f"(d[2]), "+f"(d[3]), "+f"(d[4]), "+f"(d[5]), "+f"(d[6]), "+f"(d[7]),
      "+f"(d[8]), "+f"(d[9]), "+f"(d[10]), "+f"(d[11]), "+f"(d[12]), "+f"(d[13]), "+f"(d[14]), "+f"(d[15]),
      "+f"(d[16]), "+f"(d[17]), "+f"(d[18]), "+f"(d[19])
    : "r"(a0), "r"(a1), "r"(a2), "r"(a3), "r"(db), "r"(scale_d), "n"(HB));
}
template <uint32_t HB = 0x40000040u>
__device__ __forceinline__ void wg_rs40t_z(float* d, uint32_t a0, uint32_t a1, uint32_t a2, uint32_t a3, uint32_t db) {
  asm volatile("{\n.reg .pred p;\n.reg .b64 dB;\nmov.b64 dB, {%24, %25};\nsetp.ne.b32 p, 0, 0;\n"
    "wgmma.mma_async.sync.aligned.m64n40k16.f32.bf16.bf16 "
    "{%0, %1, %2, %3, %4, %5, %6, %7, %8, %9, %10, %11, %12, %13, %14, %15, "
    "%16, %17, %18, %19}, "
    "{%20, %21, %22, %23}, dB, p, 1, 1, 1;\n}\n"
    : "=f"(d[0]), "=f"(d[1]), "=f"(d[2]), "=f"(d[3]), "=f"(d[4]), "=f"(d[5]), "=f"(d[6]), "=f"(d[7]),
      "=f"(d[8]), "=f"(d[9]), "=f"(d[10]), "=f"(d[11]), "=f"(d[12]), "=f"(d[13]), "=f"(d[14]), "=f"(d[15]),
      "=f"(d[16]), "=f"(d[17]), "=f"(d[18]), "=f"(d[19])
    : "r"(a0), "r"(a1), "r"(a2), "r"(a3), "r"(db), "n"(HB));
}

constexpr uint32_t SOFF = 1024;
constexpr int STG = 57344, QE = 28672, SL_W = 16384, SL_HD = 12288, SL_F = 3 * STG, AT_ST = 131072;
constexpr int OFF_ONES = 4 * STG;
constexpr int OFF_PATCH = OFF_ONES + 1024;
constexpr int OFF_CS = OFF_PATCH + 768;
constexpr int OFF_BAR = OFF_CS + 768;
constexpr int OFF_MISC = OFF_BAR + 416;
constexpr int SMEM_BYTES = OFF_MISC + 96;
enum { B_FULL = 0, B_EMPTY = 6, B_HALO = 12, B_CS = 15, B_KVREADY, B_QDONE = B_KVREADY + 2, B_QREADY, B_OST, B_ADONE = B_OST + 2,
       B_QFREE, B_WS, B_WFULL, B_WEMPTY = B_WFULL + 4, B_GU = B_WEMPTY + 4, B_RES = B_GU + 2, B_DN,
       B_HX = B_DN + 2, B_RST, B_WGO, B_UNIT = B_WGO + 2, B_COUNT = B_UNIT + 8 };
static_assert(B_COUNT <= 52, "barrier area");
__host__ __device__ constexpr int bar_count(int i) {
  return i >= B_EMPTY && i < B_HALO ? 17 : i == B_CS ? 4 : i == B_QFREE ? 16
       : i == B_KVREADY || i == B_KVREADY + 1 || i == B_QREADY ? 8 : i == B_ADONE ? 32 : i == B_OST ? 2 : i >= B_UNIT ? 4
       : i == B_QDONE || (i >= B_WEMPTY && i < B_GU) ? 16 : i == B_RST ? 4 : i == B_RES ? 2 : 1;
}
enum { M_KEY = 0, M_MEAN, M_INV, M_WSUM, M_TAG, M_SEL0, M_PMEAN, M_PINV, M_XQ = 8, M_KEYS = 12, M_PROG = 20 };
constexpr int FFN_PIECE = 14336;
constexpr int T_XS = 163840, T_HP = T_XS + 1024;
constexpr float LSUM_MIN = 5.421010862427522e-20f, LSUM_MAX = 1.8446744073709552e19f;
constexpr float SM_C = 0.17677669529663687f * 1.4426950408889634f;
constexpr uint32_t VSTEP = 64u - (64u << 16);
#define FFN_POL policy_evict_first()
#define D_SPLIT 1
#define WS1_AT 0
#define WS1_PACE 1000
#define WS_AT 5
#define WS_PACE 1000
#define GUB_PACE 800
#define HOLD_K 0
#define PROG 1
#define ULIST1 0x854
#define ULIST2 0x8721
#define RES_K 3
#define REL_NOW 0
#define FAKE 0
#define X_STAGGER 500
#define GU_PACE1 1600
#define GU_PACE 2500
#define DELAY_P 600
#define DELAY_S 2000
#define DELAY_Y 700

struct Params {
  CUtensorMap mapA[2], mapW, mapWo, mapRes[2], mapXst[2], mapG, mapU, mapD, mapWs;
  const bf16 *x, *wqkv, *wo, *w_r, *w_g, *w_u, *w_d;
  bf16* out;
};

template <int N> __device__ __forceinline__ void exp_pack(const float* s, uint32_t* p) {
#pragma unroll
  for (int b = 0; b < N; b++) {
    p[2 * b] = pack_bf16(ex2(s[4 * b]), ex2(s[4 * b + 1]));
    p[2 * b + 1] = pack_bf16(ex2(s[4 * b + 2]), ex2(s[4 * b + 3]));
  }
}
template <int KIND> __device__ __forceinline__ void edge16(const float* sd, const float* st, uint32_t* pd, uint32_t* pt, int dl, uint32_t mt) {
  if (KIND == 0) { exp_pack<2>(sd, pd); pt[0] = pt[1] = pt[2] = pt[3] = 0; }
  else if (KIND == 1) { exp_pack<2>(st, pt); pd[0] = pd[1] = pd[2] = pd[3] = 0; }
  else {
    const uint32_t a = pack_bf16(ex2(dl >= 0 ? sd[0] : st[0]), ex2(dl >= 1 ? sd[1] : st[1]));
    const uint32_t c = pack_bf16(ex2(dl >= 0 ? sd[6] : st[6]), ex2(dl >= 1 ? sd[7] : st[7]));
    pd[0] = a & ~mt; pt[0] = a & mt; pd[3] = c & ~mt; pt[3] = c & mt;
    pd[1] = pack_bf16(ex2(sd[2]), ex2(sd[3])); pt[1] = 0;
    pt[2] = pack_bf16(ex2(st[4]), ex2(st[5])); pd[2] = 0;
  }
}
__device__ __forceinline__ void edge32(const float* sd, const float* st, uint32_t* pd, uint32_t* pt, int rel, int dl, uint32_t mt) {
  if (rel > 1) { edge16<0>(sd, st, pd, pt, dl, mt); edge16<0>(sd + 8, st + 8, pd + 4, pt + 4, dl, mt); }
  else if (rel == 1) { edge16<0>(sd, st, pd, pt, dl, mt); edge16<2>(sd + 8, st + 8, pd + 4, pt + 4, dl, mt); }
  else if (rel == 0) { edge16<2>(sd, st, pd, pt, dl, mt); edge16<1>(sd + 8, st + 8, pd + 4, pt + 4, dl, mt); }
  else { edge16<1>(sd, st, pd, pt, dl, mt); edge16<1>(sd + 8, st + 8, pd + 4, pt + 4, dl, mt); }
}
__device__ __forceinline__ void qk64(float* s, const uint32_t* qf, uint32_t kd) {
  wg_rs64_z<H64>(s, qf[0], qf[1], qf[2], qf[3], kd);
  wg_rs64<H64>(s, qf[4], qf[5], qf[6], qf[7], kd + 2, 1);
}
__device__ __forceinline__ void qk32x2(float* a, float* b, const uint32_t* qf, uint32_t ka, uint32_t kb) {
  wg_rs32_z<H64>(a, qf[0], qf[1], qf[2], qf[3], ka); wg_rs32_z<H64>(b, qf[0], qf[1], qf[2], qf[3], kb);
  wg_rs32<H64>(a, qf[4], qf[5], qf[6], qf[7], ka + 2, 1); wg_rs32<H64>(b, qf[4], qf[5], qf[6], qf[7], kb + 2, 1);
}
__device__ __forceinline__ void pv32(float* o, const uint32_t* p, uint32_t vd) {
  wg_rs40t<H64>(o, p[0], p[1], p[2], p[3], vd, 1);
  wg_rs40t<H64>(o, p[4], p[5], p[6], p[7], vd + VSTEP, 1);
}

__device__ __forceinline__ void fma8(float* d, uint4 w, float x) {
  d[0] += x * bf_lo(w.x); d[1] += x * bf_hi(w.x); d[2] += x * bf_lo(w.y); d[3] += x * bf_hi(w.y);
  d[4] += x * bf_lo(w.z); d[5] += x * bf_hi(w.z); d[6] += x * bf_lo(w.w); d[7] += x * bf_hi(w.w);
}

__device__ __forceinline__ int fresh_tid() { int r; asm volatile("mov.u32 %0, %%tid.x;" : "=r"(r)); return r; }
__device__ __forceinline__ int fresh_bid() { int r; asm volatile("mov.u32 %0, %%ctaid.x;" : "=r"(r)); return r; }
#define PHASE_IDS                                                                                                              \
  const uint32_t sbase = smem_u32(smem);                                                                                       \
  const int tid = fresh_tid(), bid = fresh_bid();                                                                              \
  const int warp = __shfl_sync(0xffffffffu, tid >> 5, 0), lane = tid & 31;                                                     \
  const int rank = bid & 1, cl = bid >> 1, rb = bid & 7, hp = bid >> 3;                  \
  const int mb = 2 * rb + (hp >> 3), nb = hp & 7;                                            \
  const int wg = warp >> 2, wi = warp & 3, g = lane >> 2, q = lane & 3;                                                        \
  const int mi = lane >> 3, srow = wi * 16 + (mi & 1) * 8 + (lane & 7);      \
  auto bar = [&](int i) { return sbase + OFF_BAR + 8 * i; };                                                                   \
  volatile uint32_t* s_misc = (volatile uint32_t*)(smem + OFF_MISC);                                                           \
  auto load_w = [&](int s, int kt) {                           \
    tma_load3_mc(sbase + s * QE + SL_W + rank * 6144, &P.mapW, hp * 64, kt * 32 + rank * 16, 0, bar(B_FULL + s));              \
  };                                                                                                                           \
  auto load_a = [&](int s, int kt, int layer) { mbar_expect_tx(bar(B_FULL + s), QE); tma_load2(sbase + s * QE, &P.mapA[layer], kt * 32, rb * 256, bar(B_FULL + s)); }; \
  auto load_wo = [&](int k) {                                                 \
    mbar_expect_tx(bar(B_WFULL + (k & 3)), 32768);                                                                             \
    tma_load3_mc(sbase + (k & 3) * 32768 + 16384 + rank * 8192, &P.mapWo, nb * 128 + rank * 64, (k >> 3) * 32, (k & 7) * 2, bar(B_WFULL + (k & 3))); \
  };                                                                                                                           \
  auto load_o = [&](int k) {                                                            \
    bulk_load(sbase + (k & 3) * 32768, g_o + (size_t)(mb * 16 + k) * 16384, 16384, bar(B_WFULL + (k & 3)));                    \
  };                                                                                                                           \
  auto import_halo = [&](int layer, int h) {                                   \
    poll_flag(&g_kvflag[(rb - 1) >> 1][hp][h].v[layer], s_misc[M_TAG]);                                                        \
    fence_async_global();                                                                                                      \
    const uint8_t* src = g_kv + (size_t)(((rb - 1) >> 1) * 16 + hp) * 65536 + h * 32768;                                       \
    mbar_expect_tx(bar(B_HALO + 2 * h), 16384 << h);                                                                           \
    bulk_load_h(sbase + (h ? 65536 : 16384), src + (h ? 0 : 16384), 16384 << h, bar(B_HALO + 2 * h), policy_evict_first());    \
    if (h == 0) { mbar_expect_tx(bar(B_HALO + 1), 16384); bulk_load_h(sbase, src, 16384, bar(B_HALO + 1), policy_evict_first()); } \
  };                                                                                                                           \
  auto load_res = [&](int half, int layer) {                                                  \
    mbar_expect_tx(bar(B_RES), 16384);                                                                                         \
    tma_load2(sbase + AT_ST + half * 16384, &P.mapRes[layer], nb * 128, mb * 128 + half * 64, bar(B_RES));                     \
    tma_load2(sbase + AT_ST + half * 16384 + 8192, &P.mapRes[layer], nb * 128 + 64, mb * 128 + half * 64, bar(B_RES));         \
  };                                                                                                                           \
  auto store_tile = [&](int layer, int skip, bool wait) {                                           \
    _Pragma("unroll 1")                                                                                                        \
    for (int j = 0; j < 4; j++)                                                                                                \
      if ((j & 1) != skip) tma_store(&P.mapXst[layer], sbase + AT_ST + (j & 1) * 16384 + (j >> 1) * 8192, nb * 128 + (j >> 1) * 64, mb * 128 + (j & 1) * 64); \
    bulk_commit();                                                                                                             \
    if (wait) bulk_wait_all();                                                                                                 \
  };                                                                                                                           \
  auto load_ws = [&](int pace) {                                    \
    mbar_expect_tx(bar(B_WS), 4 * SL_HD);                                                                                      \
    _Pragma("unroll 1")                                                                                                        \
    for (int j = 0; j < 4; j++) {                                                                                              \
      tma_load3(sbase + SL_F + j * SL_HD, &P.mapWs, hp * 64, rb * 128 + j * 32, 0, bar(B_WS));                                 \
      if (pace) spin_cycles(pace);                                                                                             \
    }                                                                                                                          \
  };                                                                                                                           \
  auto load_gu = [&](int half, int pace) {                             \
    mbar_expect_tx(bar(B_GU + half), 4 * FFN_PIECE);                                                                           \
    _Pragma("unroll 1")                                                                                                        \
    for (int j = 0; j < 4; j++) {                                                                                              \
      tma_load2_h(sbase + SL_F + j * FFN_PIECE, &P.mapG + (j >> 1), cl * 56, rank * 512 + half * 256 + (j & 1) * 128, bar(B_GU + half), FFN_POL); \
      if (j < 3) spin_cycles(pace);                                                                                            \
    }                                                                                                                          \
  };                                                                                                                           \
  auto fetch_gu = [&](uint32_t* a, int ks, int ct) {                 \
    ldsm_x4_t(sbase + SL_F + (mi & 1) * 2 * FFN_PIECE + (ks * 16 + (mi >> 1) * 8 + (lane & 7)) * 112 + ct * 16, a[0], a[1], a[2], a[3]); \
  };                                                                                                                           \
  auto send_gu = [&](float gate, float up, int ct, int part) {        \
    const int u = 8 * ct + g, own = u >= 28;                                                                                   \
    if (q == 0) st_async2(mapa(sbase + T_HP + ((rank * 5 + part) * 28 + u - 28 * own) * 8, own), gate, up, mapa(bar(B_HX), own)); \
  };                                                                                                                           \
  auto hidden = [&]() {                                     \
    const float2* hpart = (const float2*)(smem + T_HP) + min(lane, 27);                                                        \
    float gs[2] = {0.f, 0.f}, us[2] = {0.f, 0.f};                                                                              \
    _Pragma("unroll")                                                                                                          \
    for (int j = 0; j < 10; j++) { const float2 v = hpart[j * 28]; gs[j & 1] += v.x; us[j & 1] += v.y; }                       \
    const float gb = rbf(gs[0] + gs[1]), ub = rbf(us[0] + us[1]);                                                              \
    return lane < 28 ? rbf(__fdividef(gb, 1.f + __expf(-gb))) * ub : 0.f;                                                      \
  };                                                                                                                           \
  (void)load_wo; (void)load_o; (void)import_halo; (void)load_res; (void)store_tile; (void)fetch_gu; (void)load_ws; (void)load_gu; (void)send_gu; (void)hidden; (void)cl; (void)mb; (void)nb; (void)wg; (void)g; (void)q; (void)srow; (void)s_misc; (void)load_w; (void)load_a;

__global__ void __launch_bounds__(512, 1) mega_kernel(const __grid_constant__ Params P) {
  extern __shared__ __align__(1024) uint8_t smem[];
  {
    PHASE_IDS
    if (warp == 0) {
      if (lane == 0) {
        prefetch_tmap(&P.mapA[0]); prefetch_tmap(&P.mapW);
#pragma unroll
        for (int i = 0; i < 6; i++) mbar_init(bar(B_FULL + i), 1);
        asm volatile("fence.mbarrier_init.release.cluster;" ::: "memory");
      }
      __syncwarp();
      load_a(0, 0, 0);
    } else if (tid == 32) {
#pragma unroll
      for (int i = 6; i < B_COUNT; i++) mbar_init(bar(i), bar_count(i));
      asm volatile("fence.mbarrier_init.release.cluster;" ::: "memory");
    } else if (warp == 8) {
      ((uint4*)(smem + OFF_ONES))[lane] = make_uint4(0x3F803F80u, 0x3F803F80u, 0x3F803F80u, 0x3F803F80u);
      ((uint4*)(smem + OFF_ONES))[lane + 32] = make_uint4(0x3F803F80u, 0x3F803F80u, 0x3F803F80u, 0x3F803F80u);
    }
    __syncwarp();
    cluster_arrive(); cluster_wait();
    if (warp == 0) {
#pragma unroll 1
      for (int i = 0; i < 6; i++) { load_w(i, i); if (i) load_a(i, i, 0); }
      PROFL(0, 1);
    } else if (warp == 1) {
      if (lane < 16) g_rowab[0][rb * 256 + hp * 16 + lane] = make_uint4(0, 0, 0, 0);
    } else if (warp == 2) {
      const int f = lane >> 1;
      Flag* fl = f < 2 ? &g_kvflag[rb >> 1][hp][f] : f < 4 ? &g_oflag[rb][f & 1][hp] : &g_xflag[mb][nb];
      if (f < 5 && (f >= 2 || (rank == 1 && rb < 7))) ((uint4*)fl)[lane & 1] = make_uint4(0, 0, 0, 0);
    } else if (tid == 96) {
      if ((sbase & 0x3FFFF) != SOFF) __trap();
#pragma unroll 1
      for (int i = 1; i < 12; i++) prefetch_tmap(&P.mapA[0] + i);
    }
    __syncwarp();
  }

  regs_dec<120>();
#pragma unroll 1
  for (unsigned pass_v = 0;;) {
    const unsigned pass = __shfl_sync(0xffffffffu, pass_v, 0);
    if (__shfl_sync(0xffffffffu, fresh_tid() >> 8, 0)) {
      if (pass > 0) {
        const unsigned layer = pass - 1;
        uint32_t xr[32];
        {
          PHASE_IDS
          float acc[64];
#pragma unroll
          for (int i = 0; i < 64; i++) acc[i] = 0.f;
          const uint32_t da0 = dlo(SOFF, 16) + (wg - 2) * 256;
          constexpr uint32_t db0 = dlo(SOFF + 16384, 8192);
#pragma unroll 1
          for (int k4 = 0; k4 < 4; k4++) {
#pragma unroll
            for (int st = 0; st < 4; st++) {
              mbar_wait(bar(B_WFULL + st), k4 & 1);
              wg_fence();
#pragma unroll
              for (int kk = 0; kk < 4; kk++)
                wg_ss128t<H64, H128>(acc, da0 + ((st * 32768) >> 4) + (kk >> 1) * 512 + (kk & 1) * 2, db0 + ((st * 32768) >> 4) + kk * 128, 1);
              wg_commit();
              if (st == 0 && k4 == 0 && warp == 9) PROF(10);
              if (warp == 9) STEPT(16 + k4 * 4 + st);
              if (REL_NOW) {
                if (st < 3 || k4 < 3) wg_wait<0>();
                if (lane < 2 && (st < 2 || k4 < 3)) mbar_arrive_cluster(bar(B_WEMPTY + st), lane);
              } else {
                wg_wait<1>();
                if (lane < 2 && (st == 0 ? k4 > 0 : (st < 3 || k4 < 3))) mbar_arrive_cluster(bar(B_WEMPTY + ((st + 3) & 3)), lane);
              }
            }
          }
          mbar_wait(bar(B_RES), layer);
          mbar_wait(bar(B_RST), layer);
          const uint32_t zoff = AT_ST + (wg - 2) * 16384;
#pragma unroll
          for (int j = 0; j < 8; j++)
            ldsm_x4(sbase + zoff + srow * 128 + (j >> 2) * 8192 + ((((2 * j + (mi >> 1)) & 7) ^ (srow & 7)) << 4), xr[4 * j], xr[4 * j + 1], xr[4 * j + 2], xr[4 * j + 3]);
          wg_wait<0>();
          fence_regs<64>(acc);
          if (warp == 9) PROF(11);
          if (layer == 0 && lane < 2) mbar_arrive_cluster(bar(B_QFREE), lane);
#pragma unroll
          for (int j = 0; j < 32; j++) xr[j] = hadd_bf2(xr[j], pack_bf16(acc[2 * j], acc[2 * j + 1]));
        }
        PHASE_IDS
        const uint32_t tag = s_misc[M_TAG];
        const int grow = mb * 128 + (warp - 8) * 16 + g;
        {
          float d[6][4];
#pragma unroll
          for (int i = 0; i < 6; i++) d[i][0] = d[i][1] = d[i][2] = d[i][3] = 0.f;
          const uint4* tab = (const uint4*)(smem + OFF_PATCH + (g == 1 ? q * 64 : (g == 0 ? 256 : 320)));
#pragma unroll
          for (int j2 = 0; j2 < 4; j2++) {
            const uint4 w = tab[j2];
#pragma unroll
            for (int jj = 0; jj < 2; jj++) {
              const uint32_t* a = &xr[8 * j2 + 4 * jj];
              mma_16816(d[jj], a[0], a[1], a[2], a[3], jj ? w.z : w.x, jj ? w.w : w.y);
              mma_16816(d[2 + jj], a[0], a[1], a[2], a[3], a[0], a[2]);
              mma_16816(d[4 + jj], a[0], a[1], a[2], a[3], a[1], a[3]);
            }
          }
          const float sq0 = __shfl_sync(0xffffffffu, (g & 1) ? d[2][1] + d[3][1] : d[2][0] + d[3][0], g * 4 + (g >> 1));
          const float sq1 = __shfl_sync(0xffffffffu, (g & 1) ? d[4][3] + d[5][3] : d[4][2] + d[5][2], g * 4 + (g >> 1));
          uint4* dst = &g_part[layer][nb * SEQ + grow];
          if (q == 0) {
            st_relaxed4(dst, make_uint4(__float_as_uint(d[0][0] + d[1][0]), __float_as_uint(sq0), __float_as_uint(d[0][1] + d[1][1]), tag));
            st_relaxed4(dst + 8, make_uint4(__float_as_uint(d[0][2] + d[1][2]), __float_as_uint(sq1), __float_as_uint(d[0][3] + d[1][3]), tag));
          }
        }
        if (warp == 9) PROF(12);
        asm volatile("bar.arrive 6, 320;" ::: "memory");
        const int t_p = (int)clock();
        const uint32_t zrow = sbase + AT_ST + (wg - 2) * 16384 + srow * 128;
        if (layer == 0) {
#pragma unroll
          for (int j = 0; j < 8; j++)
            stsm_x4(zrow + (j >> 2) * 8192 + ((((2 * j + (mi >> 1)) & 7) ^ (srow & 7)) << 4), xr[4 * j], xr[4 * j + 1], xr[4 * j + 2], xr[4 * j + 3]);
          fence_async_smem();
          asm volatile("bar.arrive 8, 288;" ::: "memory");
        }
#pragma unroll 1
        while ((int)clock() - t_p < DELAY_P) {}
        {
          const uint4* src = &g_part[layer][2 * q * SEQ + grow];
          uint4 pp[4];
          uint32_t spins = 0;
#pragma unroll 1
          do {
            pp[0] = ld_relaxed4(src); pp[1] = ld_relaxed4(src + SEQ); pp[2] = ld_relaxed4(src + 8); pp[3] = ld_relaxed4(src + SEQ + 8);
          } while (!__all_sync(0xffffffffu, pp[0].w == tag && pp[1].w == tag && pp[2].w == tag && pp[3].w == tag) && ++spins < SPIN_LIMIT);
          if (warp == 9) PROF(13);
          const int rr = q >> 1;
          float s3[3];
#pragma unroll
          for (int c = 0; c < 3; c++) {
            const float lo = __uint_as_float(c == 0 ? pp[0].x : c == 1 ? pp[0].y : pp[0].z) + __uint_as_float(c == 0 ? pp[1].x : c == 1 ? pp[1].y : pp[1].z);
            const float hi = __uint_as_float(c == 0 ? pp[2].x : c == 1 ? pp[2].y : pp[2].z) + __uint_as_float(c == 0 ? pp[3].x : c == 1 ? pp[3].y : pp[3].z);
            s3[c] = (rr ? hi : lo) + __shfl_xor_sync(0xffffffffu, rr ? lo : hi, 2);
            s3[c] += __shfl_xor_sync(0xffffffffu, s3[c], 1);
          }
          const float mu = s3[0] * (1.f / DM), var = fmaxf(fmaf(-mu, mu, s3[1] * (1.f / DM)), 0.f);
          const float mn = rbf(mu), iv = ln_inv(var);
          const uint32_t ky = router_key(rbf((s3[2] - mn * __uint_as_float(s_misc[M_WSUM])) * iv), grow + 8 * rr);
          const uint32_t wbest = __reduce_max_sync(0xffffffffu, ky);
          s_misc[M_KEYS + warp - 8] = wbest;
          named_bar(5, 256);
          if (__reduce_max_sync(0xffffffffu, s_misc[M_KEYS + (lane & 7)]) == wbest) {
            if (nb == 0 && ky == wbest && (q & 1) == 0) st_relaxed4(&g_slot[layer][mb * 8], make_uint4(ky, __float_as_uint(mn), __float_as_uint(iv), tag));
            const int r = ~wbest & 15;
            if ((r & 7) == g) {
#pragma unroll
              for (int j = 0; j < 4; j++) {
                const uint32_t* a = &xr[8 * j];
                st_relaxed4(&g_cand[layer][mb * 128 + nb * 16 + q * 4 + j],
                            r < 8 ? make_uint4(nosent(a[0]), nosent(a[2]), nosent(a[4]), nosent(a[6])) : make_uint4(nosent(a[1]), nosent(a[3]), nosent(a[5]), nosent(a[7])));
              }
            }
            __syncwarp();
          }
          if (warp == 9) PROF(14);
          if (layer == 0) {
            if ((q & 1) == 0) {
              g_rowln[nb][grow + 8 * rr] = make_float2(mn, iv);
              if (warp - 8 == nb) {
                const float mu2 = mu + (mu - mn) * iv, inv2 = ln_inv(var * (1.f + iv) * (1.f + iv));
                st_relaxed4(&g_rowab[1][grow + 8 * rr], make_uint4(__float_as_uint((1.f + iv) * inv2), __float_as_uint((mn * iv + rbf(mu2)) * inv2), tag, 0));
              }
            }
            __syncwarp();
          } else {
            const float mo = __shfl_xor_sync(0xffffffffu, mn, 2), io = __shfl_xor_sync(0xffffffffu, iv, 2);
            const uint32_t m0 = pack_bf16(rr ? mo : mn, rr ? mo : mn), m1 = pack_bf16(rr ? mn : mo, rr ? mn : mo);
            const float i0 = rr ? io : iv, i1 = rr ? iv : io;
#pragma unroll
            for (int j = 0; j < 8; j++)
              stsm_x4(zrow + (j >> 2) * 8192 + ((((2 * j + (mi >> 1)) & 7) ^ (srow & 7)) << 4), add_ln_pair(xr[4 * j], m0, i0),
                      add_ln_pair(xr[4 * j + 1], m1, i1), add_ln_pair(xr[4 * j + 2], m0, i0), add_ln_pair(xr[4 * j + 3], m1, i1));
            fence_async_smem();
          }
          if (warp == 15) asm volatile("bar.arrive 7, 512;" ::: "memory");
        }
        if (warp < 15) {
          uint32_t gu[64];
          mbar_wait(bar(B_GU + 1), layer);
#pragma unroll
          for (int j = 0; j < 16; j++) fetch_gu(gu + 4 * j, j, warp - 8);
          fence_async_smem();
          float d[4][4] = {};
          named_bar(7, 512);
#pragma unroll
          for (int hf = 0; hf < 2; hf++) {
            uint4 xv[4] = {};
            if (g == 0) {
#pragma unroll
              for (int j = 0; j < 4; j++) xv[j] = ((const uint4*)(smem + T_XS))[32 + hf * 16 + j * 4 + q];
            }
            __syncwarp();
#pragma unroll
            for (int j = 0; j < 4; j++) {
              const uint32_t* a = gu + hf * 32 + j * 8;
              mma_16816(d[(j & 1) * 2], a[0], a[1], a[2], a[3], xv[j].x, xv[j].y);
              mma_16816(d[(j & 1) * 2 + 1], a[4], a[5], a[6], a[7], xv[j].z, xv[j].w);
            }
          }
          send_gu((d[0][0] + d[1][0]) + (d[2][0] + d[3][0]), (d[0][2] + d[1][2]) + (d[2][2] + d[3][2]), warp - 8, 4);
          __syncwarp();
        }
        if (layer == 0) asm volatile("bar.arrive 9, 512;" ::: "memory");
        else {
        uint32_t wd[64];
        mbar_wait(bar(B_DN), layer);
#pragma unroll
        for (int j = 0; j < 16; j++) {
          const uint32_t row = sbase + ((warp - 8) * 2 + (j >> 3)) * 3584 + min((j & 1) * 16 + (mi >> 1) * 8 + (lane & 7), 27) * 128;
          ldsm_x4_t(row + ((((j & 6) + (mi & 1)) ^ ((row >> 7) & 7)) << 4), wd[4 * j], wd[4 * j + 1], wd[4 * j + 2], wd[4 * j + 3]);
        }
        fence_regs_u<64>(wd);
        mbar_wait_cluster(bar(B_HX), layer);
        uint32_t hf[4];
        {
          const float hv = hidden();
          const uint32_t hp2 = pack_bf16(hv, __shfl_down_sync(0xffffffffu, hv, 1));
#pragma unroll
          for (int j = 0; j < 4; j++) hf[j] = __shfl_sync(0xffffffffu, hp2, 8 * j + 2 * q);
        }
        if (warp == 9) PROF(19);
        float y[4][4] = {};
#pragma unroll
        for (int j = 0; j < 16; j++)
          mma_16816(y[j & 3], wd[4 * j], wd[4 * j + 1], wd[4 * j + 2], wd[4 * j + 3], g == j >> 1 ? hf[(j & 1) * 2] : 0u, g == j >> 1 ? hf[(j & 1) * 2 + 1] : 0u);
        {
          float e[4];
#pragma unroll
          for (int c = 0; c < 4; c++) { const int i = (c & 1) * 2 + (c >> 1); e[c] = (y[0][i] + y[1][i]) + (y[2][i] + y[3][i]); }
          const bool b0 = g & 1, b1 = g & 2;
          float t0 = __shfl_xor_sync(0xffffffffu, b0 ? e[0] : e[1], 4), t1 = __shfl_xor_sync(0xffffffffu, b0 ? e[2] : e[3], 4);
          const float f0 = b0 ? t0 : e[0], f1 = b0 ? e[1] : t0, f2 = b0 ? t1 : e[2], f3 = b0 ? e[3] : t1;
          t0 = __shfl_xor_sync(0xffffffffu, b1 ? f0 : f2, 8); t1 = __shfl_xor_sync(0xffffffffu, b1 ? f1 : f3, 8);
          st_relaxed4(&g_ypart[layer][bid * 256 + (warp - 8) * 32 + (q * 4 + (g & 3)) * 2 + (g >> 2)],
                      b1 ? make_uint4(f2u(t0), f2u(t1), f2u(f2), f2u(f3)) : make_uint4(f2u(f0), f2u(f1), f2u(t0), f2u(t1)));
        }
        if (warp == 9) PROF(20);
        asm volatile("bar.arrive 9, 384;" ::: "memory");
        cluster_arrive(); cluster_wait();
        return;
        }
      }
      const unsigned layer = pass;
      named_bar(1 + (fresh_tid() >> 7), 128);
      regs_inc<224>();
      float acc[2][96];
      {
        PHASE_IDS
        const uint32_t da0 = dlo(SOFF, 16) + (wg - 2) * 256;
        constexpr uint32_t db0 = dlo(SOFF + SL_W, 2048);
        mbar_wait(bar(B_FULL), 0);
        if (warp == 9) PROF(29);
        if (warp == 9) STEPT(0);
        wg_fence();
        wg_ss192t_z<H64, H128>(acc[0], da0, db0); wg_ss192t_z<H64, H128>(acc[1], da0 + 512, db0);
        wg_ss192t<H64, H128>(acc[0], da0 + 2, db0 + 384, 1); wg_ss192t<H64, H128>(acc[1], da0 + 514, db0 + 384, 1);
        wg_commit();
        int s = 1, u = 0;
#pragma unroll 1
        for (int i = 1; i < 32; i++) {
          const uint32_t da = da0 + s * (QE >> 4), db = db0 + s * (QE >> 4);
          mbar_wait(bar(B_FULL + s), (u + (s > 1 ? layer : 0)) & 1);
          if (warp == 9 && !(i & 1)) STEPT(i >> 1);
          wg_fence();
          wg_ss192t<H64, H128>(acc[0], da, db, 1); wg_ss192t<H64, H128>(acc[1], da + 512, db, 1);
          wg_ss192t<H64, H128>(acc[0], da + 2, db + 384, 1); wg_ss192t<H64, H128>(acc[1], da + 514, db + 384, 1);
          wg_commit();
          wg_wait<1>();
          if (lane < 2 && i < 27) mbar_arrive_cluster(bar(B_EMPTY + (s == 0 ? 5 : s - 1)), lane);
          if (++s == 6) { s = 0; u++; }
        }
      }
      PHASE_IDS
      mbar_wait(bar(B_CS), layer);
      float pa[2][2], pb[2][2];
      {
        const uint32_t tag = s_misc[M_TAG];
        const uint4* src = &g_rowab[layer][rb * 256 + (wg - 2 + (lane >> 4) * 2) * 64 + wi * 16 + (lane & 15)];
        uint4 v;
        uint32_t spins = 0;
#pragma unroll 1
        do { v = ld_relaxed4(src); } while (!__all_sync(0xffffffffu, v.z == tag) && ++spins < SPIN_LIMIT);
#pragma unroll
        for (int j = 0; j < 4; j++) {
          pa[j >> 1][j & 1] = __uint_as_float(__shfl_sync(0xffffffffu, v.x, g + 8 * j));
          pb[j >> 1][j & 1] = __uint_as_float(__shfl_sync(0xffffffffu, v.y, g + 8 * j));
        }
      }
      const int prow = (int)s_misc[M_SEL0] - rb * 256;
      const bool patch = ((prow - (wg - 2) * 64 - wi * 16) & ~0x8F) == 0;
      const float* cs = (const float*)(smem + OFF_CS);
      auto finish = [&](int m, int b, float2 c, uint32_t* dst) {
        dst[0] = pack_bf16(acc[m][4 * b] * pa[m][0] - c.x * pb[m][0], acc[m][4 * b + 1] * pa[m][0] - c.y * pb[m][0]);
        dst[1] = pack_bf16(acc[m][4 * b + 2] * pa[m][1] - c.x * pb[m][1], acc[m][4 * b + 3] * pa[m][1] - c.y * pb[m][1]);
      };
      wg_wait<0>();
      fence_regs<96>(acc[0]); fence_regs<96>(acc[1]);
      if (warp != 9) STEPT(1);
      if (lane < 2) mbar_arrive_cluster(bar(B_QDONE), lane);
      if (warp == 9) PROF(2);
#pragma unroll
      for (int h = 0; h < 2; h++) {
        const uint32_t dst = sbase + (h * 8 + 2 + wg) * 8192 + srow * 64;
#pragma unroll
        for (int jj = 0; jj < 4; jj++) {
          const int b = 8 + (jj >> 1) * 8 + h * 4 + (jj & 1) * 2;
          const float2 c0 = *(const float2*)&cs[8 * b + 2 * q], c1 = *(const float2*)&cs[8 * b + 8 + 2 * q];
          uint32_t r[2][4];
#pragma unroll
          for (int m = 0; m < 2; m++) { finish(m, b, c0, r[m]); finish(m, b + 1, c1, r[m] + 2); }
          if (h == 0 && jj == 0) named_bar(5, 256);
#pragma unroll
          for (int m = 0; m < 2; m++)
            stsm_x4(dst + m * 16384 + (jj >> 1) * 4096 + ((((jj & 1) * 2 + (mi >> 1)) ^ ((srow >> 1) & 3)) << 4), r[m][0], r[m][1], r[m][2], r[m][3]);
        }
        if (patch) {
          __syncwarp();
          if (lane < 8)
            *(uint4*)(smem + (h * 8 + 4 + (prow >> 6)) * 8192 + g * 4096 + (prow & 63) * 64 + ((q ^ ((prow >> 1) & 3)) << 4)) =
                *(const uint4*)(smem + OFF_PATCH + 128 + g * 128 + h * 64 + q * 16);
        }
        fence_async_smem();
        __syncwarp();
        mbar_arrive_e(bar(B_KVREADY + h));
        if (warp != 9) STEPT(2 + h);
      }
#pragma unroll
      for (int j = 0; j < 4; j++) { pa[j >> 1][j & 1] *= SM_C; pb[j >> 1][j & 1] *= SM_C; }
#pragma unroll
      for (int jj = 0; jj < 4; jj++) {
        const float2 c0 = *(const float2*)&cs[16 * jj + 2 * q], c1 = *(const float2*)&cs[16 * jj + 8 + 2 * q];
#pragma unroll
        for (int m = 0; m < 2; m++) {
          uint32_t r[4];
          finish(m, 2 * jj, c0, r); finish(m, 2 * jj + 1, c1, r + 2);
          *(uint4*)(smem + AT_ST + ((jj >> 1) * 16 + warp - 8 + 8 * m) * 1024 + (jj & 1) * 512 + lane * 16) = make_uint4(r[0], r[1], r[2], r[3]);
        }
      }
      __syncwarp();
      if (patch) {
        *(uint32_t*)(smem + AT_ST + ((lane >> 4) * 16 + (prow >> 4)) * 1024 + (mi & 1) * 512 + ((prow & 7) * 4 + q) * 16 + ((g & 1) * 2 + ((prow >> 3) & 1)) * 4) =
            *(const uint32_t*)(smem + OFF_PATCH + lane * 4);
        __syncwarp();
      }
      if (warp == 9) PROF(3);
      mbar_arrive_e(bar(B_QREADY));
      regs_dec<120>();
    } else {
      if (pass > 0) {
        const unsigned layer = pass - 1;
        PHASE_IDS
        const uint32_t tag = s_misc[M_TAG];
        if (warp == 7) {
              uint32_t* tab = (uint32_t*)(smem + OFF_PATCH);
#pragma unroll
              for (int j = 0; j < 2; j++) { const int w = lane + 32 * j; tab[(w & 3) * 16 + (w >> 2)] = ((const uint32_t*)P.w_r)[nb * 64 + w]; }
              tab[64 + lane] = lane < 16 ? 0x3F803F80u : 0u;
              float tot = 0.f;
#pragma unroll
              for (int j = 0; j < 4; j++) {
                const uint4 u = ((const uint4*)P.w_r)[lane + 32 * j];
                tot += bf_lo(u.x) + bf_hi(u.x) + bf_lo(u.y) + bf_hi(u.y) + bf_lo(u.z) + bf_hi(u.z) + bf_lo(u.w) + bf_hi(u.w);
              }
              s_misc[M_WSUM] = __float_as_uint(warp_sum(tot));
        }
              if (layer == 1) {
                const float2 ln = g_rowln[nb][mb * 128 + tid - 128];
                const uint32_t m2 = pack_bf16(ln.x, ln.x);
                uint8_t* row = smem + AT_ST + (wi >> 1) * 16384 + (tid & 63) * 128;
                mbar_wait(bar(B_RES), 1);
#pragma unroll 1
                for (int j = 0; j < 8; j++) {
                  uint4* c = (uint4*)(row + (((j + lane) & 7) << 4));
                  const uint4 v = c[0], w = c[512];
                  c[0] = make_uint4(add_ln_pair(v.x, m2, ln.y), add_ln_pair(v.y, m2, ln.y), add_ln_pair(v.z, m2, ln.y), add_ln_pair(v.w, m2, ln.y));
                  c[512] = make_uint4(add_ln_pair(w.x, m2, ln.y), add_ln_pair(w.y, m2, ln.y), add_ln_pair(w.z, m2, ln.y), add_ln_pair(w.w, m2, ln.y));
                }
                const int prow = (int)s_misc[M_SEL0] - mb * 128;
                __syncwarp();
                if (prow >> 5 == wi && lane < 16)
                  *(uint4*)(smem + AT_ST + (prow >> 6) * 16384 + (lane >> 3) * 8192 + (prow & 63) * 128 + (((lane ^ prow) & 7) << 4)) = poll4(&g_x2row[(nb * 16 + lane) * 2]);
                PROF(30);
              }
              __syncwarp();
              mbar_arrive_e(bar(B_RST));
        if (warp == 4) {
            named_bar(6, 320);
            spin_cycles(DELAY_S);
            uint4 c, u0, u1;
            uint32_t u2, best = 0, spins = 0;
            int src;
#pragma unroll 1
            for (;;) {
              src = (~best & 0x7FFu) >> 7;
              const uint4* xsel = &g_cand[layer][src * 128];
              c = ld_relaxed4(&g_slot[layer][(lane & 15) * 8]);
              u0 = ld_relaxed4(xsel + rank * 64 + lane); u1 = ld_relaxed4(xsel + rank * 64 + 32 + lane);
              u2 = ld_relaxed((const uint32_t*)(xsel + (bid >> 4) * 16 + q * 4) + (bid & 15));
              const uint32_t prev = best;
              best = __reduce_max_sync(0xffffffffu, c.w == tag ? c.x : 0u);
              if ((__all_sync(0xffffffffu, c.w == tag && valid4(u0) && valid4(u1) && u2 != SENT) && best == prev) || ++spins > SPIN_LIMIT) break;
            }
            const float sel_m = __uint_as_float(__shfl_sync(0xffffffffu, c.y, src)), sel_inv = __uint_as_float(__shfl_sync(0xffffffffu, c.z, src));
            const uint32_t m2 = pack_bf16(sel_m, sel_m);
            uint4* xs = (uint4*)(smem + T_XS) + (lane & 16) + q * 4 + (g & 3);
            xs[0] = make_uint4(ln_pair(u0.x, m2, sel_inv), ln_pair(u0.y, m2, sel_inv), ln_pair(u0.z, m2, sel_inv), ln_pair(u0.w, m2, sel_inv));
            xs[32] = make_uint4(ln_pair(u1.x, m2, sel_inv), ln_pair(u1.y, m2, sel_inv), ln_pair(u1.z, m2, sel_inv), ln_pair(u1.w, m2, sel_inv));
            s_misc[M_KEY] = best; s_misc[M_MEAN] = __float_as_uint(sel_m); s_misc[M_INV] = __float_as_uint(sel_inv);
            s_misc[M_XQ + q] = u2;
            PROF(16);
        }
        if (layer == 1) {
          named_bar(7, 512);
          const int sel = SEQ - 1 - (int)(s_misc[M_KEY] & 0x7FFFu), skip = sel >> 7 == mb ? (sel >> 6) & 1 : -1;
          if (warp == 7) store_tile(1, skip, false);
#pragma unroll 1
          for (int c = tid - 128; c < 1024 && skip >= 0; c += 128) {
            const int r = c >> 4;
            if (r != (sel & 63))
              *(uint4*)(P.out + (size_t)(mb * 128 + skip * 64 + r) * DM + nb * 128 + (c & 15) * 8) =
                  *(const uint4*)(smem + AT_ST + skip * 16384 + ((c >> 3) & 1) * 8192 + r * 128 + (((c ^ r) & 7) << 4));
          }
          __syncwarp();
        } else asm volatile("bar.arrive 7, 512;" ::: "memory");
        if (warp == 5 && layer == 0) {
              named_bar(8, 288);
              if (nb > 0) spin_cycles(X_STAGGER);
              store_tile(0, -1, true);
              set_flag(&g_xflag[mb][nb].v[0], tag);
              PROF(17);
              poll_flag(&g_xflag[2 * rb + (lane & 1)][0].v[0], tag);
              fence_async_global();
#pragma unroll 1
              for (int i = 0; i < 4; i++) load_a(i, i, 1);
              PROFL(1, 1);
        }
      }
      named_bar(1 + (fresh_tid() >> 7), 128);
      regs_dec<32>();
#pragma unroll 1
      for (;;) {
      const unsigned pass = __shfl_sync(0xffffffffu, pass_v, 0);
      if (pass > 0) {
        const unsigned layer = pass - 1;
        PHASE_IDS
        const uint32_t tag = s_misc[M_TAG], bkey = s_misc[M_KEY];
        const int sel = SEQ - 1 - (int)(bkey & 0x7FFFu);
        if (warp == 3) {
          if (layer == 1) {
#pragma unroll
            for (int j = 0; j < 3; j++) ((uint4*)g_vw)[bid * 96 + j * 32 + lane] = make_uint4(0, 0, 0, 0);
          } else s_misc[M_SEL0] = sel;
          if (bid == 0 && lane == 0) g_sel[layer] = sel;
        }
        __syncwarp();
        if (layer == 0) {
          auto load_down = [&](int j) {
            mbar_expect_tx(bar(B_DN + j), 2 * FFN_PIECE);
            bulk_load_h(sbase + SL_F + j * 2 * FFN_PIECE, P.w_d + (size_t)(bid * 28 + j * 14) * DM, 2 * FFN_PIECE, bar(B_DN + j), FFN_POL);
          };
          if (warp == 5) {
            poll_flag(&g_xflag[2 * rb + (lane & 1)][(lane >> 1) & 7].v[0], tag);
            fence_async_global();
            load_a(4, 4, 1); load_a(5, 5, 1);
          }
          float hv = 0.f;
          if (wg == 1) { mbar_wait_cluster(bar(B_HX), 0); hv = rbf(hidden()); fence_regs<1>(&hv); }
          named_bar(9, 512);
          if (warp == 0) {
            fence_async_smem();
            if (lane < 16) mbar_arrive_cluster(bar(B_QFREE), lane & 1);
            mbar_wait(bar(B_QFREE), 1);
            load_w(4, 4); load_w(5, 5);
            load_down(0);
          } else if (wg == 1) {
            if (warp == 4) { mbar_wait(bar(B_DN), 0); load_down(1); }
            float d[8] = {0.f, 0.f, 0.f, 0.f, 0.f, 0.f, 0.f, 0.f};
#pragma unroll 1
            for (int j = 0; j < 28; j += 2) {
              if (j == 0 || j == 14) mbar_wait(bar(B_DN + (j > 0)), 0);
              const uint4 w0 = *(const uint4*)(smem + SL_F + j * 2048 + (tid - 128) * 16), w1 = *(const uint4*)(smem + SL_F + j * 2048 + 2048 + (tid - 128) * 16);
              fma8(d, w0, __shfl_sync(0xffffffffu, hv, j));
              fma8(d, w1, __shfl_sync(0xffffffffu, hv, j + 1));
            }
            uint4* dst = &g_ypart[0][bid * 256 + (tid - 128) * 2];
            st_relaxed4(dst, make_uint4(f2u(d[0]), f2u(d[1]), f2u(d[2]), f2u(d[3])));
            st_relaxed4(dst + 1, make_uint4(f2u(d[4]), f2u(d[5]), f2u(d[6]), f2u(d[7])));
            if (WS1_AT == 0) asm volatile("bar.arrive 11, 160;" ::: "memory");
            PROF(20);
          } else if (warp == 2) {
            named_bar(11, 160);
            fence_async_smem();
            load_ws(WS1_PACE);
          }
        } else {
          if (wg == 1) named_bar(9, 384);
        }
        if (wg == 1) {
          const int t_y = (int)clock();
          const uint32_t xw = s_misc[M_XQ + ((lane & 7) >> 1)];
          const float x = (lane & 1) ? bf_hi(xw) : bf_lo(xw);
          float xn = rbf(rbf(x - __uint_as_float(s_misc[M_MEAN])) * __uint_as_float(s_misc[M_INV]));
          uint32_t u = bkey & 0xFFFF0000u;
          u = (u & 0x80000000u) ? (u & 0x7FFFFFFFu) : (~u & 0xFFFF0000u);
          float sg = rbf(__fdividef(1.f, 1.f + __expf(-__uint_as_float(u))));
          uint32_t* dst = (layer == 0 ? (uint32_t*)&g_x2row[bid * 2] : (uint32_t*)(P.out + (size_t)sel * DM + bid * 8)) + (lane >> 1);
          asm volatile("" : "+f"(xn), "+f"(sg), "+l"(dst));
#pragma unroll 1
          while ((int)clock() - t_y < DELAY_Y) {}
          const uint4* src = &g_ypart[layer][((tid - 128) >> 1) * 256 + bid * 2 + (tid & 1)];
          uint4 v, w;
          uint32_t spins = 0;
#pragma unroll 1
          do { v = ld_relaxed4(src); w = ld_relaxed4(src + 64 * 256); } while (!__all_sync(0xffffffffu, valid4(v) && valid4(w)) && ++spins < SPIN_LIMIT);
          float a[4] = {__uint_as_float(v.x) + __uint_as_float(w.x), __uint_as_float(v.y) + __uint_as_float(w.y),
                        __uint_as_float(v.z) + __uint_as_float(w.z), __uint_as_float(v.w) + __uint_as_float(w.w)};
          const bool b1 = lane & 2, b2 = lane & 4;
          float c0 = (b1 ? a[1] : a[0]) + __shfl_xor_sync(0xffffffffu, b1 ? a[0] : a[1], 2);
          float c1 = (b1 ? a[3] : a[2]) + __shfl_xor_sync(0xffffffffu, b1 ? a[2] : a[3], 2);
          float y = (b2 ? c1 : c0) + __shfl_xor_sync(0xffffffffu, b2 ? c0 : c1, 4);
          y += __shfl_xor_sync(0xffffffffu, y, 8);
          y += __shfl_xor_sync(0xffffffffu, y, 16);
          float* red = (float*)(smem + OFF_PATCH);
          red[wi * 8 + (lane & 1) * 4 + ((lane >> 1) & 3)] = y;
          named_bar(2, 128);
          if (WS1_AT == 1 && layer == 0 && warp != 4) asm volatile("bar.arrive 11, 160;" ::: "memory");
          if (warp == 4) {
            PROF(21);
            y = (red[lane & 7] + red[8 + (lane & 7)]) + (red[16 + (lane & 7)] + red[24 + (lane & 7)]);
            const float res = x + rbf(xn + rbf(rbf(y) * sg));
            const uint32_t pr = nosent(pack_bf16(res, __shfl_down_sync(0xffffffffu, res, 1)));
            if (lane < 8 && (lane & 1) == 0) st_relaxed(dst, pr);
            PROF(22);
            if (WS1_AT == 1 && layer == 0) asm volatile("bar.arrive 11, 160;" ::: "memory");
          }
        }
        if (pass == 2) {
          if (bid == 0 && tid == 128) g_epoch = tag;
          bulk_wait_all();
          __syncwarp();
          cluster_arrive(); cluster_wait();
          return;
        }
      }
      const unsigned layer = pass;
      if (__shfl_sync(0xffffffffu, fresh_tid() >> 5, 0) > 1 - (int)layer) {
        PHASE_IDS
        uint4* xrow = (uint4*)(smem + SL_F + 4 * SL_HD);
        if (wg == 1) {
          if (layer == 0) {
            xrow[tid - 128] = make_uint4(0x3F803F80u, 0x3F803F80u, 0x3F803F80u, 0x3F803F80u);
            if (warp == 5) { mbar_wait(bar(B_FULL + WS_AT), 0); load_ws(WS_PACE); }
          } else xrow[tid - 128] = poll4(&g_x2row[(tid - 128) * 2]);
          PROF(23);
        }
        named_bar(12, 192 + 32 * layer);
        if (warp == 1) {
          float mean = 0.f;
#pragma unroll 1
          for (int pass2 = 0; pass2 < 2; pass2++) {
            float acc = 0.f;
#pragma unroll 1
            for (int j = lane; j < 128; j += 32) {
              const uint4 v = xrow[j];
              const uint32_t w[4] = {v.x, v.y, v.z, v.w};
#pragma unroll
              for (int c = 0; c < 4; c++) {
                const float d0 = bf_lo(w[c]) - mean, d1 = bf_hi(w[c]) - mean;
                acc += pass2 ? d0 * d0 + d1 * d1 : d0 + d1;
              }
            }
            acc = warp_sum(acc) * (1.f / DM);
            if (pass2 == 0) mean = acc;
            else { s_misc[M_PMEAN] = __float_as_uint(rbf(mean)); s_misc[M_PINV] = __float_as_uint(ln_inv(acc)); }
          }
        } else {
          mbar_wait(bar(B_WS), layer);
          const uint8_t* wa = smem + SL_F + (g >> 1) * SL_HD + ((warp - 2) >> 1) * 4096 + (g & 1) * 2048;
          const uint32_t* xs = (const uint32_t*)xrow + rb * 64 + g * 8;
          const int ch = (warp & 1) * 4 + q;
          float d[8] = {0.f, 0.f, 0.f, 0.f, 0.f, 0.f, 0.f, 0.f};
#pragma unroll 1
          for (int j0 = 0; j0 < 16; j0 += 2) {
            const int j = j0 ^ ((g & 1) * 4);
            const uint4 w0 = *(const uint4*)(wa + j * 128 + (((ch ^ j) & 7) << 4)), w1 = *(const uint4*)(wa + j * 128 + 128 + (((ch ^ (j + 1)) & 7) << 4));
            const uint32_t xx = xs[j >> 1];
            fma8(d, w0, bf_lo(xx)); fma8(d, w1, bf_hi(xx));
          }
#pragma unroll
          for (int c = 0; c < 4; c++) d[c] = ((g & 4) ? d[c + 4] : d[c]) + __shfl_xor_sync(0xffffffffu, (g & 4) ? d[c] : d[c + 4], 16);
#pragma unroll
          for (int c = 0; c < 2; c++) d[c] = ((g & 2) ? d[c + 2] : d[c]) + __shfl_xor_sync(0xffffffffu, (g & 2) ? d[c] : d[c + 2], 8);
          d[0] = ((g & 1) ? d[1] : d[0]) + __shfl_xor_sync(0xffffffffu, (g & 1) ? d[0] : d[1], 4);
          st_relaxed(&g_vw[layer][rb][((warp - 2) >> 1) * DM + hp * 64 + ch * 8 + g], enc(d[0]));
        }
        named_bar(12, 192 + 32 * layer);
        PROF(24);
      }
      PHASE_IDS
      if (wg == 0) {
        if (warp == 0) {
          int s = 0, u = 0;
#pragma unroll 1
          for (int i = 6; i < 32; i++) {
            if (layer == 1) mbar_arrive_e(bar(B_EMPTY + s));
            mbar_wait(bar(B_EMPTY + s), (u + (s > 1 ? 0 : layer)) & 1);
            load_w(s, i);
            load_a(s, i, layer);
            if (++s == 6) { s = 0; u++; }
          }
        } else if (warp == 1) {
          if (layer == 0) {
            const uint32_t tag = ld_relaxed(&g_epoch) + 1;
            float shift = 0.f, sum = 0.f, sq = 0.f;
            const int r = hp * 16 + (lane >> 1);
#pragma unroll 1
            for (int i = 0; i < 32; i++) {
              mbar_wait(bar(B_FULL + i % 6), (i / 6) & 1);
              const uint8_t* base = smem + (i % 6) * QE + r * 64 + (lane & 1) * 32;
              uint4 v[2];
#pragma unroll
              for (int j = 0; j < 2; j++) v[j] = *(const uint4*)(base + ((j ^ ((r >> 1) & 1)) << 4));
              if (i == 0) shift = __shfl_sync(0xffffffffu, bf_lo(v[0].x), lane & ~1);
#pragma unroll
              for (int j = 0; j < 2; j++) {
                const uint32_t w[4] = {v[j].x, v[j].y, v[j].z, v[j].w};
#pragma unroll
                for (int c = 0; c < 4; c++) {
                  const float d0 = bf_lo(w[c]) - shift, d1 = bf_hi(w[c]) - shift;
                  sum += d0 + d1; sq = fmaf(d0, d0, fmaf(d1, d1, sq));
                }
              }
              fence_async_smem();
              __syncwarp();
              if (i < 26) mbar_arrive_e(bar(B_EMPTY + i % 6));
            }
            sum += __shfl_xor_sync(0xffffffffu, sum, 1); sq += __shfl_xor_sync(0xffffffffu, sq, 1);
            const float dm = sum * (1.f / DM), var = fmaxf(sq * (1.f / DM) - dm * dm, 0.f), mean = shift + dm;
            const float inv = ln_inv(var);
            if ((lane & 1) == 0) st_relaxed4(&g_rowab[0][rb * 256 + r], make_uint4(__float_as_uint(inv), __float_as_uint(rbf(mean) * inv), tag, 0));
          }
          if (rb == 0) {
            mbar_wait(bar(B_QDONE), layer);
#pragma unroll 1
            for (int j = lane; j < 512; j += 32) ((uint4*)(smem + 65536))[j] = make_uint4(0, 0, 0, 0);
            fence_async_smem();
            __syncwarp();
            if (lane < 3) mbar_arrive(bar(B_HALO + lane));
          }
        } else if (warp == 3) {
          fence_async_smem();
          load_gu(0, layer ? GU_PACE1 : GU_PACE);
          PROF(27);
        } else {
          const uint4 sent = make_uint4(SENT, SENT, SENT, SENT), zero = make_uint4(0, 0, 0, 0);
#pragma unroll 1
          for (int t = lane; t < 128; t += 32) {
            g_ypart[layer][bid * 256 + t] = sent; g_ypart[layer][bid * 256 + 128 + t] = sent;
            g_part[layer][nb * SEQ + mb * 128 + t] = zero;
            if (t < 16) g_cand[layer][mb * 128 + nb * 16 + t] = sent;
            else if (t < 18) { if (nb == 0) g_slot[layer][mb * 8 + t - 16] = zero; }
            else if (t < 20) { if (layer == 0) g_x2row[bid * 2 + t - 18] = sent; }
          }
        }
        __syncwarp();
        if (rank == 0) {
          if (warp == 0) {
            mbar_wait(bar(B_QDONE), layer);
#pragma unroll 1
            for (int j = 0; j < 3; j++) {
              const int o = j == 0 ? 16384 : (j == 1 ? 0 : 65536);
              mbar_wait(bar(B_KVREADY + (j >> 1)), layer);
              bulk_push(mapa(sbase + o, 1), sbase + 32768 + o, j == 2 ? 32768 : 16384, mapa(bar(B_HALO + j), 1));
            }
          } else if (warp < 3 && rb > 0) {
            mbar_wait(bar(B_QREADY), layer);
            if (warp == 2) spin_cycles(1000);
            import_halo(layer, warp - 1);
            if (warp == 1) PROF(5);
          }
        } else if (warp == 2) {
          mbar_expect_tx(bar(B_HALO), 16384); mbar_expect_tx(bar(B_HALO + 1), 16384); mbar_expect_tx(bar(B_HALO + 2), 32768);
        } else if (warp < 2 && rb < 7) {
          mbar_wait(bar(B_KVREADY + warp), layer);
          if (warp == 1) named_bar(13, 64);
          bulk_store(g_kv + (size_t)((rb >> 1) * 16 + hp) * 65536 + warp * 32768, sbase + 32768 + warp * 65536, 32768);
          bulk_commit();
          bulk_wait_all();
          if (warp == 0) asm volatile("bar.arrive 13, 64;" ::: "memory");
          set_flag(&g_kvflag[rb >> 1][hp][warp].v[layer], s_misc[M_TAG]);
          if (warp == 0) PROF(4);
        }
      } else {
        const int t = tid - 128, go = (t >> 5) * DM + hp * 64 + (t & 31) * 2;
        if (layer == 0 && t == 96) { s_misc[M_TAG] = ld_relaxed(&g_epoch) + 1; s_misc[M_SEL0] = 0xFFFFFFFFu; s_misc[M_PROG] = 0; }
        if ((layer == 0 || (int)s_misc[M_SEL0] >> 8 == rb) && warp < 7) {
          spin_cycles(layer ? 300 : 1500);
          uint2 w[8];
          uint32_t spins = 0;
          bool ok;
#pragma unroll 1
          do {
            ok = true;
#pragma unroll
            for (int j = 0; j < 8; j++) w[j] = ld_relaxed2(&g_vw[layer][j][go]);
#pragma unroll
            for (int j = 0; j < 8; j++) ok = ok && w[j].x && w[j].y;
          } while (!__all_sync(0xffffffffu, ok) && ++spins < SPIN_LIMIT);
          float s0 = 0.f, s1 = 0.f;
#pragma unroll
          for (int j = 0; j < 8; j++) { s0 += dec(w[j].x); s1 += dec(w[j].y); }
          if (layer == 0) ((float2*)(smem + OFF_CS))[t] = make_float2(s0, s1);
          else {
            const float2 c = ((const float2*)(smem + OFF_CS))[t];
            const float a = __uint_as_float(s_misc[M_PINV]) * (warp == 4 ? SM_C : 1.f), b = __uint_as_float(s_misc[M_PMEAN]) * a;
            ((uint32_t*)(smem + OFF_PATCH))[t] = pack_bf16(s0 * a - c.x * b, s1 * a - c.y * b);
          }
          PROF(25);
        }
        __syncwarp();
        mbar_arrive_e(bar(B_CS));
      }
      __syncwarp();
      mbar_wait(bar(B_QREADY), layer);
      named_bar(1 + (fresh_tid() >> 7), 128);
      if (__shfl_sync(0xffffffffu, fresh_tid() >> 7, 0) == 0) {
        regs_inc<152>();
        uint32_t gu[112];
        {
          PHASE_IDS
          const uint32_t tag = s_misc[M_TAG];
          mbar_wait(bar(B_GU), layer);
#pragma unroll
          for (int j = 0; j < 28; j++) fetch_gu(gu + 4 * j, warp * 4 + (j & 3), j >> 2);
          fence_async_smem();
          named_bar(1, 128);
          if (warp == 0) {
            mbar_wait(bar(B_WGO), layer);
            mbar_wait(bar(B_ADONE), layer);
#pragma unroll 1
            for (int k = 2; k < 16; k++) {
              if (HOLD_K && k == HOLD_K) named_bar(14, 64);
              if (PROG) {
#pragma unroll 1
                for (uint32_t spins = 0; k >= 8 && (int)s_misc[M_PROG] <= k + 16 * (int)layer && spins < SPIN_LIMIT; spins++) {}
              } else if (k == 8) mbar_wait(bar(B_WGO + 1), layer);
              if (k >= 4) mbar_wait(bar(B_WEMPTY + (k & 3)), ((k >> 2) - 1 + ((k & 2) ? layer : 0)) & 1);
              load_o(k); load_wo(k);
              STEPT(16 + k);
              if (k == RES_K) { mbar_wait(bar(B_OST + 1), layer); load_res(1, layer); }
            }
            if (layer == 1) {
              mbar_wait(bar(B_WEMPTY + 1), 1);
              if (FAKE & 2) mbar_arrive_e(bar(B_DN)); else mbar_expect_tx(bar(B_DN), 4 * FFN_PIECE);
              if (!(FAKE & 2)) tma_load3_h(sbase, &P.mapD, 0, bid * 28, 0, bar(B_DN), FFN_POL);
              if (D_SPLIT == 0) tma_load3_h(sbase + 2 * FFN_PIECE, &P.mapD, 0, bid * 28, 8, bar(B_DN), FFN_POL);
            }
            named_bar(6, 320);
            if (layer == 0) {
              mbar_wait(bar(B_QFREE), 0);
#pragma unroll 1
              for (int i = 0; i < 4; i++) load_w(i, i);
            } else if (D_SPLIT == 1 && !(FAKE & 2)) tma_load3_h(sbase + 2 * FFN_PIECE, &P.mapD, 0, bid * 28, 8, bar(B_DN), FFN_POL);
          } else if (warp < 3) {
            const int h = warp - 1;
#pragma unroll 1
            for (int qb = 3; qb >= 0; qb--) {
              mbar_wait(bar(B_UNIT + h * 4 + 3 - qb), layer);
              bulk_store(g_o + (size_t)((((rb * 2 + (qb >> 1)) * 2 + h) * 16 + hp) * 2 + (qb & 1)) * 4096, sbase + AT_ST + (h * 4 + qb) * 4096, 4096);
            }
            bulk_commit();
            if (h == 0 && lane < 2) mbar_arrive_cluster(bar(B_OST), lane);
            bulk_wait_all();
            if (h == 1) mbar_arrive_e(bar(B_OST + 1));
            set_flag(&g_oflag[rb][h][hp].v[layer], tag);
            if (HOLD_K && h == 1) asm volatile("bar.arrive 14, 64;" ::: "memory");
            PROF(28 + 3 * h);
            if (h == 0) {
              load_res(0, layer);
              mbar_wait(bar(B_OST), layer);
              load_wo(0); load_wo(1);
            }
            if (PROG && h == 1) {
              int n = 0;
#pragma unroll 1
              for (uint32_t spins = 0; n < 8 && spins < SPIN_LIMIT; spins++) {
                n = (__ffs(__ballot_sync(0xffffffffu, ld_relaxed(&g_oflag[rb][1][lane & 15].v[layer]) != tag || lane == 16)) - 1) >> 1;
                asm volatile("fence.acquire.gpu;" ::: "memory");
                fence_async_global();
                s_misc[M_PROG] = 8 + n + 16 * layer;
              }
            } else {
            poll_flag(&g_oflag[rb][h][lane & 15].v[layer], tag);
            fence_async_global();
            }
            PROF(15 + 11 * h);
            if (h == 0) { load_o(0); load_o(1); }
            mbar_arrive_e(bar(B_WGO + h));
          } else {
            mbar_expect_tx(bar(B_HX), 2240);
            mbar_wait(bar(B_HALO + 2), layer);
            if (rb == 0) spin_cycles(2000);
            PROF(6);
            load_gu(1, GUB_PACE);
          }
        }
        PHASE_IDS
        uint4 xa = {}, xb = {};
        named_bar(7, 512);
        if (g == 0) { xa = ((const uint4*)(smem + T_XS))[warp * 8 + q]; xb = ((const uint4*)(smem + T_XS))[warp * 8 + 4 + q]; }
        __syncwarp();
        float d[7][4] = {};
#pragma unroll
        for (int j = 0; j < 28; j++) {
          const int ks = j / 7, ct = j % 7;
          const uint32_t* a = gu + ct * 16 + ks * 4;
          mma_16816(d[ct], a[0], a[1], a[2], a[3], ks == 0 ? xa.x : ks == 1 ? xa.z : ks == 2 ? xb.x : xb.z, ks == 0 ? xa.y : ks == 1 ? xa.w : ks == 2 ? xb.y : xb.w);
        }
#pragma unroll
        for (int ct = 0; ct < 7; ct++) send_gu(d[ct][0], d[ct][2], ct, warp);
        __syncwarp();
        if (warp == 2) PROF(18);
        regs_dec<32>();
        pass_v = pass + 1;
        continue;
      }
      break;
      }
      regs_inc<120>();
    }
    const unsigned layer = pass;
    {
      PHASE_IDS
      mbar_wait(bar(B_QREADY), layer);
      if (warp != 9) STEPT(7);
      auto kdesc = [&](int h, int b) { return dlo(SOFF, 16) + (rb == 0 && b < 4 ? 4096 : h * 4096 + b * 512); };
      auto vdesc = [&](int h, int b) { return rb == 0 && b < 4 ? dlo(SOFF + 65536, 4096) : dlo(SOFF + 4096, OFF_ONES - 4096) + (h * 8 + b) * 8 * VSTEP; };
      const int units = wg == 3 ? 0x8630 : (wg == 2 ? ULIST2 : ULIST1);
      auto need = [&](int h, int b) { if (b == 3 || b == 1) mbar_wait(bar(B_HALO + (h ? 2 : b == 1)), layer); };
      auto load_q = [&](uint32_t* qf, int u) {
        *(uint4*)&qf[0] = *(const uint4*)(smem + AT_ST + ((u ^ 3) * 4 + wi) * 1024 + lane * 16);
        *(uint4*)&qf[4] = *(const uint4*)(smem + AT_ST + ((u ^ 3) * 4 + wi) * 1024 + 512 + lane * 16);
      };
      auto store_o = [&](const float* o, int u) {
        const float i0 = __fdividef(1.f, o[16]), i1 = __fdividef(1.f, o[18]);
        const int v = u ^ 3;
        if (u >= 4 && lane < 2) mbar_arrive_cluster(bar(B_ADONE), lane);
#pragma unroll
        for (int j = 0; j < 2; j++)
          stsm_x4(sbase + AT_ST + v * 4096 + srow * 64 + (((2 * j + (mi >> 1)) ^ ((srow >> 1) & 3)) << 4),
                  pack_bf16(o[8 * j] * i0, o[8 * j + 1] * i0), pack_bf16(o[8 * j + 2] * i1, o[8 * j + 3] * i1),
                  pack_bf16(o[8 * j + 4] * i0, o[8 * j + 5] * i0), pack_bf16(o[8 * j + 6] * i1, o[8 * j + 7] * i1));
        fence_async_smem();
        __syncwarp();
        mbar_arrive_e(bar(B_UNIT + u));
      };
      int redo = 0;
      {
        const int dl = g - 2 * q;
        const uint32_t mt = shl_clamp(0xFFFFFFFFu, max(16 * dl + 16, 0));
        uint32_t qf[8];
        float s[32];
        load_q(qf, units & 7);
        wg_fence();
        qk64(s, qf, kdesc((units >> 2) & 1, 6 - (units & 3)));
        wg_commit();
        wg_wait<0>();
        fence_regs<32>(s);
#pragma unroll 1
        for (int ul = units; ul != 8; ul >>= 4) {
          const int u = ul & 7, h = u >> 2, qb = 3 - (u & 3);
          float o[20];
          uint32_t p1[16], p2[16], p3[16], p4[16], p5[16];
          if (warp != 9) STEPT(8 + nu * 8);
          exp_pack<8>(s, p1);
          fence_regs_u<16>(p1);
          need(h, qb + 2);
          {
            float s2[32];
            const uint32_t vd = vdesc(h, qb + 3);
            wg_fence();
            qk64(s2, qf, kdesc(h, qb + 2));
            wg_commit();
            wg_rs40t_z<H64>(o, p1[0], p1[1], p1[2], p1[3], vd);
            wg_rs40t<H64>(o, p1[4], p1[5], p1[6], p1[7], vd + VSTEP, 1);
            pv32(o, p1 + 8, vd + 2 * VSTEP);
            wg_commit();
            wg_wait<1>();
            fence_regs<32>(s2);
            if (warp != 9) STEPT(9 + nu * 8);
            exp_pack<8>(s2, p2);
            fence_regs_u<16>(p2);
            wg_wait<0>();
            fence_regs<20>(o);
          }
          need(h, qb + 1);
          {
            float s3[32];
            wg_fence();
            qk64(s3, qf, kdesc(h, qb + 1));
            wg_commit();
            pv32(o, p2, vdesc(h, qb + 2)); pv32(o, p2 + 8, vdesc(h, qb + 2) + 2 * VSTEP);
            wg_commit();
            wg_wait<1>();
            fence_regs<32>(s3);
            if (warp != 9) STEPT(10 + nu * 8);
            exp_pack<8>(s3, p3);
            fence_regs_u<16>(p3);
            wg_wait<0>();
            fence_regs<20>(o);
          }
          need(h, qb);
          const uint32_t kd = kdesc(h, qb + 4), kt = kdesc(h, qb), vd = vdesc(h, qb + 4), vt = vdesc(h, qb);
          {
            float sd[16], st[16];
            wg_fence();
            qk32x2(sd, st, qf, kd, kt);
            wg_commit();
            pv32(o, p3, vdesc(h, qb + 1)); pv32(o, p3 + 8, vdesc(h, qb + 1) + 2 * VSTEP);
            wg_commit();
            wg_wait<1>();
            fence_regs<16>(sd); fence_regs<16>(st);
            if (warp != 9) STEPT(11 + nu * 8);
            edge32(sd, st, p4, p4 + 8, wi, dl, mt);
            fence_regs_u<16>(p4);
            wg_wait<0>();
            fence_regs<20>(o);
          }
          const int un = (ul >> 4) == 8 ? 4 : (ul >> 4) & 7;
          {
            float sd[16], st[16];
            wg_fence();
            qk32x2(sd, st, qf, kd + 128, kt + 128);
            wg_commit();
            pv32(o, p4, vd); pv32(o, p4 + 8, vt);
            wg_commit();
            wg_wait<1>();
            fence_regs<16>(sd); fence_regs<16>(st);
            load_q(qf, un);
            edge32(sd, st, p5, p5 + 8, wi - 2, dl, mt);
            fence_regs_u<16>(p5);
          }
          need(un >> 2, 6 - (un & 3));
          wg_fence();
          pv32(o, p5, vd + 2 * VSTEP); pv32(o, p5 + 8, vt + 2 * VSTEP);
          wg_commit();
          qk64(s, qf, kdesc(un >> 2, 6 - (un & 3)));
          wg_commit();
          wg_wait<1>();
          fence_regs<20>(o);
          if (warp != 9) STEPT(12 + nu * 8);
          const bool unsafe = !(o[16] >= LSUM_MIN && o[16] <= LSUM_MAX && o[18] >= LSUM_MIN && o[18] <= LSUM_MAX);
          if (__any_sync(0xffffffffu, unsafe)) redo |= 1 << u;
          else store_o(o, u);
          wg_wait<0>();
          fence_regs<32>(s);
        }
      }
      if (warp != 9) STEPT(31);
      if (bar_red_or(1 + wg, 128, redo)) {
#pragma unroll 1
        for (int ul = units; ul != 8; ul >>= 4) {
          const int u = ul & 7;
          if (!bar_red_or(1 + wg, 128, redo >> u & 1)) continue;
          const int h = u >> 2, qb = 3 - (u & 3);
          uint32_t qf[8], p[16];
          float o[20], m0 = -INFINITY, m1 = -INFINITY;
          load_q(qf, u);
#pragma unroll
          for (int i = 0; i < 20; i++) o[i] = 0.f;
#pragma unroll 1
          for (int j = 0; j <= (rb == 0 ? qb : 4); j++) {
            const int b = qb + 4 - j;
            float s[32];
            wg_fence();
            qk64(s, qf, kdesc(h, b));
            wg_commit();
            wg_wait<0>();
            fence_regs<32>(s);
            float mx0 = m0, mx1 = m1;
#pragma unroll
            for (int c = 0; c < 8; c++) {
#pragma unroll
              for (int i = 0; i < 4; i++) {
                const int diff = j * 64 + (16 * wi + g + (i >> 1) * 8) - (8 * c + 2 * q + (i & 1));
                if (diff < 0 || diff > 255) s[4 * c + i] = -INFINITY;
              }
              mx0 = fmaxf(mx0, fmaxf(s[4 * c], s[4 * c + 1]));
              mx1 = fmaxf(mx1, fmaxf(s[4 * c + 2], s[4 * c + 3]));
            }
            mx0 = fmaxf(mx0, __shfl_xor_sync(0xffffffffu, mx0, 1)); mx1 = fmaxf(mx1, __shfl_xor_sync(0xffffffffu, mx1, 1));
            mx0 = fmaxf(mx0, __shfl_xor_sync(0xffffffffu, mx0, 2)); mx1 = fmaxf(mx1, __shfl_xor_sync(0xffffffffu, mx1, 2));
            const float r0 = j == 0 ? 0.f : ex2(m0 - mx0), r1 = j == 0 ? 0.f : ex2(m1 - mx1);
            m0 = mx0; m1 = mx1;
#pragma unroll
            for (int i = 0; i < 5; i++) { o[4 * i] *= r0; o[4 * i + 1] *= r0; o[4 * i + 2] *= r1; o[4 * i + 3] *= r1; }
#pragma unroll
            for (int c = 0; c < 8; c++) { s[4 * c] -= m0; s[4 * c + 1] -= m0; s[4 * c + 2] -= m1; s[4 * c + 3] -= m1; }
            exp_pack<8>(s, p);
            fence_regs<20>(o); fence_regs_u<16>(p);
            wg_fence();
            pv32(o, p, vdesc(h, b)); pv32(o, p + 8, vdesc(h, b) + 2 * VSTEP);
            wg_commit();
            wg_wait<0>();
            fence_regs<20>(o);
          }
          named_bar(1 + wg, 128);
          if (redo >> u & 1) store_o(o, u);
          __syncwarp();
        }
      }
      if (wi == 0) PROF(6 + wg);
    }
    pass_v = pass + 1;
  }
}

}

typedef CUresult (*EncodeFn)(CUtensorMap*, CUtensorMapDataType, cuuint32_t, void*, const cuuint64_t*, const cuuint64_t*,
                             const cuuint32_t*, const cuuint32_t*, CUtensorMapInterleave, CUtensorMapSwizzle,
                             CUtensorMapL2promotion, CUtensorMapFloatOOBfill);
static EncodeFn g_encode = nullptr;
struct Dim { uint64_t size, stride; uint32_t box; };
template <int N> static CUtensorMap make_map(const void* ptr, const Dim (&d)[N], int swizzle) {
  CUtensorMap m;
  cuuint64_t dims[N], strides[N];
  cuuint32_t box[N], es[N];
  for (int i = 0; i < N; i++) { dims[i] = d[i].size; strides[i] = d[i].stride; box[i] = d[i].box; es[i] = 1; }
  g_encode(&m, CU_TENSOR_MAP_DATA_TYPE_BFLOAT16, N, const_cast<void*>(ptr), dims, strides + 1, box, es, CU_TENSOR_MAP_INTERLEAVE_NONE,
           swizzle == 128 ? CU_TENSOR_MAP_SWIZZLE_128B : (swizzle == 64 ? CU_TENSOR_MAP_SWIZZLE_64B : CU_TENSOR_MAP_SWIZZLE_NONE),
           swizzle ? CU_TENSOR_MAP_L2_PROMOTION_L2_256B : CU_TENSOR_MAP_L2_PROMOTION_L2_128B, CU_TENSOR_MAP_FLOAT_OOB_FILL_NONE);
  return m;
}
static CUtensorMap map2(const void* ptr, uint64_t inner, uint64_t outer, uint32_t bi, uint32_t bo, int swizzle) {
  const Dim d[2] = {{inner, 0, bi}, {outer, inner * 2, bo}};
  return make_map(ptr, d, swizzle);
}
template <class T> static void* sym_addr(T& sym) { void* p = nullptr; cudaGetSymbolAddress(&p, sym); return p; }

static Params h_p;
static const void* h_key[9];

static cudaLaunchConfig_t launch_cfg(int grid, cudaLaunchAttribute* at) {
  cudaLaunchConfig_t cfg = {};
  cfg.gridDim = dim3(grid); cfg.blockDim = dim3(512); cfg.dynamicSmemBytes = SMEM_BYTES; cfg.stream = cudaStreamPerThread;
  at[0].id = cudaLaunchAttributeClusterDimension;
  at[0].val.clusterDim.x = 2; at[0].val.clusterDim.y = 1; at[0].val.clusterDim.z = 1;
  cfg.attrs = at; cfg.numAttrs = 1;
  return cfg;
}

extern "C" void kernel_launch(void* const* d_in, const int* in_sizes, int n_in, void* d_out, int out_size) {
  const bf16* x = (const bf16*)d_in[0];
  const bf16* wqkv = (const bf16*)d_in[1];
  const bf16* wo = (const bf16*)d_in[2];
  cudaLaunchAttribute at[1];
  bool fresh = g_encode != nullptr && h_key[8] == d_out;
  for (int i = 0; i < 8; i++) fresh = fresh && h_key[i] == d_in[i];
  if (!fresh) {
    if (!g_encode) {
      void* fn = nullptr;
      cudaDriverEntryPointQueryResult st;
      cudaGetDriverEntryPoint("cuTensorMapEncodeTiled", &fn, cudaEnableDefault, &st);
      g_encode = (EncodeFn)fn;
      cudaFuncSetAttribute(mega_kernel, cudaFuncAttributeMaxDynamicSharedMemorySize, SMEM_BYTES);
    }
    bf16* x1 = (bf16*)sym_addr(g_x1);
    Params& p = h_p;
    p.x = x; p.wqkv = wqkv; p.wo = wo; p.w_r = (const bf16*)d_in[4]; p.w_g = (const bf16*)d_in[5]; p.w_u = (const bf16*)d_in[6]; p.w_d = (const bf16*)d_in[7];
    p.out = (bf16*)d_out;
    p.mapA[0] = map2(x, DM, SEQ, 32, 256, 64);
    p.mapA[1] = map2(x1, DM, SEQ, 32, 256, 64);
    { const Dim d[3] = {{DM, 0, 64}, {DM, 3 * DM * 2, 16}, {3, DM * 2, 3}}; p.mapW = make_map(wqkv, d, 128); }
    { const Dim d[3] = {{DM, 0, 64}, {DM, 3 * DM * 2, 32}, {3, DM * 2, 3}}; p.mapWs = make_map(wqkv, d, 128); }
    { const Dim d[3] = {{DM, 0, 64}, {64, DM * 2, 32}, {16, 64 * DM * 2, 2}}; p.mapWo = make_map(wo, d, 128); }
    p.mapRes[0] = map2(x, DM, SEQ, 64, 64, 128);
    p.mapRes[1] = p.mapXst[0] = map2(x1, DM, SEQ, 64, 64, 128);
    p.mapXst[1] = map2(d_out, DM, SEQ, 64, 64, 128);
    p.mapG = map2(p.w_g, FF, DM, 56, 128, 0);
    p.mapU = map2(p.w_u, FF, DM, 56, 128, 0);
    { const Dim d[3] = {{64, 0, 64}, {FF, DM * 2, 28}, {DM / 64, 128, 8}}; p.mapD = make_map(p.w_d, d, 128); }
    for (int i = 0; i < 8; i++) h_key[i] = d_in[i];
    h_key[8] = d_out;
  }
  void* a0[] = {&h_p};
  cudaLaunchConfig_t cfg = launch_cfg(128, at);
  cudaLaunchKernelExC(&cfg, (const void*)mega_kernel, a0);
}
```

```cpp
#include <cuda_runtime.h>
#include <cuda_bf16.h>
#include <cuda.h>
#include <stdint.h>

namespace {

constexpr int SEQ = 2048, DM = 1024, FF = 3584;
constexpr float LN_EPS = 1e-5f;
typedef __nv_bfloat16 bf16;

__device__ __align__(1024) uint8_t g_kv[3 * 16 * 65536];
__device__ __align__(1024) uint8_t g_o[SEQ * DM * 2];
__device__ __align__(1024) bf16 g_x1[SEQ * DM];
__device__ unsigned g_epoch;
struct __align__(128) Flag { unsigned v[32]; };
__device__ Flag g_kvflag[3][16][2], g_oflag[8][2][16], g_xflag[16][8];
__device__ uint4 g_rowab[2][SEQ];
__device__ __align__(16) uint32_t g_vw[2][8][3 * DM];
constexpr uint32_t SENT = 0xFFFFFFFFu;
__device__ uint4 g_part[2][8 * SEQ];
__device__ uint4 g_slot[2][16 * 8];
__device__ uint4 g_cand[2][16 * 128];
__device__ uint4 g_ypart[2][128 * DM / 4];
__device__ uint4 g_x2row[128 * 2];
__device__ float2 g_rowln[8][SEQ];
__device__ int g_sel[2];

#define PROFL(l, e)
#define PROF(e) PROFL(layer, e)
#define STEPT(i)
#define SPIN_LIMIT 4000000u
__device__ __forceinline__ uint32_t smem_u32(const void* p) { return (uint32_t)__cvta_generic_to_shared(p); }
__device__ __forceinline__ void mbar_init(uint32_t bar, uint32_t cnt) {
  asm volatile("mbarrier.init.shared::cta.b64 [%0], %1;" ::"r"(bar), "r"(cnt) : "memory");
}
#define ELECT "{\n.reg .pred e;\nelect.sync _|e, 0xffffffff;\n@e "
__device__ __forceinline__ void mbar_expect_tx(uint32_t bar, uint32_t bytes) {
  asm volatile(ELECT "mbarrier.arrive.expect_tx.shared::cta.b64 _, [%0], %1;\n}" ::"r"(bar), "r"(bytes) : "memory");
}
__device__ __forceinline__ void mbar_arrive(uint32_t bar) {
  asm volatile("mbarrier.arrive.shared::cta.b64 _, [%0];" ::"r"(bar) : "memory");
}
__device__ __forceinline__ void mbar_arrive_e(uint32_t bar) {
  asm volatile(ELECT "mbarrier.arrive.shared::cta.b64 _, [%0];\n}" ::"r"(bar) : "memory");
}
__device__ __forceinline__ uint32_t mapa(uint32_t addr, uint32_t cta) {
  uint32_t r; asm("mapa.shared::cluster.u32 %0, %1, %2;" : "=r"(r) : "r"(addr), "r"(cta)); return r;
}
__device__ __forceinline__ void mbar_arrive_cluster(uint32_t bar, uint32_t cta) {
  asm volatile("mbarrier.arrive.shared::cluster.b64 _, [%0];" ::"r"(mapa(bar, cta)) : "memory");
}
#define MBAR_WAIT_ASM(QUAL)                                                                                                \
  asm volatile("{\n.reg .pred p;\n.reg .u32 n;\nmov.u32 n, 0;\nWAIT_LOOP:\n.pragma \"nounroll\";\n"                         \
               "mbarrier.try_wait.parity" QUAL ".shared::cta.b64 p, [%0], %1;\n@p bra WAIT_DONE;\n"                        \
               "add.u32 n, n, 1;\nsetp.lt.u32 p, n, %2;\n@p bra WAIT_LOOP;\nWAIT_DONE:\n}" ::"r"(bar), "r"(parity), "n"(SPIN_LIMIT) : "memory")
__device__ __forceinline__ void mbar_wait(uint32_t bar, uint32_t parity) { MBAR_WAIT_ASM(""); }
__device__ __forceinline__ void mbar_wait_cluster(uint32_t bar, uint32_t parity) { MBAR_WAIT_ASM(".acquire.cluster"); }
__device__ __forceinline__ bool mbar_wait_brief(uint32_t bar, uint32_t parity) {
  uint32_t ok;
  asm volatile("{\n.reg .pred p;\nmbarrier.try_wait.parity.shared::cta.b64 p, [%1], %2, 1000;\nselp.u32 %0, 1, 0, p;\n}"
               : "=r"(ok) : "r"(bar), "r"(parity) : "memory");
  return __all_sync(0xffffffffu, ok);
}
__device__ __forceinline__ void st_async2(uint32_t addr, float a, float b, uint32_t bar) {
  asm volatile("st.async.weak.shared::cluster.mbarrier::complete_tx::bytes.v2.f32 [%0], {%1, %2}, [%3];"
               ::"r"(addr), "f"(a), "f"(b), "r"(bar) : "memory");
}
__device__ __forceinline__ uint64_t policy_evict_first() {
  uint64_t p; asm volatile("createpolicy.fractional.L2::evict_first.b64 %0, 1.0;" : "=l"(p)); return p;
}
__device__ __forceinline__ void tma_load2(uint32_t dst, const CUtensorMap* m, int c0, int c1, uint32_t bar) {
  asm volatile(ELECT "cp.async.bulk.tensor.2d.shared::cluster.global.mbarrier::complete_tx::bytes [%0], [%1, {%3, %4}], [%2];\n}"
               ::"r"(dst), "l"(m), "r"(bar), "r"(c0), "r"(c1) : "memory");
}
__device__ __forceinline__ void tma_load2_h(uint32_t dst, const CUtensorMap* m, int c0, int c1, uint32_t bar, uint64_t pol) {
  asm volatile(ELECT "cp.async.bulk.tensor.2d.shared::cluster.global.mbarrier::complete_tx::bytes.L2::cache_hint [%0], [%1, {%3, %4}], [%2], %5;\n}"
               ::"r"(dst), "l"(m), "r"(bar), "r"(c0), "r"(c1), "l"(pol) : "memory");
}
__device__ __forceinline__ void tma_load3(uint32_t dst, const CUtensorMap* m, int c0, int c1, int c2, uint32_t bar) {
  asm volatile(ELECT "cp.async.bulk.tensor.3d.shared::cluster.global.mbarrier::complete_tx::bytes [%0], [%1, {%3, %4, %5}], [%2];\n}"
               ::"r"(dst), "l"(m), "r"(bar), "r"(c0), "r"(c1), "r"(c2) : "memory");
}
__device__ __forceinline__ void tma_load3_h(uint32_t dst, const CUtensorMap* m, int c0, int c1, int c2, uint32_t bar, uint64_t pol) {
  asm volatile(ELECT "cp.async.bulk.tensor.3d.shared::cluster.global.mbarrier::complete_tx::bytes.L2::cache_hint [%0], [%1, {%3, %4, %5}], [%2], %6;\n}"
               ::"r"(dst), "l"(m), "r"(bar), "r"(c0), "r"(c1), "r"(c2), "l"(pol) : "memory");
}
__device__ __forceinline__ void tma_load3_mc(uint32_t dst, const CUtensorMap* m, int c0, int c1, int c2, uint32_t bar) {
  asm volatile(ELECT "cp.async.bulk.tensor.3d.shared::cluster.global.mbarrier::complete_tx::bytes.multicast::cluster [%0], [%1, {%3, %4, %5}], [%2], %6;\n}"
               ::"r"(dst), "l"(m), "r"(bar), "r"(c0), "r"(c1), "r"(c2), "h"((uint16_t)3) : "memory");
}
__device__ __forceinline__ void bulk_push(uint32_t dst, uint32_t src, uint32_t bytes, uint32_t bar) {
  asm volatile(ELECT "cp.async.bulk.shared::cluster.shared::cta.mbarrier::complete_tx::bytes [%0], [%1], %2, [%3];\n}"
               ::"r"(dst), "r"(src), "r"(bytes), "r"(bar) : "memory");
}
template <int N> __device__ __forceinline__ void regs_inc() { asm volatile("setmaxnreg.inc.sync.aligned.u32 %0;" ::"n"(N)); }
template <int N> __device__ __forceinline__ void regs_dec() { asm volatile("setmaxnreg.dec.sync.aligned.u32 %0;" ::"n"(N)); }
__device__ __forceinline__ void tma_prefetch2(const CUtensorMap* m, int c0, int c1) {
  asm volatile(ELECT "cp.async.bulk.prefetch.tensor.2d.L2.global [%0, {%1, %2}];\n}" ::"l"(m), "r"(c0), "r"(c1) : "memory");
}
__device__ __forceinline__ void bulk_prefetch(const void* p, uint32_t bytes) {
  asm volatile(ELECT "cp.async.bulk.prefetch.L2.global [%0], %1;\n}" ::"l"(p), "r"(bytes) : "memory");
}
__device__ __forceinline__ void tma_store(const CUtensorMap* m, uint32_t src, int c0, int c1) {
  asm volatile(ELECT "cp.async.bulk.tensor.2d.global.shared::cta.bulk_group [%0, {%2, %3}], [%1];\n}"
               ::"l"(m), "r"(src), "r"(c0), "r"(c1) : "memory");
}
__device__ __forceinline__ void bulk_load(uint32_t dst, const void* src, uint32_t bytes, uint32_t bar) {
  asm volatile(ELECT "cp.async.bulk.shared::cluster.global.mbarrier::complete_tx::bytes [%0], [%1], %2, [%3];\n}"
               ::"r"(dst), "l"(src), "r"(bytes), "r"(bar) : "memory");
}
__device__ __forceinline__ void bulk_load_h(uint32_t dst, const void* src, uint32_t bytes, uint32_t bar, uint64_t pol) {
  asm volatile(ELECT "cp.async.bulk.shared::cluster.global.mbarrier::complete_tx::bytes.L2::cache_hint [%0], [%1], %2, [%3], %4;\n}"
               ::"r"(dst), "l"(src), "r"(bytes), "r"(bar), "l"(pol) : "memory");
}
__device__ __forceinline__ void bulk_store(void* dst, uint32_t src, uint32_t bytes) {
  asm volatile(ELECT "cp.async.bulk.global.shared::cta.bulk_group [%0], [%1], %2;\n}" ::"l"(dst), "r"(src), "r"(bytes) : "memory");
}
__device__ __forceinline__ void bulk_commit() { asm volatile("cp.async.bulk.commit_group;" ::: "memory"); }
__device__ __forceinline__ void bulk_wait_all() { asm volatile("cp.async.bulk.wait_group 0;" ::: "memory"); }
__device__ __forceinline__ void fence_async_smem() { asm volatile("fence.proxy.async.shared::cta;" ::: "memory"); }
__device__ __forceinline__ void fence_async_global() { asm volatile("fence.proxy.async.global;" ::: "memory"); }
__device__ __forceinline__ void fence_release() { asm volatile("fence.release.gpu;" ::: "memory"); }
__device__ __forceinline__ void l2_prefetch_line(const void* p) { asm volatile("prefetch.global.L2 [%0];" ::"l"(p) : "memory"); }
__device__ __forceinline__ void prefetch_tmap(const CUtensorMap* m) { asm volatile("prefetch.tensormap [%0];" ::"l"(m) : "memory"); }
__device__ __forceinline__ void named_bar(int id, int n) { asm volatile("bar.sync %0, %1;" ::"r"(id), "r"(n) : "memory"); }
__device__ __forceinline__ bool bar_red_or(int id, int n, bool v) {
  uint32_t r;
  asm volatile("{\n.reg .pred p, q;\nsetp.ne.u32 q, %3, 0;\nbarrier.cta.red.or.pred p, %1, %2, q;\nselp.u32 %0, 1, 0, p;\n}"
               : "=r"(r) : "r"(id), "r"(n), "r"((uint32_t)v) : "memory");
  return r != 0;
}
__device__ __forceinline__ void cluster_arrive() { asm volatile("barrier.cluster.arrive.relaxed.aligned;" ::: "memory"); }
__device__ __forceinline__ void cluster_wait() { asm volatile("barrier.cluster.wait.aligned;" ::: "memory"); }
__device__ __forceinline__ uint32_t cluster_rank() { uint32_t r; asm volatile("mov.u32 %0, %%cluster_ctarank;" : "=r"(r)); return r; }
__device__ __forceinline__ unsigned ld_relaxed(const unsigned* p) {
  unsigned v; asm volatile("ld.relaxed.gpu.global.u32 %0, [%1];" : "=r"(v) : "l"(p) : "memory"); return v;
}
__device__ __forceinline__ uint4 ld_relaxed4(const uint4* p) {
  uint4 v; asm volatile("ld.relaxed.gpu.global.v4.u32 {%0, %1, %2, %3}, [%4];" : "=r"(v.x), "=r"(v.y), "=r"(v.z), "=r"(v.w) : "l"(p) : "memory"); return v;
}
__device__ __forceinline__ void st_relaxed(unsigned* p, unsigned v) {
  asm volatile("st.relaxed.gpu.global.u32 [%0], %1;" ::"l"(p), "r"(v) : "memory");
}
__device__ __forceinline__ uint2 ld_relaxed2(const void* p) {
  uint2 v; asm volatile("ld.relaxed.gpu.global.v2.u32 {%0, %1}, [%2];" : "=r"(v.x), "=r"(v.y) : "l"(p) : "memory"); return v;
}
__device__ __forceinline__ void st_relaxed4(uint4* p, uint4 v) {
  asm volatile("st.relaxed.gpu.global.v4.u32 [%0], {%1, %2, %3, %4};" ::"l"(p), "r"(v.x), "r"(v.y), "r"(v.z), "r"(v.w) : "memory");
}
__device__ __forceinline__ bool valid4(uint4 v) { return v.x != SENT && v.y != SENT && v.z != SENT && v.w != SENT; }
__device__ __forceinline__ uint4 poll4(const uint4* p) {
  uint4 v;
  uint32_t spins = 0;
#pragma unroll 1
  do { v = ld_relaxed4(p); } while (!valid4(v) && ++spins < SPIN_LIMIT);
  return v;
}
__device__ __forceinline__ void set_flag(unsigned* p, unsigned tag) {
  asm volatile(ELECT "st.release.gpu.global.u32 [%0], %1;\n}" ::"l"(p), "r"(tag) : "memory");
}
__device__ __forceinline__ void poll_flag(const unsigned* p, unsigned tag) {
#pragma unroll 1
  for (uint32_t spins = 0; !__all_sync(0xffffffffu, ld_relaxed(p) == tag) && spins < SPIN_LIMIT; spins++) {}
  asm volatile("fence.acquire.gpu;" ::: "memory");
}
__device__ __forceinline__ uint32_t enc(float x) { return __float_as_uint(x + 0.0f) ^ 0x80000000u; }
__device__ __forceinline__ float dec(uint32_t u) { return __uint_as_float(u ^ 0x80000000u); }
__device__ __forceinline__ uint32_t f2u(float x) { uint32_t u = __float_as_uint(x); return u == SENT ? 0x7FFFFFFFu : u; }
__device__ __forceinline__ uint32_t nosent(uint32_t u) { return u == SENT ? 0x7FFF7FFFu : u; }
__device__ __forceinline__ uint32_t hadd_bf2(uint32_t a, uint32_t b) {
  uint32_t r; asm("add.rn.bf16x2 %0, %1, %2;" : "=r"(r) : "r"(a), "r"(b)); return r;
}
__device__ __forceinline__ uint32_t hsub_bf2(uint32_t a, uint32_t b) {
  uint32_t r; asm("sub.rn.bf16x2 %0, %1, %2;" : "=r"(r) : "r"(a), "r"(b)); return r;
}
__device__ __forceinline__ void wg_fence() { asm volatile("wgmma.fence.sync.aligned;" ::: "memory"); }
__device__ __forceinline__ void wg_commit() { asm volatile("wgmma.commit_group.sync.aligned;" ::: "memory"); }
template <int N> __device__ __forceinline__ void wg_wait() { asm volatile("wgmma.wait_group.sync.aligned %0;" ::"n"(N) : "memory"); }
template <int R> __device__ __forceinline__ void fence_regs(float* d) {
#pragma unroll
  for (int i = 0; i < R; i++) asm volatile("" : "+f"(d[i])::"memory");
}
template <int R> __device__ __forceinline__ void fence_regs_u(uint32_t* d) {
#pragma unroll
  for (int i = 0; i < R; i++) asm volatile("" : "+r"(d[i])::"memory");
}
__host__ __device__ constexpr uint32_t dlo(uint32_t addr, uint32_t lbo) { return ((addr & 0x3FFFF) >> 4) | ((lbo >> 4) << 16); }
constexpr uint32_t H128 = 0x40000040u, H64 = 0x80000020u;
__device__ __forceinline__ void stsm_x4(uint32_t addr, uint32_t r0, uint32_t r1, uint32_t r2, uint32_t r3) {
  asm volatile("stmatrix.sync.aligned.m8n8.x4.shared.b16 [%0], {%1, %2, %3, %4};"
               ::"r"(addr), "r"(r0), "r"(r1), "r"(r2), "r"(r3) : "memory");
}
__device__ __forceinline__ void ldsm_x4(uint32_t addr, uint32_t& r0, uint32_t& r1, uint32_t& r2, uint32_t& r3) {
  asm volatile("ldmatrix.sync.aligned.m8n8.x4.shared.b16 {%0, %1, %2, %3}, [%4];"
               : "=r"(r0), "=r"(r1), "=r"(r2), "=r"(r3) : "r"(addr) : "memory");
}
__device__ __forceinline__ void ldsm_x4_t(uint32_t addr, uint32_t& r0, uint32_t& r1, uint32_t& r2, uint32_t& r3) {
  asm volatile("ldmatrix.sync.aligned.m8n8.x4.trans.shared.b16 {%0, %1, %2, %3}, [%4];"
               : "=r"(r0), "=r"(r1), "=r"(r2), "=r"(r3) : "r"(addr) : "memory");
}
__device__ __forceinline__ void mma_16816(float* d, uint32_t a0, uint32_t a1, uint32_t a2, uint32_t a3, uint32_t b0, uint32_t b1) {
  asm volatile("mma.sync.aligned.m16n8k16.row.col.f32.bf16.bf16.f32 {%0, %1, %2, %3}, {%4, %5, %6, %7}, {%8, %9}, {%0, %1, %2, %3};"
               : "+f"(d[0]), "+f"(d[1]), "+f"(d[2]), "+f"(d[3]) : "r"(a0), "r"(a1), "r"(a2), "r"(a3), "r"(b0), "r"(b1));
}
__device__ __forceinline__ void spin_cycles(int n) {
  const int t0 = (int)clock();
#pragma unroll 1
  while ((int)clock() - t0 < n) {}
}
__device__ __forceinline__ uint32_t pack_bf16(float lo, float hi) {
  uint32_t r; asm("cvt.rn.bf16x2.f32 %0, %1, %2;" : "=r"(r) : "f"(hi), "f"(lo)); return r;
}
__device__ __forceinline__ float bf_lo(uint32_t v) { return __uint_as_float(v << 16); }
__device__ __forceinline__ float bf_hi(uint32_t v) { return __uint_as_float(v & 0xffff0000u); }
__device__ __forceinline__ float rbf(float x) { return __bfloat162float(__float2bfloat16_rn(x)); }
__device__ __forceinline__ float ex2(float x) { float y; asm("ex2.approx.ftz.f32 %0, %1;" : "=f"(y) : "f"(x)); return y; }
__device__ __forceinline__ float rcp(float x) { float y; asm("rcp.approx.ftz.f32 %0, %1;" : "=f"(y) : "f"(x)); return y; }
__device__ __forceinline__ uint32_t shl_clamp(uint32_t v, uint32_t n) {
  uint32_t r; asm("shl.b32 %0, %1, %2;" : "=r"(r) : "r"(v), "r"(n)); return r;
}
__device__ __forceinline__ float warp_sum(float v) {
#pragma unroll
  for (int o = 16; o > 0; o >>= 1) v += __shfl_xor_sync(0xffffffffu, v, o);
  return v;
}
__device__ __forceinline__ float ln_inv(float var) {
  float r;
  asm("sqrt.approx.ftz.f32 %0, %1;" : "=f"(r) : "f"(rbf(rbf(var) + LN_EPS)));
  asm("rcp.approx.ftz.f32 %0, %1;" : "=f"(r) : "f"(rbf(r)));
  return r;
}
__device__ __forceinline__ uint32_t ln_pair(uint32_t x, uint32_t mean2, float inv) {
  const uint32_t d = hsub_bf2(x, mean2);
  return pack_bf16(bf_lo(d) * inv, bf_hi(d) * inv);
}
__device__ __forceinline__ uint32_t add_ln_pair(uint32_t x, uint32_t mean2, float inv) { return hadd_bf2(x, ln_pair(x, mean2, inv)); }
__device__ __forceinline__ uint32_t router_key(float r_bf, int row) {
  uint32_t u = __float_as_uint(r_bf);
  u = (u & 0x80000000u) ? ~u : (u | 0x80000000u);
  return (u & 0xFFFF0000u) | 0x8000u | (uint32_t)(SEQ - 1 - row);
}

template <uint32_t HA = 0x40000040u, uint32_t HB = 0x40000040u>
__device__ __forceinline__ void wg_ss192t(float* d, uint32_t da, uint32_t db, int scale_d) {
  asm volatile("{\n.reg .pred p;\n.reg .b64 dA, dB;\nmov.b64 dA, {%96, %99};\nmov.b64 dB, {%97, %100};\nsetp.ne.b32 p, %98, 0;\n"
    "wgmma.mma_async.sync.aligned.m64n192k16.f32.bf16.bf16 "
    "{%0, %1, %2, %3, %4, %5, %6, %7, %8, %9, %10, %11, %12, %13, %14, %15, "
    "%16, %17, %18, %19, %20, %21, %22, %23, %24, %25, %26, %27, %28, %29, %30, %31, "
    "%32, %33, %34, %35, %36, %37, %38, %39, %40, %41, %42, %43, %44, %45, %46, %47, "
    "%48, %49, %50, %51, %52, %53, %54, %55, %56, %57, %58, %59, %60, %61, %62, %63, "
    "%64, %65, %66, %67, %68, %69, %70, %71, %72, %73, %74, %75, %76, %77, %78, %79, "
    "%80, %81, %82, %83, %84, %85, %86, %87, %88, %89, %90, %91, %92, %93, %94, %95}, "
    "dA, dB, p, 1, 1, 0, 1;\n}\n"
    : "+f"(d[0]), "+f"(d[1]), "+f"(d[2]), "+f"(d[3]), "+f"(d[4]), "+f"(d[5]), "+f"(d[6]), "+f"(d[7]),
      "+f"(d[8]), "+f"(d[9]), "+f"(d[10]), "+f"(d[11]), "+f"(d[12]), "+f"(d[13]), "+f"(d[14]), "+f"(d[15]),
      "+f"(d[16]), "+f"(d[17]), "+f"(d[18]), "+f"(d[19]), "+f"(d[20]), "+f"(d[21]), "+f"(d[22]), "+f"(d[23]),
      "+f"(d[24]), "+f"(d[25]), "+f"(d[26]), "+f"(d[27]), "+f"(d[28]), "+f"(d[29]), "+f"(d[30]), "+f"(d[31]),
      "+f"(d[32]), "+f"(d[33]), "+f"(d[34]), "+f"(d[35]), "+f"(d[36]), "+f"(d[37]), "+f"(d[38]), "+f"(d[39]),
      "+f"(d[40]), "+f"(d[41]), "+f"(d[42]), "+f"(d[43]), "+f"(d[44]), "+f"(d[45]), "+f"(d[46]), "+f"(d[47]),
      "+f"(d[48]), "+f"(d[49]), "+f"(d[50]), "+f"(d[51]), "+f"(d[52]), "+f"(d[53]), "+f"(d[54]), "+f"(d[55]),
      "+f"(d[56]), "+f"(d[57]), "+f"(d[58]), "+f"(d[59]), "+f"(d[60]), "+f"(d[61]), "+f"(d[62]), "+f"(d[63]),
      "+f"(d[64]), "+f"(d[65]), "+f"(d[66]), "+f"(d[67]), "+f"(d[68]), "+f"(d[69]), "+f"(d[70]), "+f"(d[71]),
      "+f"(d[72]), "+f"(d[73]), "+f"(d[74]), "+f"(d[75]), "+f"(d[76]), "+f"(d[77]), "+f"(d[78]), "+f"(d[79]),
      "+f"(d[80]), "+f"(d[81]), "+f"(d[82]), "+f"(d[83]), "+f"(d[84]), "+f"(d[85]), "+f"(d[86]), "+f"(d[87]),
      "+f"(d[88]), "+f"(d[89]), "+f"(d[90]), "+f"(d[91]), "+f"(d[92]), "+f"(d[93]), "+f"(d[94]), "+f"(d[95])
    : "r"(da), "r"(db), "r"(scale_d), "n"(HA), "n"(HB));
}
template <uint32_t HA = 0x40000040u, uint32_t HB = 0x40000040u>
__device__ __forceinline__ void wg_ss192t_z(float* d, uint32_t da, uint32_t db) {
  asm volatile("{\n.reg .pred p;\n.reg .b64 dA, dB;\nmov.b64 dA, {%96, %98};\nmov.b64 dB, {%97, %99};\nsetp.ne.b32 p, 0, 0;\n"
    "wgmma.mma_async.sync.aligned.m64n192k16.f32.bf16.bf16 "
    "{%0, %1, %2, %3, %4, %5, %6, %7, %8, %9, %10, %11, %12, %13, %14, %15, "
    "%16, %17, %18, %19, %20, %21, %22, %23, %24, %25, %26, %27, %28, %29, %30, %31, "
    "%32, %33, %34, %35, %36, %37, %38, %39, %40, %41, %42, %43, %44, %45, %46, %47, "
    "%48, %49, %50, %51, %52, %53, %54, %55, %56, %57, %58, %59, %60, %61, %62, %63, "
    "%64, %65, %66, %67, %68, %69, %70, %71, %72, %73, %74, %75, %76, %77, %78, %79, "
    "%80, %81, %82, %83, %84, %85, %86, %87, %88, %89, %90, %91, %92, %93, %94, %95}, "
    "dA, dB, p, 1, 1, 0, 1;\n}\n"
    : "=f"(d[0]), "=f"(d[1]), "=f"(d[2]), "=f"(d[3]), "=f"(d[4]), "=f"(d[5]), "=f"(d[6]), "=f"(d[7]),
      "=f"(d[8]), "=f"(d[9]), "=f"(d[10]), "=f"(d[11]), "=f"(d[12]), "=f"(d[13]), "=f"(d[14]), "=f"(d[15]),
      "=f"(d[16]), "=f"(d[17]), "=f"(d[18]), "=f"(d[19]), "=f"(d[20]), "=f"(d[21]), "=f"(d[22]), "=f"(d[23]),
      "=f"(d[24]), "=f"(d[25]), "=f"(d[26]), "=f"(d[27]), "=f"(d[28]), "=f"(d[29]), "=f"(d[30]), "=f"(d[31]),
      "=f"(d[32]), "=f"(d[33]), "=f"(d[34]), "=f"(d[35]), "=f"(d[36]), "=f"(d[37]), "=f"(d[38]), "=f"(d[39]),
      "=f"(d[40]), "=f"(d[41]), "=f"(d[42]), "=f"(d[43]), "=f"(d[44]), "=f"(d[45]), "=f"(d[46]), "=f"(d[47]),
      "=f"(d[48]), "=f"(d[49]), "=f"(d[50]), "=f"(d[51]), "=f"(d[52]), "=f"(d[53]), "=f"(d[54]), "=f"(d[55]),
      "=f"(d[56]), "=f"(d[57]), "=f"(d[58]), "=f"(d[59]), "=f"(d[60]), "=f"(d[61]), "=f"(d[62]), "=f"(d[63]),
      "=f"(d[64]), "=f"(d[65]), "=f"(d[66]), "=f"(d[67]), "=f"(d[68]), "=f"(d[69]), "=f"(d[70]), "=f"(d[71]),
      "=f"(d[72]), "=f"(d[73]), "=f"(d[74]), "=f"(d[75]), "=f"(d[76]), "=f"(d[77]), "=f"(d[78]), "=f"(d[79]),
      "=f"(d[80]), "=f"(d[81]), "=f"(d[82]), "=f"(d[83]), "=f"(d[84]), "=f"(d[85]), "=f"(d[86]), "=f"(d[87]),
      "=f"(d[88]), "=f"(d[89]), "=f"(d[90]), "=f"(d[91]), "=f"(d[92]), "=f"(d[93]), "=f"(d[94]), "=f"(d[95])
    : "r"(da), "r"(db), "n"(HA), "n"(HB));
}
template <uint32_t HA = 0x40000040u, uint32_t HB = 0x40000040u>
__device__ __forceinline__ void wg_ss128t(float* d, uint32_t da, uint32_t db, int scale_d) {
  asm volatile("{\n.reg .pred p;\n.reg .b64 dA, dB;\nmov.b64 dA, {%64, %67};\nmov.b64 dB, {%65, %68};\nsetp.ne.b32 p, %66, 0;\n"
    "wgmma.mma_async.sync.aligned.m64n128k16.f32.bf16.bf16 "
    "{%0, %1, %2, %3, %4, %5, %6, %7, %8, %9, %10, %11, %12, %13, %14, %15, "
    "%16, %17, %18, %19, %20, %21, %22, %23, %24, %25, %26, %27, %28, %29, %30, %31, "
    "%32, %33, %34, %35, %36, %37, %38, %39, %40, %41, %42, %43, %44, %45, %46, %47, "
    "%48, %49, %50, %51, %52, %53, %54, %55, %56, %57, %58, %59, %60, %61, %62, %63}, "
    "dA, dB, p, 1, 1, 0, 1;\n}\n"
    : "+f"(d[0]), "+f"(d[1]), "+f"(d[2]), "+f"(d[3]), "+f"(d[4]), "+f"(d[5]), "+f"(d[6]), "+f"(d[7]),
      "+f"(d[8]), "+f"(d[9]), "+f"(d[10]), "+f"(d[11]), "+f"(d[12]), "+f"(d[13]), "+f"(d[14]), "+f"(d[15]),
      "+f"(d[16]), "+f"(d[17]), "+f"(d[18]), "+f"(d[19]), "+f"(d[20]), "+f"(d[21]), "+f"(d[22]), "+f"(d[23]),
      "+f"(d[24]), "+f"(d[25]), "+f"(d[26]), "+f"(d[27]), "+f"(d[28]), "+f"(d[29]), "+f"(d[30]), "+f"(d[31]),
      "+f"(d[32]), "+f"(d[33]), "+f"(d[34]), "+f"(d[35]), "+f"(d[36]), "+f"(d[37]), "+f"(d[38]), "+f"(d[39]),
      "+f"(d[40]), "+f"(d[41]), "+f"(d[42]), "+f"(d[43]), "+f"(d[44]), "+f"(d[45]), "+f"(d[46]), "+f"(d[47]),
      "+f"(d[48]), "+f"(d[49]), "+f"(d[50]), "+f"(d[51]), "+f"(d[52]), "+f"(d[53]), "+f"(d[54]), "+f"(d[55]),
      "+f"(d[56]), "+f"(d[57]), "+f"(d[58]), "+f"(d[59]), "+f"(d[60]), "+f"(d[61]), "+f"(d[62]), "+f"(d[63])
    : "r"(da), "r"(db), "r"(scale_d), "n"(HA), "n"(HB));
}
template <uint32_t HB = 0x40000040u>
__device__ __forceinline__ void wg_rs64(float* d, uint32_t a0, uint32_t a1, uint32_t a2, uint32_t a3, uint32_t db, int scale_d) {
  asm volatile("{\n.reg .pred p;\n.reg .b64 dB;\nmov.b64 dB, {%36, %38};\nsetp.ne.b32 p, %37, 0;\n"
    "wgmma.mma_async.sync.aligned.m64n64k16.f32.bf16.bf16 "
    "{%0, %1, %2, %3, %4, %5, %6, %7, %8, %9, %10, %11, %12, %13, %14, %15, "
    "%16, %17, %18, %19, %20, %21, %22, %23, %24, %25, %26, %27, %28, %29, %30, %31}, "
    "{%32, %33, %34, %35}, dB, p, 1, 1, 0;\n}\n"
    : "+f"(d[0]), "+f"(d[1]), "+f"(d[2]), "+f"(d[3]), "+f"(d[4]), "+f"(d[5]), "+f"(d[6]), "+f"(d[7]),
      "+f"(d[8]), "+f"(d[9]), "+f"(d[10]), "+f"(d[11]), "+f"(d[12]), "+f"(d[13]), "+f"(d[14]), "+f"(d[15]),
      "+f"(d[16]), "+f"(d[17]), "+f"(d[18]), "+f"(d[19]), "+f"(d[20]), "+f"(d[21]), "+f"(d[22]), "+f"(d[23]),
      "+f"(d[24]), "+f"(d[25]), "+f"(d[26]), "+f"(d[27]), "+f"(d[28]), "+f"(d[29]), "+f"(d[30]), "+f"(d[31])
    : "r"(a0), "r"(a1), "r"(a2), "r"(a3), "r"(db), "r"(scale_d), "n"(HB));
}
template <uint32_t HB = 0x40000040u>
__device__ __forceinline__ void wg_rs64_z(float* d, uint32_t a0, uint32_t a1, uint32_t a2, uint32_t a3, uint32_t db) {
  asm volatile("{\n.reg .pred p;\n.reg .b64 dB;\nmov.b64 dB, {%36, %37};\nsetp.ne.b32 p, 0, 0;\n"
    "wgmma.mma_async.sync.aligned.m64n64k16.f32.bf16.bf16 "
    "{%0, %1, %2, %3, %4, %5, %6, %7, %8, %9, %10, %11, %12, %13, %14, %15, "
    "%16, %17, %18, %19, %20, %21, %22, %23, %24, %25, %26, %27, %28, %29, %30, %31}, "
    "{%32, %33, %34, %35}, dB, p, 1, 1, 0;\n}\n"
    : "=f"(d[0]), "=f"(d[1]), "=f"(d[2]), "=f"(d[3]), "=f"(d[4]), "=f"(d[5]), "=f"(d[6]), "=f"(d[7]),
      "=f"(d[8]), "=f"(d[9]), "=f"(d[10]), "=f"(d[11]), "=f"(d[12]), "=f"(d[13]), "=f"(d[14]), "=f"(d[15]),
      "=f"(d[16]), "=f"(d[17]), "=f"(d[18]), "=f"(d[19]), "=f"(d[20]), "=f"(d[21]), "=f"(d[22]), "=f"(d[23]),
      "=f"(d[24]), "=f"(d[25]), "=f"(d[26]), "=f"(d[27]), "=f"(d[28]), "=f"(d[29]), "=f"(d[30]), "=f"(d[31])
    : "r"(a0), "r"(a1), "r"(a2), "r"(a3), "r"(db), "n"(HB));
}
template <uint32_t HB = 0x40000040u>
__device__ __forceinline__ void wg_rs32(float* d, uint32_t a0, uint32_t a1, uint32_t a2, uint32_t a3, uint32_t db, int scale_d) {
  asm volatile("{\n.reg .pred p;\n.reg .b64 dB;\nmov.b64 dB, {%20, %22};\nsetp.ne.b32 p, %21, 0;\n"
    "wgmma.mma_async.sync.aligned.m64n32k16.f32.bf16.bf16 "
    "{%0, %1, %2, %3, %4, %5, %6, %7, %8, %9, %10, %11, %12, %13, %14, %15}, "
    "{%16, %17, %18, %19}, dB, p, 1, 1, 0;\n}\n"
    : "+f"(d[0]), "+f"(d[1]), "+f"(d[2]), "+f"(d[3]), "+f"(d[4]), "+f"(d[5]), "+f"(d[6]), "+f"(d[7]),
      "+f"(d[8]), "+f"(d[9]), "+f"(d[10]), "+f"(d[11]), "+f"(d[12]), "+f"(d[13]), "+f"(d[14]), "+f"(d[15])
    : "r"(a0), "r"(a1), "r"(a2), "r"(a3), "r"(db), "r"(scale_d), "n"(HB));
}
template <uint32_t HB = 0x40000040u>
__device__ __forceinline__ void wg_rs32_z(float* d, uint32_t a0, uint32_t a1, uint32_t a2, uint32_t a3, uint32_t db) {
  asm volatile("{\n.reg .pred p;\n.reg .b64 dB;\nmov.b64 dB, {%20, %21};\nsetp.ne.b32 p, 0, 0;\n"
    "wgmma.mma_async.sync.aligned.m64n32k16.f32.bf16.bf16 "
    "{%0, %1, %2, %3, %4, %5, %6, %7, %8, %9, %10, %11, %12, %13, %14, %15}, "
    "{%16, %17, %18, %19}, dB, p, 1, 1, 0;\n}\n"
    : "=f"(d[0]), "=f"(d[1]), "=f"(d[2]), "=f"(d[3]), "=f"(d[4]), "=f"(d[5]), "=f"(d[6]), "=f"(d[7]),
      "=f"(d[8]), "=f"(d[9]), "=f"(d[10]), "=f"(d[11]), "=f"(d[12]), "=f"(d[13]), "=f"(d[14]), "=f"(d[15])
    : "r"(a0), "r"(a1), "r"(a2), "r"(a3), "r"(db), "n"(HB));
}
template <uint32_t HB = 0x40000040u>
__device__ __forceinline__ void wg_rs40t(float* d, uint32_t a0, uint32_t a1, uint32_t a2, uint32_t a3, uint32_t db, int scale_d) {
  asm volatile("{\n.reg .pred p;\n.reg .b64 dB;\nmov.b64 dB, {%24, %26};\nsetp.ne.b32 p, %25, 0;\n"
    "wgmma.mma_async.sync.aligned.m64n40k16.f32.bf16.bf16 "
    "{%0, %1, %2, %3, %4, %5, %6, %7, %8, %9, %10, %11, %12, %13, %14, %15, "
    "%16, %17, %18, %19}, "
    "{%20, %21, %22, %23}, dB, p, 1, 1, 1;\n}\n"
    : "+f"(d[0]), "+f"(d[1]), "+f"(d[2]), "+f"(d[3]), "+f"(d[4]), "+f"(d[5]), "+f"(d[6]), "+f"(d[7]),
      "+f"(d[8]), "+f"(d[9]), "+f"(d[10]), "+f"(d[11]), "+f"(d[12]), "+f"(d[13]), "+f"(d[14]), "+f"(d[15]),
      "+f"(d[16]), "+f"(d[17]), "+f"(d[18]), "+f"(d[19])
    : "r"(a0), "r"(a1), "r"(a2), "r"(a3), "r"(db), "r"(scale_d), "n"(HB));
}
template <uint32_t HB = 0x40000040u>
__device__ __forceinline__ void wg_rs40t_z(float* d, uint32_t a0, uint32_t a1, uint32_t a2, uint32_t a3, uint32_t db) {
  asm volatile("{\n.reg .pred p;\n.reg .b64 dB;\nmov.b64 dB, {%24, %25};\nsetp.ne.b32 p, 0, 0;\n"
    "wgmma.mma_async.sync.aligned.m64n40k16.f32.bf16.bf16 "
    "{%0, %1, %2, %3, %4, %5, %6, %7, %8, %9, %10, %11, %12, %13, %14, %15, "
    "%16, %17, %18, %19}, "
    "{%20, %21, %22, %23}, dB, p, 1, 1, 1;\n}\n"
    : "=f"(d[0]), "=f"(d[1]), "=f"(d[2]), "=f"(d[3]), "=f"(d[4]), "=f"(d[5]), "=f"(d[6]), "=f"(d[7]),
      "=f"(d[8]), "=f"(d[9]), "=f"(d[10]), "=f"(d[11]), "=f"(d[12]), "=f"(d[13]), "=f"(d[14]), "=f"(d[15]),
      "=f"(d[16]), "=f"(d[17]), "=f"(d[18]), "=f"(d[19])
    : "r"(a0), "r"(a1), "r"(a2), "r"(a3), "r"(db), "n"(HB));
}

constexpr uint32_t SOFF = 1024;
constexpr int STG = 57344, QE = 28672, SL_W = 16384, SL_HD = 12288, SL_F = 3 * STG, AT_ST = 131072;
constexpr int OFF_ONES = 4 * STG;
constexpr int OFF_PATCH = OFF_ONES + 1024;
constexpr int OFF_CS = OFF_PATCH + 768;
constexpr int OFF_BAR = OFF_CS + 768;
constexpr int OFF_MISC = OFF_BAR + 416;
constexpr int SMEM_BYTES = OFF_MISC + 96;
enum { B_FULL = 0, B_EMPTY = 6, B_HALO = 12, B_CS = 15, B_KVREADY, B_QDONE = B_KVREADY + 2, B_QREADY, B_OST, B_ADONE = B_OST + 2,
       B_QFREE, B_WS, B_WFULL, B_WEMPTY = B_WFULL + 4, B_GU = B_WEMPTY + 4, B_RES = B_GU + 2, B_DN,
       B_HX = B_DN + 2, B_RST, B_UNIT, B_COUNT = B_UNIT + 8 };
static_assert(B_COUNT <= 52, "barrier area");
__host__ __device__ constexpr int bar_count(int i) {
  return i >= B_EMPTY && i < B_HALO ? 17 : i == B_CS ? 4 : i == B_QFREE ? 16
       : i == B_KVREADY || i == B_KVREADY + 1 || i == B_QREADY ? 8 : i == B_ADONE ? 32 : i == B_OST ? 2 : i >= B_UNIT ? 4
       : i == B_QDONE || (i >= B_WEMPTY && i < B_GU) ? 16 : i == B_RST ? 4 : i == B_RES ? 2 : 1;
}
enum { M_KEY = 0, M_MEAN, M_INV, M_WSUM, M_TAG, M_SEL0, M_PMEAN, M_PINV, M_XQ = 8, M_KEYS = 12, M_PROG = 20 };
constexpr int FFN_PIECE = 14336;
constexpr int T_XS = 163840, T_HP = T_XS + 1024;
constexpr float LSUM_MIN = 5.421010862427522e-20f, LSUM_MAX = 1.8446744073709552e19f;
constexpr float SM_C = 0.17677669529663687f * 1.4426950408889634f;
constexpr uint32_t VSTEP = 64u - (64u << 16);
#define D_SPLIT 1
#define WS1_PACE 1000
#define WS_AT 5
#define WS_PACE 1000
#define GUB_PACE 800
#define ULIST1 0x854
#define ULIST2 0x8721
#define RES_K 6
#define FAKE 0
#define X_STAGGER 500
#define GU_PACE1 1600
#define GU_PACE 2500
#define DELAY_P 600
#define DELAY_S 2400
#define DELAY_Y 400

struct Params {
  CUtensorMap mapA[2], mapW, mapWo, mapRes[2], mapXst[2], mapG, mapU, mapD, mapWs;
  const bf16 *x, *wqkv, *wo, *w_r, *w_g, *w_u, *w_d;
  bf16* out;
};

template <int N> __device__ __forceinline__ void exp_pack(const float* s, uint32_t* p) {
#pragma unroll
  for (int b = 0; b < N; b++) {
    p[2 * b] = pack_bf16(ex2(s[4 * b]), ex2(s[4 * b + 1]));
    p[2 * b + 1] = pack_bf16(ex2(s[4 * b + 2]), ex2(s[4 * b + 3]));
  }
}
template <int KIND> __device__ __forceinline__ void edge16(const float* sd, const float* st, uint32_t* pd, uint32_t* pt, int dl, uint32_t mt) {
  if (KIND == 0) { exp_pack<2>(sd, pd); pt[0] = pt[1] = pt[2] = pt[3] = 0; }
  else if (KIND == 1) { exp_pack<2>(st, pt); pd[0] = pd[1] = pd[2] = pd[3] = 0; }
  else {
    const uint32_t a = pack_bf16(ex2(dl >= 0 ? sd[0] : st[0]), ex2(dl >= 1 ? sd[1] : st[1]));
    const uint32_t c = pack_bf16(ex2(dl >= 0 ? sd[6] : st[6]), ex2(dl >= 1 ? sd[7] : st[7]));
    pd[0] = a & ~mt; pt[0] = a & mt; pd[3] = c & ~mt; pt[3] = c & mt;
    pd[1] = pack_bf16(ex2(sd[2]), ex2(sd[3])); pt[1] = 0;
    pt[2] = pack_bf16(ex2(st[4]), ex2(st[5])); pd[2] = 0;
  }
}
__device__ __forceinline__ void edge32(const float* sd, const float* st, uint32_t* pd, uint32_t* pt, int rel, int dl, uint32_t mt) {
  if (rel > 1) { edge16<0>(sd, st, pd, pt, dl, mt); edge16<0>(sd + 8, st + 8, pd + 4, pt + 4, dl, mt); }
  else if (rel == 1) { edge16<0>(sd, st, pd, pt, dl, mt); edge16<2>(sd + 8, st + 8, pd + 4, pt + 4, dl, mt); }
  else if (rel == 0) { edge16<2>(sd, st, pd, pt, dl, mt); edge16<1>(sd + 8, st + 8, pd + 4, pt + 4, dl, mt); }
  else { edge16<1>(sd, st, pd, pt, dl, mt); edge16<1>(sd + 8, st + 8, pd + 4, pt + 4, dl, mt); }
}
__device__ __forceinline__ void qk64(float* s, const uint32_t* qf, uint32_t kd) {
  wg_rs64_z<H64>(s, qf[0], qf[1], qf[2], qf[3], kd);
  wg_rs64<H64>(s, qf[4], qf[5], qf[6], qf[7], kd + 2, 1);
}
__device__ __forceinline__ void qk32x2(float* a, float* b, const uint32_t* qf, uint32_t ka, uint32_t kb) {
  wg_rs32_z<H64>(a, qf[0], qf[1], qf[2], qf[3], ka); wg_rs32_z<H64>(b, qf[0], qf[1], qf[2], qf[3], kb);
  wg_rs32<H64>(a, qf[4], qf[5], qf[6], qf[7], ka + 2, 1); wg_rs32<H64>(b, qf[4], qf[5], qf[6], qf[7], kb + 2, 1);
}
__device__ __forceinline__ void pv32(float* o, const uint32_t* p, uint32_t vd) {
  wg_rs40t<H64>(o, p[0], p[1], p[2], p[3], vd, 1);
  wg_rs40t<H64>(o, p[4], p[5], p[6], p[7], vd + VSTEP, 1);
}

__device__ __forceinline__ void fma8(float* d, uint4 w, float x) {
  d[0] += x * bf_lo(w.x); d[1] += x * bf_hi(w.x); d[2] += x * bf_lo(w.y); d[3] += x * bf_hi(w.y);
  d[4] += x * bf_lo(w.z); d[5] += x * bf_hi(w.z); d[6] += x * bf_lo(w.w); d[7] += x * bf_hi(w.w);
}

__device__ __forceinline__ int fresh_tid() { int r; asm volatile("mov.u32 %0, %%tid.x;" : "=r"(r)); return r; }
__device__ __forceinline__ int fresh_bid() { int r; asm volatile("mov.u32 %0, %%ctaid.x;" : "=r"(r)); return r; }
#define PHASE_IDS                                                                                                              \
  const uint32_t sbase = smem_u32(smem);                                                                                       \
  const int tid = fresh_tid(), bid = fresh_bid();                                                                              \
  const int warp = __shfl_sync(0xffffffffu, tid >> 5, 0), lane = tid & 31;                                                     \
  const int rank = bid & 1, cl = bid >> 1, rb = bid & 7, hp = bid >> 3;                  \
  const int mb = 2 * rb + (hp >> 3), nb = hp & 7;                                            \
  const int wg = warp >> 2, wi = warp & 3, g = lane >> 2, q = lane & 3;                                                        \
  const int mi = lane >> 3, srow = wi * 16 + (mi & 1) * 8 + (lane & 7);      \
  auto bar = [&](int i) { return sbase + OFF_BAR + 8 * i; };                                                                   \
  volatile uint32_t* s_misc = (volatile uint32_t*)(smem + OFF_MISC);                                                           \
  auto load_w = [&](int s, int kt) {                           \
    tma_load3_mc(sbase + s * QE + SL_W + rank * 6144, &P.mapW, hp * 64, kt * 32 + rank * 16, 0, bar(B_FULL + s));              \
  };                                                                                                                           \
  auto load_a = [&](int s, int kt, int layer) { mbar_expect_tx(bar(B_FULL + s), QE); tma_load2(sbase + s * QE, &P.mapA[layer], kt * 32, rb * 256, bar(B_FULL + s)); }; \
  auto load_wo = [&](int k) {                                                 \
    mbar_expect_tx(bar(B_WFULL + (k & 3)), 32768);                                                                             \
    tma_load3_mc(sbase + (k & 3) * 32768 + 16384 + rank * 8192, &P.mapWo, nb * 128 + rank * 64, (k >> 3) * 32, (k & 7) * 2, bar(B_WFULL + (k & 3))); \
  };                                                                                                                           \
  auto load_o = [&](int k) {                                                            \
    bulk_load_h(sbase + (k & 3) * 32768, g_o + (size_t)(mb * 16 + k) * 16384, 16384, bar(B_WFULL + (k & 3)), policy_evict_first());                    \
  };                                                                                                                           \
  auto import_halo = [&](int layer, int h) {                                   \
    poll_flag(&g_kvflag[(rb - 1) >> 1][hp][h].v[layer], s_misc[M_TAG]);                                                        \
    fence_async_global();                                                                                                      \
    const uint8_t* src = g_kv + (size_t)(((rb - 1) >> 1) * 16 + hp) * 65536 + h * 32768;                                       \
    mbar_expect_tx(bar(B_HALO + 2 * h), 16384 << h);                                                                           \
    bulk_load_h(sbase + (h ? 65536 : 16384), src + (h ? 0 : 16384), 16384 << h, bar(B_HALO + 2 * h), policy_evict_first());    \
    if (h == 0) { mbar_expect_tx(bar(B_HALO + 1), 16384); bulk_load_h(sbase, src, 16384, bar(B_HALO + 1), policy_evict_first()); } \
  };                                                                                                                           \
  auto load_res = [&](int half, int layer) {                                                  \
    mbar_expect_tx(bar(B_RES), 16384);                                                                                         \
    tma_load2_h(sbase + AT_ST + half * 16384, &P.mapRes[layer], nb * 128, mb * 128 + half * 64, bar(B_RES), policy_evict_first());                     \
    tma_load2_h(sbase + AT_ST + half * 16384 + 8192, &P.mapRes[layer], nb * 128 + 64, mb * 128 + half * 64, bar(B_RES), policy_evict_first());         \
  };                                                                                                                           \
  auto store_tile = [&](int layer, int skip, bool wait) {                                           \
    _Pragma("unroll 1")                                                                                                        \
    for (int j = 0; j < 4; j++)                                                                                                \
      if ((j & 1) != skip) tma_store(&P.mapXst[layer], sbase + AT_ST + (j & 1) * 16384 + (j >> 1) * 8192, nb * 128 + (j >> 1) * 64, mb * 128 + (j & 1) * 64); \
    bulk_commit();                                                                                                             \
    if (wait) bulk_wait_all();                                                                                                 \
  };                                                                                                                           \
  auto load_ws = [&](int pace) {                                    \
    mbar_expect_tx(bar(B_WS), 4 * SL_HD);                                                                                      \
    _Pragma("unroll 1")                                                                                                        \
    for (int j = 0; j < 4; j++) {                                                                                              \
      tma_load3(sbase + SL_F + j * SL_HD, &P.mapWs, hp * 64, rb * 128 + j * 32, 0, bar(B_WS));                                 \
      if (pace) spin_cycles(pace);                                                                                             \
    }                                                                                                                          \
  };                                                                                                                           \
  auto load_gu = [&](int half, int pace) {                             \
    mbar_expect_tx(bar(B_GU + half), 4 * FFN_PIECE);                                                                           \
    _Pragma("unroll 1")                                                                                                        \
    for (int j = 0; j < 4; j++) {                                                                                              \
      tma_load2_h(sbase + SL_F + j * FFN_PIECE, &P.mapG + (j >> 1), cl * 56, rank * 512 + half * 256 + (j & 1) * 128, bar(B_GU + half), policy_evict_first()); \
      if (j < 3) spin_cycles(pace);                                                                                            \
    }                                                                                                                          \
  };                                                                                                                           \
  auto fetch_gu = [&](uint32_t* a, int ks, int ct) {                 \
    ldsm_x4_t(sbase + SL_F + (mi & 1) * 2 * FFN_PIECE + (ks * 16 + (mi >> 1) * 8 + (lane & 7)) * 112 + ct * 16, a[0], a[1], a[2], a[3]); \
  };                                                                                                                           \
  auto send_gu = [&](float gate, float up, int ct, int part) {        \
    const int u = 8 * ct + g, own = u >= 28;                                                                                   \
    if (q == 0) st_async2(mapa(sbase + T_HP + ((rank * 5 + part) * 28 + u - 28 * own) * 8, own), gate, up, mapa(bar(B_HX), own)); \
  };                                                                                                                           \
  auto hidden = [&]() {                                     \
    const float2* hpart = (const float2*)(smem + T_HP) + min(lane, 27);                                                        \
    float gs[2] = {0.f, 0.f}, us[2] = {0.f, 0.f};                                                                              \
    _Pragma("unroll")                                                                                                          \
    for (int j = 0; j < 10; j++) { const float2 v = hpart[j * 28]; gs[j & 1] += v.x; us[j & 1] += v.y; }                       \
    const float gb = rbf(gs[0] + gs[1]), ub = rbf(us[0] + us[1]);                                                              \
    return lane < 28 ? rbf(__fdividef(gb, 1.f + __expf(-gb))) * ub : 0.f;                                                      \
  };                                                                                                                           \
  (void)load_wo; (void)load_o; (void)import_halo; (void)load_res; (void)store_tile; (void)fetch_gu; (void)load_ws; (void)load_gu; (void)send_gu; (void)hidden; (void)cl; (void)mb; (void)nb; (void)wg; (void)g; (void)q; (void)srow; (void)s_misc; (void)load_w; (void)load_a;

__global__ void __launch_bounds__(512, 1) mega_kernel(const __grid_constant__ Params P) {
  extern __shared__ __align__(1024) uint8_t smem[];
  {
    PHASE_IDS
    if (warp == 0) {
      if (lane == 0) {
        prefetch_tmap(&P.mapA[0]); prefetch_tmap(&P.mapW);
#pragma unroll
        for (int i = 0; i < 6; i++) mbar_init(bar(B_FULL + i), 1);
        asm volatile("fence.mbarrier_init.release.cluster;" ::: "memory");
      }
      __syncwarp();
      load_a(0, 0, 0);
    } else if (tid == 32) {
#pragma unroll
      for (int i = 6; i < B_COUNT; i++) mbar_init(bar(i), bar_count(i));
      asm volatile("fence.mbarrier_init.release.cluster;" ::: "memory");
    } else if (warp == 8) {
      ((uint4*)(smem + OFF_ONES))[lane] = make_uint4(0x3F803F80u, 0x3F803F80u, 0x3F803F80u, 0x3F803F80u);
      ((uint4*)(smem + OFF_ONES))[lane + 32] = make_uint4(0x3F803F80u, 0x3F803F80u, 0x3F803F80u, 0x3F803F80u);
    }
    __syncwarp();
    cluster_arrive(); cluster_wait();
    if (warp == 0) {
#pragma unroll 1
      for (int i = 0; i < 6; i++) { load_w(i, i); if (i) load_a(i, i, 0); }
      PROFL(0, 1);
    } else if (warp == 1) {
      if (lane < 16) g_rowab[0][rb * 256 + hp * 16 + lane] = make_uint4(0, 0, 0, 0);
    } else if (warp == 2) {
      const int f = lane >> 1;
      Flag* fl = f < 2 ? &g_kvflag[rb >> 1][hp][f] : f < 4 ? &g_oflag[rb][f & 1][hp] : &g_xflag[mb][nb];
      if (f < 5 && (f >= 2 || (rank == 1 && rb < 7))) ((uint4*)fl)[lane & 1] = make_uint4(0, 0, 0, 0);
    } else if (tid == 96) {
      if ((sbase & 0x3FFFF) != SOFF) __trap();
#pragma unroll 1
      for (int i = 1; i < 12; i++) prefetch_tmap(&P.mapA[0] + i);
    }
    __syncwarp();
  }

  regs_dec<120>();
#pragma unroll 1
  for (unsigned pass_v = 0;;) {
    const unsigned pass = __shfl_sync(0xffffffffu, pass_v, 0);
    if (__shfl_sync(0xffffffffu, fresh_tid() >> 8, 0)) {
      if (pass > 0) {
        const unsigned layer = pass - 1;
        uint32_t xr[32];
        {
          PHASE_IDS
          float acc[64];
#pragma unroll
          for (int i = 0; i < 64; i++) acc[i] = 0.f;
          const uint32_t da0 = dlo(SOFF, 16) + (wg - 2) * 256;
          constexpr uint32_t db0 = dlo(SOFF + 16384, 8192);
#pragma unroll 1
          for (int k4 = 0; k4 < 4; k4++) {
#pragma unroll
            for (int st = 0; st < 4; st++) {
              mbar_wait(bar(B_WFULL + st), k4 & 1);
              wg_fence();
#pragma unroll
              for (int kk = 0; kk < 4; kk++)
                wg_ss128t<H64, H128>(acc, da0 + ((st * 32768) >> 4) + (kk >> 1) * 512 + (kk & 1) * 2, db0 + ((st * 32768) >> 4) + kk * 128, 1);
              wg_commit();
              if (st == 0 && k4 == 0 && warp == 9) PROF(10);
              if (warp == 9) STEPT(16 + k4 * 4 + st);
              wg_wait<1>();
              if (lane < 2 && (st == 0 ? k4 > 0 : (st < 3 || k4 < 3))) mbar_arrive_cluster(bar(B_WEMPTY + ((st + 3) & 3)), lane);
            }
          }
          mbar_wait(bar(B_RES), layer);
          mbar_wait(bar(B_RST), layer);
          const uint32_t zoff = AT_ST + (wg - 2) * 16384;
#pragma unroll
          for (int j = 0; j < 8; j++)
            ldsm_x4(sbase + zoff + srow * 128 + (j >> 2) * 8192 + ((((2 * j + (mi >> 1)) & 7) ^ (srow & 7)) << 4), xr[4 * j], xr[4 * j + 1], xr[4 * j + 2], xr[4 * j + 3]);
          wg_wait<0>();
          fence_regs<64>(acc);
          if (warp == 9) PROF(11);
          if (layer == 0 && lane < 2) mbar_arrive_cluster(bar(B_QFREE), lane);
#pragma unroll
          for (int j = 0; j < 32; j++) xr[j] = hadd_bf2(xr[j], pack_bf16(acc[2 * j], acc[2 * j + 1]));
        }
        PHASE_IDS
        const uint32_t tag = s_misc[M_TAG];
        const int grow = mb * 128 + (warp - 8) * 16 + g;
        {
          float d[6][4];
#pragma unroll
          for (int i = 0; i < 6; i++) d[i][0] = d[i][1] = d[i][2] = d[i][3] = 0.f;
          const uint4* tab = (const uint4*)(smem + OFF_PATCH + (g == 1 ? q * 64 : (g == 0 ? 256 : 320)));
#pragma unroll
          for (int j2 = 0; j2 < 4; j2++) {
            const uint4 w = tab[j2];
#pragma unroll
            for (int jj = 0; jj < 2; jj++) {
              const uint32_t* a = &xr[8 * j2 + 4 * jj];
              mma_16816(d[jj], a[0], a[1], a[2], a[3], jj ? w.z : w.x, jj ? w.w : w.y);
              mma_16816(d[2 + jj], a[0], a[1], a[2], a[3], a[0], a[2]);
              mma_16816(d[4 + jj], a[0], a[1], a[2], a[3], a[1], a[3]);
            }
          }
          const float sq0 = __shfl_sync(0xffffffffu, (g & 1) ? d[2][1] + d[3][1] : d[2][0] + d[3][0], g * 4 + (g >> 1));
          const float sq1 = __shfl_sync(0xffffffffu, (g & 1) ? d[4][3] + d[5][3] : d[4][2] + d[5][2], g * 4 + (g >> 1));
          uint4* dst = &g_part[layer][nb * SEQ + grow];
          if (q == 0) {
            st_relaxed4(dst, make_uint4(__float_as_uint(d[0][0] + d[1][0]), __float_as_uint(sq0), __float_as_uint(d[0][1] + d[1][1]), tag));
            st_relaxed4(dst + 8, make_uint4(__float_as_uint(d[0][2] + d[1][2]), __float_as_uint(sq1), __float_as_uint(d[0][3] + d[1][3]), tag));
          }
        }
        if (warp == 9) PROF(12);
        asm volatile("bar.arrive 6, 320;" ::: "memory");
        const int t_p = (int)clock();
        const uint32_t zrow = sbase + AT_ST + (wg - 2) * 16384 + srow * 128;
        if (layer == 0) {
#pragma unroll
          for (int j = 0; j < 8; j++)
            stsm_x4(zrow + (j >> 2) * 8192 + ((((2 * j + (mi >> 1)) & 7) ^ (srow & 7)) << 4), xr[4 * j], xr[4 * j + 1], xr[4 * j + 2], xr[4 * j + 3]);
          fence_async_smem();
          asm volatile("bar.arrive 8, 288;" ::: "memory");
        }
#pragma unroll 1
        while ((int)clock() - t_p < DELAY_P) {}
        {
          const uint4* src = &g_part[layer][2 * q * SEQ + grow];
          uint4 pp[4];
          uint32_t spins = 0;
#pragma unroll 1
          do {
            pp[0] = ld_relaxed4(src); pp[1] = ld_relaxed4(src + SEQ); pp[2] = ld_relaxed4(src + 8); pp[3] = ld_relaxed4(src + SEQ + 8);
          } while (!__all_sync(0xffffffffu, pp[0].w == tag && pp[1].w == tag && pp[2].w == tag && pp[3].w == tag) && ++spins < SPIN_LIMIT);
          if (warp == 9) PROF(13);
          const int rr = q >> 1;
          float s3[3];
#pragma unroll
          for (int c = 0; c < 3; c++) {
            const float lo = __uint_as_float(c == 0 ? pp[0].x : c == 1 ? pp[0].y : pp[0].z) + __uint_as_float(c == 0 ? pp[1].x : c == 1 ? pp[1].y : pp[1].z);
            const float hi = __uint_as_float(c == 0 ? pp[2].x : c == 1 ? pp[2].y : pp[2].z) + __uint_as_float(c == 0 ? pp[3].x : c == 1 ? pp[3].y : pp[3].z);
            s3[c] = (rr ? hi : lo) + __shfl_xor_sync(0xffffffffu, rr ? lo : hi, 2);
            s3[c] += __shfl_xor_sync(0xffffffffu, s3[c], 1);
          }
          const float mu = s3[0] * (1.f / DM), var = fmaxf(fmaf(-mu, mu, s3[1] * (1.f / DM)), 0.f);
          const float mn = rbf(mu), iv = ln_inv(var);
          const uint32_t ky = router_key(rbf((s3[2] - mn * __uint_as_float(s_misc[M_WSUM])) * iv), grow + 8 * rr);
          const uint32_t wbest = __reduce_max_sync(0xffffffffu, ky);
          s_misc[M_KEYS + warp - 8] = wbest;
          named_bar(5, 256);
          if (__reduce_max_sync(0xffffffffu, s_misc[M_KEYS + (lane & 7)]) == wbest) {
            if (nb == 0 && ky == wbest && (q & 1) == 0) st_relaxed4(&g_slot[layer][mb * 8], make_uint4(ky, __float_as_uint(mn), __float_as_uint(iv), tag));
            const int r = ~wbest & 15;
            if ((r & 7) == g) {
#pragma unroll
              for (int j = 0; j < 4; j++) {
                const uint32_t* a = &xr[8 * j];
                st_relaxed4(&g_cand[layer][mb * 128 + nb * 16 + q * 4 + j],
                            r < 8 ? make_uint4(nosent(a[0]), nosent(a[2]), nosent(a[4]), nosent(a[6])) : make_uint4(nosent(a[1]), nosent(a[3]), nosent(a[5]), nosent(a[7])));
              }
            }
            __syncwarp();
          }
          if (warp == 9) PROF(14);
          if (layer == 0) {
            if ((q & 1) == 0) {
              g_rowln[nb][grow + 8 * rr] = make_float2(mn, iv);
              if (warp - 8 == nb) {
                const float mu2 = mu + (mu - mn) * iv, inv2 = ln_inv(var * (1.f + iv) * (1.f + iv));
                st_relaxed4(&g_rowab[1][grow + 8 * rr], make_uint4(__float_as_uint((1.f + iv) * inv2), __float_as_uint((mn * iv + rbf(mu2)) * inv2), tag, 0));
              }
            }
            __syncwarp();
          } else {
            const float mo = __shfl_xor_sync(0xffffffffu, mn, 2), io = __shfl_xor_sync(0xffffffffu, iv, 2);
            const uint32_t m0 = pack_bf16(rr ? mo : mn, rr ? mo : mn), m1 = pack_bf16(rr ? mn : mo, rr ? mn : mo);
            const float i0 = rr ? io : iv, i1 = rr ? iv : io;
#pragma unroll
            for (int j = 0; j < 8; j++)
              stsm_x4(zrow + (j >> 2) * 8192 + ((((2 * j + (mi >> 1)) & 7) ^ (srow & 7)) << 4), add_ln_pair(xr[4 * j], m0, i0),
                      add_ln_pair(xr[4 * j + 1], m1, i1), add_ln_pair(xr[4 * j + 2], m0, i0), add_ln_pair(xr[4 * j + 3], m1, i1));
            fence_async_smem();
          }
          if (warp == 15) asm volatile("bar.arrive 7, 512;" ::: "memory");
        }
        if (warp < 15) {
          uint32_t gu[64];
          mbar_wait(bar(B_GU + 1), layer);
#pragma unroll
          for (int j = 0; j < 16; j++) fetch_gu(gu + 4 * j, j, warp - 8);
          fence_async_smem();
          float d[4][4] = {};
          named_bar(7, 512);
#pragma unroll
          for (int hf = 0; hf < 2; hf++) {
            uint4 xv[4] = {};
            if (g == 0) {
#pragma unroll
              for (int j = 0; j < 4; j++) xv[j] = ((const uint4*)(smem + T_XS))[32 + hf * 16 + j * 4 + q];
            }
            __syncwarp();
#pragma unroll
            for (int j = 0; j < 4; j++) {
              const uint32_t* a = gu + hf * 32 + j * 8;
              mma_16816(d[(j & 1) * 2], a[0], a[1], a[2], a[3], xv[j].x, xv[j].y);
              mma_16816(d[(j & 1) * 2 + 1], a[4], a[5], a[6], a[7], xv[j].z, xv[j].w);
            }
          }
          send_gu((d[0][0] + d[1][0]) + (d[2][0] + d[3][0]), (d[0][2] + d[1][2]) + (d[2][2] + d[3][2]), warp - 8, 4);
          __syncwarp();
        }
        if (layer == 0) asm volatile("bar.arrive 9, 512;" ::: "memory");
        else {
        uint32_t wd[64];
        mbar_wait(bar(B_DN), layer);
#pragma unroll
        for (int j = 0; j < 16; j++) {
          const uint32_t row = sbase + ((warp - 8) * 2 + (j >> 3)) * 3584 + min((j & 1) * 16 + (mi >> 1) * 8 + (lane & 7), 27) * 128;
          ldsm_x4_t(row + ((((j & 6) + (mi & 1)) ^ ((row >> 7) & 7)) << 4), wd[4 * j], wd[4 * j + 1], wd[4 * j + 2], wd[4 * j + 3]);
        }
        fence_regs_u<64>(wd);
        mbar_wait_cluster(bar(B_HX), layer);
        uint32_t hf[4];
        {
          const float hv = hidden();
          const uint32_t hp2 = pack_bf16(hv, __shfl_down_sync(0xffffffffu, hv, 1));
#pragma unroll
          for (int j = 0; j < 4; j++) hf[j] = __shfl_sync(0xffffffffu, hp2, 8 * j + 2 * q);
        }
        if (warp == 9) PROF(19);
        float y[4][4] = {};
#pragma unroll
        for (int j = 0; j < 16; j++)
          mma_16816(y[j & 3], wd[4 * j], wd[4 * j + 1], wd[4 * j + 2], wd[4 * j + 3], g == j >> 1 ? hf[(j & 1) * 2] : 0u, g == j >> 1 ? hf[(j & 1) * 2 + 1] : 0u);
        {
          float e[4];
#pragma unroll
          for (int c = 0; c < 4; c++) { const int i = (c & 1) * 2 + (c >> 1); e[c] = (y[0][i] + y[1][i]) + (y[2][i] + y[3][i]); }
          const bool b0 = g & 1, b1 = g & 2;
          float t0 = __shfl_xor_sync(0xffffffffu, b0 ? e[0] : e[1], 4), t1 = __shfl_xor_sync(0xffffffffu, b0 ? e[2] : e[3], 4);
          const float f0 = b0 ? t0 : e[0], f1 = b0 ? e[1] : t0, f2 = b0 ? t1 : e[2], f3 = b0 ? e[3] : t1;
          t0 = __shfl_xor_sync(0xffffffffu, b1 ? f0 : f2, 8); t1 = __shfl_xor_sync(0xffffffffu, b1 ? f1 : f3, 8);
          st_relaxed4(&g_ypart[layer][bid * 256 + (warp - 8) * 32 + (q * 4 + (g & 3)) * 2 + (g >> 2)],
                      b1 ? make_uint4(f2u(t0), f2u(t1), f2u(f2), f2u(f3)) : make_uint4(f2u(f0), f2u(f1), f2u(t0), f2u(t1)));
        }
        if (warp == 9) PROF(20);
        asm volatile("bar.arrive 9, 384;" ::: "memory");
        cluster_arrive(); cluster_wait();
        return;
        }
      }
      const unsigned layer = pass;
      named_bar(1 + (fresh_tid() >> 7), 128);
      regs_inc<224>();
      float acc[2][96];
      {
        PHASE_IDS
        const uint32_t da0 = dlo(SOFF, 16) + (wg - 2) * 256;
        constexpr uint32_t db0 = dlo(SOFF + SL_W, 2048);
        mbar_wait(bar(B_FULL), 0);
        if (warp == 9) PROF(29);
        if (warp == 9) STEPT(0);
        wg_fence();
        wg_ss192t_z<H64, H128>(acc[0], da0, db0); wg_ss192t_z<H64, H128>(acc[1], da0 + 512, db0);
        wg_ss192t<H64, H128>(acc[0], da0 + 2, db0 + 384, 1); wg_ss192t<H64, H128>(acc[1], da0 + 514, db0 + 384, 1);
        wg_commit();
        int s = 1, u = 0;
#pragma unroll 1
        for (int i = 1; i < 32; i++) {
          const uint32_t da = da0 + s * (QE >> 4), db = db0 + s * (QE >> 4);
          mbar_wait(bar(B_FULL + s), (u + (s > 1 ? layer : 0)) & 1);
          if (warp == 9 && !(i & 1)) STEPT(i >> 1);
          wg_fence();
          wg_ss192t<H64, H128>(acc[0], da, db, 1); wg_ss192t<H64, H128>(acc[1], da + 512, db, 1);
          wg_ss192t<H64, H128>(acc[0], da + 2, db + 384, 1); wg_ss192t<H64, H128>(acc[1], da + 514, db + 384, 1);
          wg_commit();
          wg_wait<1>();
          if (lane < 2 && i < 27) mbar_arrive_cluster(bar(B_EMPTY + (s == 0 ? 5 : s - 1)), lane);
          if (++s == 6) { s = 0; u++; }
        }
      }
      PHASE_IDS
      mbar_wait(bar(B_CS), layer);
      float pa[2][2], pb[2][2];
      {
        const uint32_t tag = s_misc[M_TAG];
        const uint4* src = &g_rowab[layer][rb * 256 + (wg - 2 + (lane >> 4) * 2) * 64 + wi * 16 + (lane & 15)];
        uint4 v;
        uint32_t spins = 0;
#pragma unroll 1
        do { v = ld_relaxed4(src); } while (!__all_sync(0xffffffffu, v.z == tag) && ++spins < SPIN_LIMIT);
#pragma unroll
        for (int j = 0; j < 4; j++) {
          pa[j >> 1][j & 1] = __uint_as_float(__shfl_sync(0xffffffffu, v.x, g + 8 * j));
          pb[j >> 1][j & 1] = __uint_as_float(__shfl_sync(0xffffffffu, v.y, g + 8 * j));
        }
      }
      const int prow = (int)s_misc[M_SEL0] - rb * 256;
      const bool patch = ((prow - (wg - 2) * 64 - wi * 16) & ~0x8F) == 0;
      const float* cs = (const float*)(smem + OFF_CS);
      auto finish = [&](int m, int b, float2 c, uint32_t* dst) {
        dst[0] = pack_bf16(acc[m][4 * b] * pa[m][0] - c.x * pb[m][0], acc[m][4 * b + 1] * pa[m][0] - c.y * pb[m][0]);
        dst[1] = pack_bf16(acc[m][4 * b + 2] * pa[m][1] - c.x * pb[m][1], acc[m][4 * b + 3] * pa[m][1] - c.y * pb[m][1]);
      };
      wg_wait<0>();
      fence_regs<96>(acc[0]); fence_regs<96>(acc[1]);
      if (warp != 9) STEPT(1);
      if (lane < 2) mbar_arrive_cluster(bar(B_QDONE), lane);
      if (warp == 9) PROF(2);
#pragma unroll
      for (int h = 0; h < 2; h++) {
        const uint32_t dst = sbase + (h * 8 + 2 + wg) * 8192 + srow * 64;
#pragma unroll
        for (int jj = 0; jj < 4; jj++) {
          const int b = 8 + (jj >> 1) * 8 + h * 4 + (jj & 1) * 2;
          const float2 c0 = *(const float2*)&cs[8 * b + 2 * q], c1 = *(const float2*)&cs[8 * b + 8 + 2 * q];
          uint32_t r[2][4];
#pragma unroll
          for (int m = 0; m < 2; m++) { finish(m, b, c0, r[m]); finish(m, b + 1, c1, r[m] + 2); }
          if (h == 0 && jj == 0) named_bar(5, 256);
#pragma unroll
          for (int m = 0; m < 2; m++)
            stsm_x4(dst + m * 16384 + (jj >> 1) * 4096 + ((((jj & 1) * 2 + (mi >> 1)) ^ ((srow >> 1) & 3)) << 4), r[m][0], r[m][1], r[m][2], r[m][3]);
        }
        if (patch) {
          __syncwarp();
          if (lane < 8)
            *(uint4*)(smem + (h * 8 + 4 + (prow >> 6)) * 8192 + g * 4096 + (prow & 63) * 64 + ((q ^ ((prow >> 1) & 3)) << 4)) =
                *(const uint4*)(smem + OFF_PATCH + 128 + g * 128 + h * 64 + q * 16);
        }
        fence_async_smem();
        __syncwarp();
        mbar_arrive_e(bar(B_KVREADY + h));
        if (warp != 9) STEPT(2 + h);
      }
#pragma unroll
      for (int j = 0; j < 4; j++) { pa[j >> 1][j & 1] *= SM_C; pb[j >> 1][j & 1] *= SM_C; }
#pragma unroll
      for (int jj = 0; jj < 4; jj++) {
        const float2 c0 = *(const float2*)&cs[16 * jj + 2 * q], c1 = *(const float2*)&cs[16 * jj + 8 + 2 * q];
#pragma unroll
        for (int m = 0; m < 2; m++) {
          uint32_t r[4];
          finish(m, 2 * jj, c0, r); finish(m, 2 * jj + 1, c1, r + 2);
          *(uint4*)(smem + AT_ST + ((jj >> 1) * 16 + warp - 8 + 8 * m) * 1024 + (jj & 1) * 512 + lane * 16) = make_uint4(r[0], r[1], r[2], r[3]);
        }
      }
      __syncwarp();
      if (patch) {
        *(uint32_t*)(smem + AT_ST + ((lane >> 4) * 16 + (prow >> 4)) * 1024 + (mi & 1) * 512 + ((prow & 7) * 4 + q) * 16 + ((g & 1) * 2 + ((prow >> 3) & 1)) * 4) =
            *(const uint32_t*)(smem + OFF_PATCH + lane * 4);
        __syncwarp();
      }
      if (warp == 9) PROF(3);
      mbar_arrive_e(bar(B_QREADY));
      regs_dec<120>();
    } else {
      if (pass > 0) {
        const unsigned layer = pass - 1;
        PHASE_IDS
        const uint32_t tag = s_misc[M_TAG];
        if (warp == 7) {
              uint32_t* tab = (uint32_t*)(smem + OFF_PATCH);
#pragma unroll
              for (int j = 0; j < 2; j++) { const int w = lane + 32 * j; tab[(w & 3) * 16 + (w >> 2)] = ((const uint32_t*)P.w_r)[nb * 64 + w]; }
              tab[64 + lane] = lane < 16 ? 0x3F803F80u : 0u;
              float tot = 0.f;
#pragma unroll
              for (int j = 0; j < 4; j++) {
                const uint4 u = ((const uint4*)P.w_r)[lane + 32 * j];
                tot += bf_lo(u.x) + bf_hi(u.x) + bf_lo(u.y) + bf_hi(u.y) + bf_lo(u.z) + bf_hi(u.z) + bf_lo(u.w) + bf_hi(u.w);
              }
              s_misc[M_WSUM] = __float_as_uint(warp_sum(tot));
        }
              if (layer == 1) {
                const float2 ln = g_rowln[nb][mb * 128 + tid - 128];
                const uint32_t m2 = pack_bf16(ln.x, ln.x);
                uint8_t* row = smem + AT_ST + (wi >> 1) * 16384 + (tid & 63) * 128;
                mbar_wait(bar(B_RES), 1);
#pragma unroll 1
                for (int j = 0; j < 8; j++) {
                  uint4* c = (uint4*)(row + (((j + lane) & 7) << 4));
                  const uint4 v = c[0], w = c[512];
                  c[0] = make_uint4(add_ln_pair(v.x, m2, ln.y), add_ln_pair(v.y, m2, ln.y), add_ln_pair(v.z, m2, ln.y), add_ln_pair(v.w, m2, ln.y));
                  c[512] = make_uint4(add_ln_pair(w.x, m2, ln.y), add_ln_pair(w.y, m2, ln.y), add_ln_pair(w.z, m2, ln.y), add_ln_pair(w.w, m2, ln.y));
                }
                const int prow = (int)s_misc[M_SEL0] - mb * 128;
                __syncwarp();
                if (prow >> 5 == wi && lane < 16)
                  *(uint4*)(smem + AT_ST + (prow >> 6) * 16384 + (lane >> 3) * 8192 + (prow & 63) * 128 + (((lane ^ prow) & 7) << 4)) = poll4(&g_x2row[(nb * 16 + lane) * 2]);
                PROF(30);
              }
              __syncwarp();
              mbar_arrive_e(bar(B_RST));
        if (warp == 4) {
            named_bar(6, 320);
            spin_cycles(DELAY_S);
            uint4 c, u0, u1;
            uint32_t u2, best = 0, spins = 0;
            int src;
#pragma unroll 1
            for (;;) {
              src = (~best & 0x7FFu) >> 7;
              const uint4* xsel = &g_cand[layer][src * 128];
              c = ld_relaxed4(&g_slot[layer][(lane & 15) * 8]);
              u0 = ld_relaxed4(xsel + rank * 64 + lane); u1 = ld_relaxed4(xsel + rank * 64 + 32 + lane);
              u2 = ld_relaxed((const uint32_t*)(xsel + (bid >> 4) * 16 + q * 4) + (bid & 15));
              const uint32_t prev = best;
              best = __reduce_max_sync(0xffffffffu, c.w == tag ? c.x : 0u);
              if ((__all_sync(0xffffffffu, c.w == tag && valid4(u0) && valid4(u1) && u2 != SENT) && best == prev) || ++spins > SPIN_LIMIT) break;
            }
            const float sel_m = __uint_as_float(__shfl_sync(0xffffffffu, c.y, src)), sel_inv = __uint_as_float(__shfl_sync(0xffffffffu, c.z, src));
            const uint32_t m2 = pack_bf16(sel_m, sel_m);
            uint4* xs = (uint4*)(smem + T_XS) + (lane & 16) + q * 4 + (g & 3);
            xs[0] = make_uint4(ln_pair(u0.x, m2, sel_inv), ln_pair(u0.y, m2, sel_inv), ln_pair(u0.z, m2, sel_inv), ln_pair(u0.w, m2, sel_inv));
            xs[32] = make_uint4(ln_pair(u1.x, m2, sel_inv), ln_pair(u1.y, m2, sel_inv), ln_pair(u1.z, m2, sel_inv), ln_pair(u1.w, m2, sel_inv));
            s_misc[M_KEY] = best; s_misc[M_MEAN] = __float_as_uint(sel_m); s_misc[M_INV] = __float_as_uint(sel_inv);
            s_misc[M_XQ + q] = u2;
            PROF(16);
        }
        if (layer == 1) {
          named_bar(7, 512);
          const int sel = SEQ - 1 - (int)(s_misc[M_KEY] & 0x7FFFu), skip = sel >> 7 == mb ? (sel >> 6) & 1 : -1;
          if (warp == 7) store_tile(1, skip, false);
#pragma unroll 1
          for (int c = tid - 128; c < 1024 && skip >= 0; c += 128) {
            const int r = c >> 4;
            if (r != (sel & 63))
              *(uint4*)(P.out + (size_t)(mb * 128 + skip * 64 + r) * DM + nb * 128 + (c & 15) * 8) =
                  *(const uint4*)(smem + AT_ST + skip * 16384 + ((c >> 3) & 1) * 8192 + r * 128 + (((c ^ r) & 7) << 4));
          }
          __syncwarp();
        } else asm volatile("bar.arrive 7, 512;" ::: "memory");
        if (warp == 5 && layer == 0) {
              named_bar(8, 288);
              if (nb > 0) spin_cycles(X_STAGGER);
              store_tile(0, -1, true);
              set_flag(&g_xflag[mb][nb].v[0], tag);
              PROF(17);
              poll_flag(&g_xflag[2 * rb + (lane & 1)][0].v[0], tag);
              fence_async_global();
#pragma unroll 1
              for (int i = 0; i < 4; i++) load_a(i, i, 1);
              PROFL(1, 1);
        }
      }
      named_bar(1 + (fresh_tid() >> 7), 128);
      regs_dec<32>();
#pragma unroll 1
      for (;;) {
      const unsigned pass = __shfl_sync(0xffffffffu, pass_v, 0);
      if (pass > 0) {
        const unsigned layer = pass - 1;
        PHASE_IDS
        const uint32_t tag = s_misc[M_TAG], bkey = s_misc[M_KEY];
        const int sel = SEQ - 1 - (int)(bkey & 0x7FFFu);
        if (warp == 3) {
          if (layer == 1) {
#pragma unroll
            for (int j = 0; j < 3; j++) ((uint4*)g_vw)[bid * 96 + j * 32 + lane] = make_uint4(0, 0, 0, 0);
          } else s_misc[M_SEL0] = sel;
          if (bid == 0 && lane == 0) g_sel[layer] = sel;
        }
        __syncwarp();
        if (layer == 0) {
          auto load_down = [&](int j) {
            mbar_expect_tx(bar(B_DN + j), 2 * FFN_PIECE);
            bulk_load_h(sbase + SL_F + j * 2 * FFN_PIECE, P.w_d + (size_t)(bid * 28 + j * 14) * DM, 2 * FFN_PIECE, bar(B_DN + j), policy_evict_first());
          };
          if (warp == 5) {
            poll_flag(&g_xflag[2 * rb + (lane & 1)][(lane >> 1) & 7].v[0], tag);
            fence_async_global();
            load_a(4, 4, 1); load_a(5, 5, 1);
          }
          float hv = 0.f;
          if (wg == 1) { mbar_wait_cluster(bar(B_HX), 0); hv = rbf(hidden()); fence_regs<1>(&hv); }
          named_bar(9, 512);
          if (warp == 0) {
            fence_async_smem();
            if (lane < 16) mbar_arrive_cluster(bar(B_QFREE), lane & 1);
            mbar_wait(bar(B_QFREE), 1);
            load_w(4, 4); load_w(5, 5);
            load_down(0);
          } else if (wg == 1) {
            if (warp == 4) { mbar_wait(bar(B_DN), 0); load_down(1); }
            float d[8] = {0.f, 0.f, 0.f, 0.f, 0.f, 0.f, 0.f, 0.f};
#pragma unroll 1
            for (int j = 0; j < 28; j += 2) {
              if (j == 0 || j == 14) mbar_wait(bar(B_DN + (j > 0)), 0);
              const uint4 w0 = *(const uint4*)(smem + SL_F + j * 2048 + (tid - 128) * 16), w1 = *(const uint4*)(smem + SL_F + j * 2048 + 2048 + (tid - 128) * 16);
              fma8(d, w0, __shfl_sync(0xffffffffu, hv, j));
              fma8(d, w1, __shfl_sync(0xffffffffu, hv, j + 1));
            }
            uint4* dst = &g_ypart[0][bid * 256 + (tid - 128) * 2];
            st_relaxed4(dst, make_uint4(f2u(d[0]), f2u(d[1]), f2u(d[2]), f2u(d[3])));
            st_relaxed4(dst + 1, make_uint4(f2u(d[4]), f2u(d[5]), f2u(d[6]), f2u(d[7])));
            asm volatile("bar.arrive 11, 160;" ::: "memory");
            PROF(20);
          } else if (warp == 2) {
            named_bar(11, 160);
            fence_async_smem();
            load_ws(WS1_PACE);
          }
        } else {
          if (wg == 1) named_bar(9, 384);
        }
        if (wg == 1) {
          const int t_y = (int)clock();
          const uint32_t xw = s_misc[M_XQ + ((lane & 7) >> 1)];
          const float x = (lane & 1) ? bf_hi(xw) : bf_lo(xw);
          float xn = rbf(rbf(x - __uint_as_float(s_misc[M_MEAN])) * __uint_as_float(s_misc[M_INV]));
          uint32_t u = bkey & 0xFFFF0000u;
          u = (u & 0x80000000u) ? (u & 0x7FFFFFFFu) : (~u & 0xFFFF0000u);
          float sg = rbf(__fdividef(1.f, 1.f + __expf(-__uint_as_float(u))));
          uint32_t* dst = (layer == 0 ? (uint32_t*)&g_x2row[bid * 2] : (uint32_t*)(P.out + (size_t)sel * DM + bid * 8)) + (lane >> 1);
          asm volatile("" : "+f"(xn), "+f"(sg), "+l"(dst));
#pragma unroll 1
          while ((int)clock() - t_y < DELAY_Y) {}
          const uint4* src = &g_ypart[layer][((tid - 128) >> 1) * 256 + bid * 2 + (tid & 1)];
          uint4 v, w;
          uint32_t spins = 0;
#pragma unroll 1
          do { v = ld_relaxed4(src); w = ld_relaxed4(src + 64 * 256); } while (!__all_sync(0xffffffffu, valid4(v) && valid4(w)) && ++spins < SPIN_LIMIT);
          float a[4] = {__uint_as_float(v.x) + __uint_as_float(w.x), __uint_as_float(v.y) + __uint_as_float(w.y),
                        __uint_as_float(v.z) + __uint_as_float(w.z), __uint_as_float(v.w) + __uint_as_float(w.w)};
          const bool b1 = lane & 2, b2 = lane & 4;
          float c0 = (b1 ? a[1] : a[0]) + __shfl_xor_sync(0xffffffffu, b1 ? a[0] : a[1], 2);
          float c1 = (b1 ? a[3] : a[2]) + __shfl_xor_sync(0xffffffffu, b1 ? a[2] : a[3], 2);
          float y = (b2 ? c1 : c0) + __shfl_xor_sync(0xffffffffu, b2 ? c0 : c1, 4);
          y += __shfl_xor_sync(0xffffffffu, y, 8);
          y += __shfl_xor_sync(0xffffffffu, y, 16);
          float* red = (float*)(smem + OFF_PATCH);
          red[wi * 8 + (lane & 1) * 4 + ((lane >> 1) & 3)] = y;
          named_bar(2, 128);
          if (warp == 4) {
            PROF(21);
            y = (red[lane & 7] + red[8 + (lane & 7)]) + (red[16 + (lane & 7)] + red[24 + (lane & 7)]);
            const float res = x + rbf(xn + rbf(rbf(y) * sg));
            const uint32_t pr = nosent(pack_bf16(res, __shfl_down_sync(0xffffffffu, res, 1)));
            if (lane < 8 && (lane & 1) == 0) st_relaxed(dst, pr);
            PROF(22);
          }
        }
        if (pass == 2) {
          if (bid == 0 && tid == 128) g_epoch = tag;
          bulk_wait_all();
          __syncwarp();
          cluster_arrive(); cluster_wait();
          return;
        }
      }
      const unsigned layer = pass;
      if (__shfl_sync(0xffffffffu, fresh_tid() >> 5, 0) > 1 - (int)layer) {
        PHASE_IDS
        uint4* xrow = (uint4*)(smem + SL_F + 4 * SL_HD);
        if (wg == 1) {
          if (layer == 0) {
            xrow[tid - 128] = make_uint4(0x3F803F80u, 0x3F803F80u, 0x3F803F80u, 0x3F803F80u);
            if (warp == 5) { mbar_wait(bar(B_FULL + WS_AT), 0); load_ws(WS_PACE); }
          } else xrow[tid - 128] = poll4(&g_x2row[(tid - 128) * 2]);
          PROF(23);
        }
        named_bar(12, 192 + 32 * layer);
        if (warp == 1) {
          float mean = 0.f;
#pragma unroll 1
          for (int pass2 = 0; pass2 < 2; pass2++) {
            float acc = 0.f;
#pragma unroll 1
            for (int j = lane; j < 128; j += 32) {
              const uint4 v = xrow[j];
              const uint32_t w[4] = {v.x, v.y, v.z, v.w};
#pragma unroll
              for (int c = 0; c < 4; c++) {
                const float d0 = bf_lo(w[c]) - mean, d1 = bf_hi(w[c]) - mean;
                acc += pass2 ? d0 * d0 + d1 * d1 : d0 + d1;
              }
            }
            acc = warp_sum(acc) * (1.f / DM);
            if (pass2 == 0) mean = acc;
            else { s_misc[M_PMEAN] = __float_as_uint(rbf(mean)); s_misc[M_PINV] = __float_as_uint(ln_inv(acc)); }
          }
        } else {
          mbar_wait(bar(B_WS), layer);
          const uint8_t* wa = smem + SL_F + (g >> 1) * SL_HD + ((warp - 2) >> 1) * 4096 + (g & 1) * 2048;
          const uint32_t* xs = (const uint32_t*)xrow + rb * 64 + g * 8;
          const int ch = (warp & 1) * 4 + q;
          float d[8] = {0.f, 0.f, 0.f, 0.f, 0.f, 0.f, 0.f, 0.f};
#pragma unroll 1
          for (int j0 = 0; j0 < 16; j0 += 2) {
            const int j = j0 ^ ((g & 1) * 4);
            const uint4 w0 = *(const uint4*)(wa + j * 128 + (((ch ^ j) & 7) << 4)), w1 = *(const uint4*)(wa + j * 128 + 128 + (((ch ^ (j + 1)) & 7) << 4));
            const uint32_t xx = xs[j >> 1];
            fma8(d, w0, bf_lo(xx)); fma8(d, w1, bf_hi(xx));
          }
#pragma unroll
          for (int c = 0; c < 4; c++) d[c] = ((g & 4) ? d[c + 4] : d[c]) + __shfl_xor_sync(0xffffffffu, (g & 4) ? d[c] : d[c + 4], 16);
#pragma unroll
          for (int c = 0; c < 2; c++) d[c] = ((g & 2) ? d[c + 2] : d[c]) + __shfl_xor_sync(0xffffffffu, (g & 2) ? d[c] : d[c + 2], 8);
          d[0] = ((g & 1) ? d[1] : d[0]) + __shfl_xor_sync(0xffffffffu, (g & 1) ? d[0] : d[1], 4);
          st_relaxed(&g_vw[layer][rb][((warp - 2) >> 1) * DM + hp * 64 + ch * 8 + g], enc(d[0]));
        }
        named_bar(12, 192 + 32 * layer);
        PROF(24);
      }
      PHASE_IDS
      if (wg == 0) {
        if (warp == 0) {
          int s = 0, u = 0;
#pragma unroll 1
          for (int i = 6; i < 32; i++) {
            if (layer == 1) mbar_arrive_e(bar(B_EMPTY + s));
            mbar_wait(bar(B_EMPTY + s), (u + (s > 1 ? 0 : layer)) & 1);
            load_w(s, i);
            load_a(s, i, layer);
            if (++s == 6) { s = 0; u++; }
          }
        } else if (warp == 1) {
          if (layer == 0) {
            const uint32_t tag = ld_relaxed(&g_epoch) + 1;
            float shift = 0.f, sum = 0.f, sq = 0.f;
            const int r = hp * 16 + (lane >> 1);
#pragma unroll 1
            for (int i = 0; i < 32; i++) {
              mbar_wait(bar(B_FULL + i % 6), (i / 6) & 1);
              const uint8_t* base = smem + (i % 6) * QE + r * 64 + (lane & 1) * 32;
              uint4 v[2];
#pragma unroll
              for (int j = 0; j < 2; j++) v[j] = *(const uint4*)(base + ((j ^ ((r >> 1) & 1)) << 4));
              if (i == 0) shift = __shfl_sync(0xffffffffu, bf_lo(v[0].x), lane & ~1);
#pragma unroll
              for (int j = 0; j < 2; j++) {
                const uint32_t w[4] = {v[j].x, v[j].y, v[j].z, v[j].w};
#pragma unroll
                for (int c = 0; c < 4; c++) {
                  const float d0 = bf_lo(w[c]) - shift, d1 = bf_hi(w[c]) - shift;
                  sum += d0 + d1; sq = fmaf(d0, d0, fmaf(d1, d1, sq));
                }
              }
              fence_async_smem();
              __syncwarp();
              if (i < 26) mbar_arrive_e(bar(B_EMPTY + i % 6));
            }
            sum += __shfl_xor_sync(0xffffffffu, sum, 1); sq += __shfl_xor_sync(0xffffffffu, sq, 1);
            const float dm = sum * (1.f / DM), var = fmaxf(sq * (1.f / DM) - dm * dm, 0.f), mean = shift + dm;
            const float inv = ln_inv(var);
            if ((lane & 1) == 0) st_relaxed4(&g_rowab[0][rb * 256 + r], make_uint4(__float_as_uint(inv), __float_as_uint(rbf(mean) * inv), tag, 0));
          }
          if (rb == 0) {
            mbar_wait(bar(B_QDONE), layer);
#pragma unroll 1
            for (int j = lane; j < 512; j += 32) ((uint4*)(smem + 65536))[j] = make_uint4(0, 0, 0, 0);
            fence_async_smem();
            __syncwarp();
            if (lane < 3) mbar_arrive(bar(B_HALO + lane));
          }
        } else if (warp == 3) {
          fence_async_smem();
          load_gu(0, layer ? GU_PACE1 : GU_PACE);
          PROF(27);
        } else {
          const uint4 sent = make_uint4(SENT, SENT, SENT, SENT), zero = make_uint4(0, 0, 0, 0);
#pragma unroll 1
          for (int t = lane; t < 128; t += 32) {
            g_ypart[layer][bid * 256 + t] = sent; g_ypart[layer][bid * 256 + 128 + t] = sent;
            g_part[layer][nb * SEQ + mb * 128 + t] = zero;
            if (t < 16) g_cand[layer][mb * 128 + nb * 16 + t] = sent;
            else if (t < 18) { if (nb == 0) g_slot[layer][mb * 8 + t - 16] = zero; }
            else if (t < 20) { if (layer == 0) g_x2row[bid * 2 + t - 18] = sent; }
          }
        }
        __syncwarp();
        if (rank == 0) {
          if (warp == 0) {
            mbar_wait(bar(B_QDONE), layer);
#pragma unroll 1
            for (int j = 0; j < 3; j++) {
              const int o = j == 0 ? 16384 : (j == 1 ? 0 : 65536);
              mbar_wait(bar(B_KVREADY + (j >> 1)), layer);
              bulk_push(mapa(sbase + o, 1), sbase + 32768 + o, j == 2 ? 32768 : 16384, mapa(bar(B_HALO + j), 1));
            }
          } else if (warp < 3 && rb > 0) {
            mbar_wait(bar(B_QREADY), layer);
            if (warp == 2) spin_cycles(1000);
            import_halo(layer, warp - 1);
            if (warp == 1) PROF(5);
          }
        } else if (warp == 2) {
          mbar_expect_tx(bar(B_HALO), 16384); mbar_expect_tx(bar(B_HALO + 1), 16384); mbar_expect_tx(bar(B_HALO + 2), 32768);
        } else if (warp < 2 && rb < 7) {
          mbar_wait(bar(B_KVREADY + warp), layer);
          if (warp == 1) named_bar(13, 64);
          bulk_store(g_kv + (size_t)((rb >> 1) * 16 + hp) * 65536 + warp * 32768, sbase + 32768 + warp * 65536, 32768);
          bulk_commit();
          bulk_wait_all();
          if (warp == 0) asm volatile("bar.arrive 13, 64;" ::: "memory");
          set_flag(&g_kvflag[rb >> 1][hp][warp].v[layer], s_misc[M_TAG]);
          if (warp == 0) PROF(4);
        }
      } else {
        const int t = tid - 128, go = (t >> 5) * DM + hp * 64 + (t & 31) * 2;
        if (layer == 0 && t == 96) { s_misc[M_TAG] = ld_relaxed(&g_epoch) + 1; s_misc[M_SEL0] = 0xFFFFFFFFu; s_misc[M_PROG] = s_misc[M_PROG + 1] = 0; }
        if ((layer == 0 || (int)s_misc[M_SEL0] >> 8 == rb) && warp < 7) {
          spin_cycles(layer ? 300 : 1500);
          uint2 w[8];
          uint32_t spins = 0;
          bool ok;
#pragma unroll 1
          do {
            ok = true;
#pragma unroll
            for (int j = 0; j < 8; j++) w[j] = ld_relaxed2(&g_vw[layer][j][go]);
#pragma unroll
            for (int j = 0; j < 8; j++) ok = ok && w[j].x && w[j].y;
          } while (!__all_sync(0xffffffffu, ok) && ++spins < SPIN_LIMIT);
          float s0 = 0.f, s1 = 0.f;
#pragma unroll
          for (int j = 0; j < 8; j++) { s0 += dec(w[j].x); s1 += dec(w[j].y); }
          if (layer == 0) ((float2*)(smem + OFF_CS))[t] = make_float2(s0, s1);
          else {
            const float2 c = ((const float2*)(smem + OFF_CS))[t];
            const float a = __uint_as_float(s_misc[M_PINV]) * (warp == 4 ? SM_C : 1.f), b = __uint_as_float(s_misc[M_PMEAN]) * a;
            ((uint32_t*)(smem + OFF_PATCH))[t] = pack_bf16(s0 * a - c.x * b, s1 * a - c.y * b);
          }
          PROF(25);
        }
        __syncwarp();
        mbar_arrive_e(bar(B_CS));
      }
      __syncwarp();
      mbar_wait(bar(B_QREADY), layer);
      named_bar(1 + (fresh_tid() >> 7), 128);
      if (__shfl_sync(0xffffffffu, fresh_tid() >> 7, 0) == 0) {
        regs_inc<152>();
        uint32_t gu[112];
        {
          PHASE_IDS
          const uint32_t tag = s_misc[M_TAG];
          mbar_wait(bar(B_GU), layer);
#pragma unroll
          for (int j = 0; j < 28; j++) fetch_gu(gu + 4 * j, warp * 4 + (j & 3), j >> 2);
          fence_async_smem();
          named_bar(1, 128);
          if (warp == 0) {
            mbar_wait(bar(B_ADONE), layer);
#pragma unroll 1
            for (int k = 2; k < 16; k++) {
#pragma unroll 1
              for (uint32_t spins = 0; (int)s_misc[M_PROG + (k >> 3)] <= (k & 7) + 16 * (int)layer && spins < SPIN_LIMIT; spins++) {}
              if (k >= 4) mbar_wait(bar(B_WEMPTY + (k & 3)), ((k >> 2) - 1 + ((k & 2) ? layer : 0)) & 1);
              load_o(k); load_wo(k);
              STEPT(16 + k);
              if (k == RES_K) { mbar_wait(bar(B_OST + 1), layer); load_res(1, layer); }
            }
            if (layer == 1) {
              mbar_wait(bar(B_WEMPTY + 1), 1);
              if (FAKE & 2) mbar_arrive_e(bar(B_DN)); else mbar_expect_tx(bar(B_DN), 4 * FFN_PIECE);
              if (!(FAKE & 2)) tma_load3_h(sbase, &P.mapD, 0, bid * 28, 0, bar(B_DN), policy_evict_first());
              if (D_SPLIT == 0) tma_load3_h(sbase + 2 * FFN_PIECE, &P.mapD, 0, bid * 28, 8, bar(B_DN), policy_evict_first());
            }
            named_bar(6, 320);
            if (layer == 0) {
              mbar_wait(bar(B_QFREE), 0);
#pragma unroll 1
              for (int i = 0; i < 4; i++) load_w(i, i);
            } else if (D_SPLIT == 1 && !(FAKE & 2)) tma_load3_h(sbase + 2 * FFN_PIECE, &P.mapD, 0, bid * 28, 8, bar(B_DN), policy_evict_first());
          } else if (warp < 3) {
            const int h = warp - 1;
#pragma unroll 1
            for (int qb = 3; qb >= 0; qb--) {
              mbar_wait(bar(B_UNIT + h * 4 + 3 - qb), layer);
              bulk_store(g_o + (size_t)((((rb * 2 + (qb >> 1)) * 2 + h) * 16 + hp) * 2 + (qb & 1)) * 4096, sbase + AT_ST + (h * 4 + qb) * 4096, 4096);
            }
            bulk_commit();
            if (h == 0 && lane < 2) mbar_arrive_cluster(bar(B_OST), lane);
            bulk_wait_all();
            if (h == 1) mbar_arrive_e(bar(B_OST + 1));
            set_flag(&g_oflag[rb][h][hp].v[layer], tag);
            PROF(28 + 3 * h);
            if (h == 0) { load_res(0, layer); mbar_wait(bar(B_OST), layer); load_wo(0); load_wo(1); }
            int n = 0, first = h;
#pragma unroll 1
            for (uint32_t spins = 0; n < 8 && spins < SPIN_LIMIT; spins++) {
              n = (__ffs(__ballot_sync(0xffffffffu, ld_relaxed(&g_oflag[rb][h][lane & 15].v[layer]) != tag || lane == 16)) - 1) >> 1;
              asm volatile("fence.acquire.gpu;" ::: "memory");
              fence_async_global();
              if (!first && n >= 2) {
                first = 1;
                load_o(0); load_o(1);
                PROF(15);
              }
              s_misc[M_PROG + h] = n + 16 * layer;
            }
            if (h) PROF(26);
          } else {
            mbar_expect_tx(bar(B_HX), 2240);
            mbar_wait(bar(B_HALO + 2), layer);
            if (rb == 0) spin_cycles(2000);
            PROF(6);
            load_gu(1, GUB_PACE);
          }
        }
        PHASE_IDS
        uint4 xa = {}, xb = {};
        named_bar(7, 512);
        if (g == 0) { xa = ((const uint4*)(smem + T_XS))[warp * 8 + q]; xb = ((const uint4*)(smem + T_XS))[warp * 8 + 4 + q]; }
        __syncwarp();
        float d[7][4] = {};
#pragma unroll
        for (int j = 0; j < 28; j++) {
          const int ks = j / 7, ct = j % 7;
          const uint32_t* a = gu + ct * 16 + ks * 4;
          mma_16816(d[ct], a[0], a[1], a[2], a[3], ks == 0 ? xa.x : ks == 1 ? xa.z : ks == 2 ? xb.x : xb.z, ks == 0 ? xa.y : ks == 1 ? xa.w : ks == 2 ? xb.y : xb.w);
        }
#pragma unroll
        for (int ct = 0; ct < 7; ct++) send_gu(d[ct][0], d[ct][2], ct, warp);
        __syncwarp();
        if (warp == 2) PROF(18);
        regs_dec<32>();
        pass_v = pass + 1;
        continue;
      }
      break;
      }
      regs_inc<120>();
    }
    const unsigned layer = pass;
    {
      PHASE_IDS
      mbar_wait(bar(B_QREADY), layer);
      if (warp != 9) STEPT(7);
      auto kdesc = [&](int h, int b) { return dlo(SOFF, 16) + (rb == 0 && b < 4 ? 4096 : h * 4096 + b * 512); };
      auto vdesc = [&](int h, int b) { return rb == 0 && b < 4 ? dlo(SOFF + 65536, 4096) : dlo(SOFF + 4096, OFF_ONES - 4096) + (h * 8 + b) * 8 * VSTEP; };
      const int units = wg == 3 ? 0x8630 : (wg == 2 ? ULIST2 : ULIST1);
      auto need = [&](int h, int b) { if (b == 3 || b == 1) mbar_wait(bar(B_HALO + (h ? 2 : b == 1)), layer); };
      auto load_q = [&](uint32_t* qf, int u) {
        *(uint4*)&qf[0] = *(const uint4*)(smem + AT_ST + ((u ^ 3) * 4 + wi) * 1024 + lane * 16);
        *(uint4*)&qf[4] = *(const uint4*)(smem + AT_ST + ((u ^ 3) * 4 + wi) * 1024 + 512 + lane * 16);
      };
      auto store_o = [&](const float* o, int u) {
        const float i0 = rcp(o[16]), i1 = rcp(o[18]);
        const int v = u ^ 3;
        if (u >= 4 && lane < 2) mbar_arrive_cluster(bar(B_ADONE), lane);
#pragma unroll
        for (int j = 0; j < 2; j++)
          stsm_x4(sbase + AT_ST + v * 4096 + srow * 64 + (((2 * j + (mi >> 1)) ^ ((srow >> 1) & 3)) << 4),
                  pack_bf16(o[8 * j] * i0, o[8 * j + 1] * i0), pack_bf16(o[8 * j + 2] * i1, o[8 * j + 3] * i1),
                  pack_bf16(o[8 * j + 4] * i0, o[8 * j + 5] * i0), pack_bf16(o[8 * j + 6] * i1, o[8 * j + 7] * i1));
        fence_async_smem();
        __syncwarp();
        mbar_arrive_e(bar(B_UNIT + u));
      };
      int redo = 0;
      {
        const int dl = g - 2 * q;
        const uint32_t mt = shl_clamp(0xFFFFFFFFu, max(16 * dl + 16, 0));
        uint32_t qf[8];
        float s[32];
        load_q(qf, units & 7);
        wg_fence();
        qk64(s, qf, kdesc((units >> 2) & 1, 6 - (units & 3)));
        wg_commit();
        wg_wait<0>();
        fence_regs<32>(s);
#pragma unroll 1
        for (int ul = units; ul != 8; ul >>= 4) {
          const int u = ul & 7, h = u >> 2, qb = 3 - (u & 3);
          float o[20];
          uint32_t p1[16], p2[16], p3[16], p4[16], p5[16];
          if (warp != 9) STEPT(8 + nu * 8);
          exp_pack<8>(s, p1);
          fence_regs_u<16>(p1);
          need(h, qb + 2);
          {
            float s2[32];
            const uint32_t vd = vdesc(h, qb + 3);
            wg_fence();
            qk64(s2, qf, kdesc(h, qb + 2));
            wg_commit();
            wg_rs40t_z<H64>(o, p1[0], p1[1], p1[2], p1[3], vd);
            wg_rs40t<H64>(o, p1[4], p1[5], p1[6], p1[7], vd + VSTEP, 1);
            pv32(o, p1 + 8, vd + 2 * VSTEP);
            wg_commit();
            wg_wait<1>();
            fence_regs<32>(s2);
            if (warp != 9) STEPT(9 + nu * 8);
            exp_pack<8>(s2, p2);
            fence_regs_u<16>(p2);
            wg_wait<0>();
            fence_regs<20>(o);
          }
          need(h, qb + 1);
          {
            float s3[32];
            wg_fence();
            qk64(s3, qf, kdesc(h, qb + 1));
            wg_commit();
            pv32(o, p2, vdesc(h, qb + 2)); pv32(o, p2 + 8, vdesc(h, qb + 2) + 2 * VSTEP);
            wg_commit();
            wg_wait<1>();
            fence_regs<32>(s3);
            if (warp != 9) STEPT(10 + nu * 8);
            exp_pack<8>(s3, p3);
            fence_regs_u<16>(p3);
            wg_wait<0>();
            fence_regs<20>(o);
          }
          need(h, qb);
          const uint32_t kd = kdesc(h, qb + 4), kt = kdesc(h, qb), vd = vdesc(h, qb + 4), vt = vdesc(h, qb);
          {
            float sd[16], st[16];
            wg_fence();
            qk32x2(sd, st, qf, kd, kt);
            wg_commit();
            pv32(o, p3, vdesc(h, qb + 1)); pv32(o, p3 + 8, vdesc(h, qb + 1) + 2 * VSTEP);
            wg_commit();
            wg_wait<1>();
            fence_regs<16>(sd); fence_regs<16>(st);
            if (warp != 9) STEPT(11 + nu * 8);
            edge32(sd, st, p4, p4 + 8, wi, dl, mt);
            fence_regs_u<16>(p4);
            wg_wait<0>();
            fence_regs<20>(o);
          }
          const int un = (ul >> 4) == 8 ? 4 : (ul >> 4) & 7;
          {
            float sd[16], st[16];
            wg_fence();
            qk32x2(sd, st, qf, kd + 128, kt + 128);
            wg_commit();
            pv32(o, p4, vd); pv32(o, p4 + 8, vt);
            wg_commit();
            wg_wait<1>();
            fence_regs<16>(sd); fence_regs<16>(st);
            load_q(qf, un);
            edge32(sd, st, p5, p5 + 8, wi - 2, dl, mt);
            fence_regs_u<16>(p5);
          }
          need(un >> 2, 6 - (un & 3));
          wg_fence();
          pv32(o, p5, vd + 2 * VSTEP); pv32(o, p5 + 8, vt + 2 * VSTEP);
          wg_commit();
          qk64(s, qf, kdesc(un >> 2, 6 - (un & 3)));
          wg_commit();
          wg_wait<1>();
          fence_regs<20>(o);
          if (warp != 9) STEPT(12 + nu * 8);
          const bool unsafe = !(o[16] >= LSUM_MIN && o[16] <= LSUM_MAX && o[18] >= LSUM_MIN && o[18] <= LSUM_MAX);
          if (__any_sync(0xffffffffu, unsafe)) redo |= 1 << u;
          else store_o(o, u);
          wg_wait<0>();
          fence_regs<32>(s);
        }
      }
      if (warp != 9) STEPT(31);
      if (bar_red_or(1 + wg, 128, redo)) {
#pragma unroll 1
        for (int ul = units; ul != 8; ul >>= 4) {
          const int u = ul & 7;
          if (!bar_red_or(1 + wg, 128, redo >> u & 1)) continue;
          const int h = u >> 2, qb = 3 - (u & 3);
          uint32_t qf[8], p[16];
          float o[20], m0 = -INFINITY, m1 = -INFINITY;
          load_q(qf, u);
#pragma unroll
          for (int i = 0; i < 20; i++) o[i] = 0.f;
#pragma unroll 1
          for (int j = 0; j <= (rb == 0 ? qb : 4); j++) {
            const int b = qb + 4 - j;
            float s[32];
            wg_fence();
            qk64(s, qf, kdesc(h, b));
            wg_commit();
            wg_wait<0>();
            fence_regs<32>(s);
            float mx0 = m0, mx1 = m1;
#pragma unroll
            for (int c = 0; c < 8; c++) {
#pragma unroll
              for (int i = 0; i < 4; i++) {
                const int diff = j * 64 + (16 * wi + g + (i >> 1) * 8) - (8 * c + 2 * q + (i & 1));
                if (diff < 0 || diff > 255) s[4 * c + i] = -INFINITY;
              }
              mx0 = fmaxf(mx0, fmaxf(s[4 * c], s[4 * c + 1]));
              mx1 = fmaxf(mx1, fmaxf(s[4 * c + 2], s[4 * c + 3]));
            }
            mx0 = fmaxf(mx0, __shfl_xor_sync(0xffffffffu, mx0, 1)); mx1 = fmaxf(mx1, __shfl_xor_sync(0xffffffffu, mx1, 1));
            mx0 = fmaxf(mx0, __shfl_xor_sync(0xffffffffu, mx0, 2)); mx1 = fmaxf(mx1, __shfl_xor_sync(0xffffffffu, mx1, 2));
            const float r0 = j == 0 ? 0.f : ex2(m0 - mx0), r1 = j == 0 ? 0.f : ex2(m1 - mx1);
            m0 = mx0; m1 = mx1;
#pragma unroll
            for (int i = 0; i < 5; i++) { o[4 * i] *= r0; o[4 * i + 1] *= r0; o[4 * i + 2] *= r1; o[4 * i + 3] *= r1; }
#pragma unroll
            for (int c = 0; c < 8; c++) { s[4 * c] -= m0; s[4 * c + 1] -= m0; s[4 * c + 2] -= m1; s[4 * c + 3] -= m1; }
            exp_pack<8>(s, p);
            fence_regs<20>(o); fence_regs_u<16>(p);
            wg_fence();
            pv32(o, p, vdesc(h, b)); pv32(o, p + 8, vdesc(h, b) + 2 * VSTEP);
            wg_commit();
            wg_wait<0>();
            fence_regs<20>(o);
          }
          named_bar(1 + wg, 128);
          if (redo >> u & 1) store_o(o, u);
          __syncwarp();
        }
      }
      if (wi == 0) PROF(6 + wg);
    }
    pass_v = pass + 1;
  }
}

}

typedef CUresult (*EncodeFn)(CUtensorMap*, CUtensorMapDataType, cuuint32_t, void*, const cuuint64_t*, const cuuint64_t*,
                             const cuuint32_t*, const cuuint32_t*, CUtensorMapInterleave, CUtensorMapSwizzle,
                             CUtensorMapL2promotion, CUtensorMapFloatOOBfill);
static EncodeFn g_encode = nullptr;
struct Dim { uint64_t size, stride; uint32_t box; };
template <int N> static CUtensorMap make_map(const void* ptr, const Dim (&d)[N], int swizzle) {
  CUtensorMap m;
  cuuint64_t dims[N], strides[N];
  cuuint32_t box[N], es[N];
  for (int i = 0; i < N; i++) { dims[i] = d[i].size; strides[i] = d[i].stride; box[i] = d[i].box; es[i] = 1; }
  g_encode(&m, CU_TENSOR_MAP_DATA_TYPE_BFLOAT16, N, const_cast<void*>(ptr), dims, strides + 1, box, es, CU_TENSOR_MAP_INTERLEAVE_NONE,
           swizzle == 128 ? CU_TENSOR_MAP_SWIZZLE_128B : (swizzle == 64 ? CU_TENSOR_MAP_SWIZZLE_64B : CU_TENSOR_MAP_SWIZZLE_NONE),
           swizzle ? CU_TENSOR_MAP_L2_PROMOTION_L2_256B : CU_TENSOR_MAP_L2_PROMOTION_L2_128B, CU_TENSOR_MAP_FLOAT_OOB_FILL_NONE);
  return m;
}
static CUtensorMap map2(const void* ptr, uint64_t inner, uint64_t outer, uint32_t bi, uint32_t bo, int swizzle) {
  const Dim d[2] = {{inner, 0, bi}, {outer, inner * 2, bo}};
  return make_map(ptr, d, swizzle);
}
template <class T> static void* sym_addr(T& sym) { void* p = nullptr; cudaGetSymbolAddress(&p, sym); return p; }

static Params h_p;
static const void* h_key[9];

static cudaLaunchConfig_t launch_cfg(int grid, cudaLaunchAttribute* at) {
  cudaLaunchConfig_t cfg = {};
  cfg.gridDim = dim3(grid); cfg.blockDim = dim3(512); cfg.dynamicSmemBytes = SMEM_BYTES; cfg.stream = cudaStreamPerThread;
  at[0].id = cudaLaunchAttributeClusterDimension;
  at[0].val.clusterDim.x = 2; at[0].val.clusterDim.y = 1; at[0].val.clusterDim.z = 1;
  cfg.attrs = at; cfg.numAttrs = 1;
  return cfg;
}

extern "C" void kernel_launch(void* const* d_in, const int* in_sizes, int n_in, void* d_out, int out_size) {
  const bf16* x = (const bf16*)d_in[0];
  const bf16* wqkv = (const bf16*)d_in[1];
  const bf16* wo = (const bf16*)d_in[2];
  cudaLaunchAttribute at[1];
  bool fresh = g_encode != nullptr && h_key[8] == d_out;
  for (int i = 0; i < 8; i++) fresh = fresh && h_key[i] == d_in[i];
  if (!fresh) {
    if (!g_encode) {
      void* fn = nullptr;
      cudaDriverEntryPointQueryResult st;
      cudaGetDriverEntryPoint("cuTensorMapEncodeTiled", &fn, cudaEnableDefault, &st);
      g_encode = (EncodeFn)fn;
      cudaFuncSetAttribute(mega_kernel, cudaFuncAttributeMaxDynamicSharedMemorySize, SMEM_BYTES);
    }
    bf16* x1 = (bf16*)sym_addr(g_x1);
    Params& p = h_p;
    p.x = x; p.wqkv = wqkv; p.wo = wo; p.w_r = (const bf16*)d_in[4]; p.w_g = (const bf16*)d_in[5]; p.w_u = (const bf16*)d_in[6]; p.w_d = (const bf16*)d_in[7];
    p.out = (bf16*)d_out;
    p.mapA[0] = map2(x, DM, SEQ, 32, 256, 64);
    p.mapA[1] = map2(x1, DM, SEQ, 32, 256, 64);
    { const Dim d[3] = {{DM, 0, 64}, {DM, 3 * DM * 2, 16}, {3, DM * 2, 3}}; p.mapW = make_map(wqkv, d, 128); }
    { const Dim d[3] = {{DM, 0, 64}, {DM, 3 * DM * 2, 32}, {3, DM * 2, 3}}; p.mapWs = make_map(wqkv, d, 128); }
    { const Dim d[3] = {{DM, 0, 64}, {64, DM * 2, 32}, {16, 64 * DM * 2, 2}}; p.mapWo = make_map(wo, d, 128); }
    p.mapRes[0] = map2(x, DM, SEQ, 64, 64, 128);
    p.mapRes[1] = p.mapXst[0] = map2(x1, DM, SEQ, 64, 64, 128);
    p.mapXst[1] = map2(d_out, DM, SEQ, 64, 64, 128);
    p.mapG = map2(p.w_g, FF, DM, 56, 128, 0);
    p.mapU = map2(p.w_u, FF, DM, 56, 128, 0);
    { const Dim d[3] = {{64, 0, 64}, {FF, DM * 2, 28}, {DM / 64, 128, 8}}; p.mapD = make_map(p.w_d, d, 128); }
    for (int i = 0; i < 8; i++) h_key[i] = d_in[i];
    h_key[8] = d_out;
  }
  void* a0[] = {&h_p};
  cudaLaunchConfig_t cfg = launch_cfg(128, at);
  cudaLaunchKernelExC(&cfg, (const void*)mega_kernel, a0);
}
```

```cpp
#include <cuda_runtime.h>
#include <cuda_bf16.h>
#include <cuda.h>
#include <stdint.h>

namespace {

constexpr int SEQ = 2048, DM = 1024, FF = 3584;
constexpr float LN_EPS = 1e-5f;
typedef __nv_bfloat16 bf16;

__device__ __align__(1024) uint8_t g_kv[3 * 16 * 65536];
__device__ __align__(1024) uint8_t g_o[SEQ * DM * 2];
__device__ __align__(1024) bf16 g_x1[SEQ * DM];
__device__ unsigned g_epoch;
struct __align__(128) Flag { unsigned v[32]; };
__device__ Flag g_kvflag[3][16][2], g_oflag[8][2][16], g_xflag[16][8];
__device__ uint4 g_rowab[2][SEQ];
__device__ __align__(16) uint32_t g_vw[2][8][3 * DM];
constexpr uint32_t SENT = 0xFFFFFFFFu;
__device__ uint4 g_part[2][8 * SEQ];
__device__ uint4 g_slot[2][16 * 8];
__device__ uint4 g_cand[2][16 * 128];
__device__ uint4 g_ypart[2][128 * DM / 4];
__device__ uint4 g_x2row[128 * 2];
__device__ float2 g_rowln[8][SEQ];
__device__ int g_sel[2];

#define PROFL(l, e)
#define PROF(e) PROFL(layer, e)
#define STEPT(i)
#define SPIN_LIMIT 4000000u
__device__ __forceinline__ uint32_t smem_u32(const void* p) { return (uint32_t)__cvta_generic_to_shared(p); }
__device__ __forceinline__ void mbar_init(uint32_t bar, uint32_t cnt) {
  asm volatile("mbarrier.init.shared::cta.b64 [%0], %1;" ::"r"(bar), "r"(cnt) : "memory");
}
#define ELECT "{\n.reg .pred e;\nelect.sync _|e, 0xffffffff;\n@e "
__device__ __forceinline__ void mbar_expect_tx(uint32_t bar, uint32_t bytes) {
  asm volatile(ELECT "mbarrier.arrive.expect_tx.shared::cta.b64 _, [%0], %1;\n}" ::"r"(bar), "r"(bytes) : "memory");
}
__device__ __forceinline__ void mbar_arrive(uint32_t bar) {
  asm volatile("mbarrier.arrive.shared::cta.b64 _, [%0];" ::"r"(bar) : "memory");
}
__device__ __forceinline__ void mbar_arrive_e(uint32_t bar) {
  asm volatile(ELECT "mbarrier.arrive.shared::cta.b64 _, [%0];\n}" ::"r"(bar) : "memory");
}
__device__ __forceinline__ uint32_t mapa(uint32_t addr, uint32_t cta) {
  uint32_t r; asm("mapa.shared::cluster.u32 %0, %1, %2;" : "=r"(r) : "r"(addr), "r"(cta)); return r;
}
__device__ __forceinline__ void mbar_arrive_cluster(uint32_t bar, uint32_t cta) {
  asm volatile("mbarrier.arrive.shared::cluster.b64 _, [%0];" ::"r"(mapa(bar, cta)) : "memory");
}
#define MBAR_WAIT_ASM(QUAL)                                                                                                \
  asm volatile("{\n.reg .pred p;\n.reg .u32 n;\nmov.u32 n, 0;\nWAIT_LOOP:\n.pragma \"nounroll\";\n"                         \
               "mbarrier.try_wait.parity" QUAL ".shared::cta.b64 p, [%0], %1;\n@p bra WAIT_DONE;\n"                        \
               "add.u32 n, n, 1;\nsetp.lt.u32 p, n, %2;\n@p bra WAIT_LOOP;\nWAIT_DONE:\n}" ::"r"(bar), "r"(parity), "n"(SPIN_LIMIT) : "memory")
__device__ __forceinline__ void mbar_wait(uint32_t bar, uint32_t parity) { MBAR_WAIT_ASM(""); }
__device__ __forceinline__ void mbar_wait_cluster(uint32_t bar, uint32_t parity) { MBAR_WAIT_ASM(".acquire.cluster"); }
__device__ __forceinline__ bool mbar_wait_brief(uint32_t bar, uint32_t parity) {
  uint32_t ok;
  asm volatile("{\n.reg .pred p;\nmbarrier.try_wait.parity.shared::cta.b64 p, [%1], %2, 1000;\nselp.u32 %0, 1, 0, p;\n}"
               : "=r"(ok) : "r"(bar), "r"(parity) : "memory");
  return __all_sync(0xffffffffu, ok);
}
__device__ __forceinline__ void st_async2(uint32_t addr, float a, float b, uint32_t bar) {
  asm volatile("st.async.weak.shared::cluster.mbarrier::complete_tx::bytes.v2.f32 [%0], {%1, %2}, [%3];"
               ::"r"(addr), "f"(a), "f"(b), "r"(bar) : "memory");
}
__device__ __forceinline__ uint64_t policy_evict_first() {
  uint64_t p; asm volatile("createpolicy.fractional.L2::evict_first.b64 %0, 1.0;" : "=l"(p)); return p;
}
__device__ __forceinline__ void tma_load2(uint32_t dst, const CUtensorMap* m, int c0, int c1, uint32_t bar) {
  asm volatile(ELECT "cp.async.bulk.tensor.2d.shared::cluster.global.mbarrier::complete_tx::bytes [%0], [%1, {%3, %4}], [%2];\n}"
               ::"r"(dst), "l"(m), "r"(bar), "r"(c0), "r"(c1) : "memory");
}
__device__ __forceinline__ void tma_load2_h(uint32_t dst, const CUtensorMap* m, int c0, int c1, uint32_t bar, uint64_t pol) {
  asm volatile(ELECT "cp.async.bulk.tensor.2d.shared::cluster.global.mbarrier::complete_tx::bytes.L2::cache_hint [%0], [%1, {%3, %4}], [%2], %5;\n}"
               ::"r"(dst), "l"(m), "r"(bar), "r"(c0), "r"(c1), "l"(pol) : "memory");
}
__device__ __forceinline__ void tma_load3(uint32_t dst, const CUtensorMap* m, int c0, int c1, int c2, uint32_t bar) {
  asm volatile(ELECT "cp.async.bulk.tensor.3d.shared::cluster.global.mbarrier::complete_tx::bytes [%0], [%1, {%3, %4, %5}], [%2];\n}"
               ::"r"(dst), "l"(m), "r"(bar), "r"(c0), "r"(c1), "r"(c2) : "memory");
}
__device__ __forceinline__ void tma_load3_h(uint32_t dst, const CUtensorMap* m, int c0, int c1, int c2, uint32_t bar, uint64_t pol) {
  asm volatile(ELECT "cp.async.bulk.tensor.3d.shared::cluster.global.mbarrier::complete_tx::bytes.L2::cache_hint [%0], [%1, {%3, %4, %5}], [%2], %6;\n}"
               ::"r"(dst), "l"(m), "r"(bar), "r"(c0), "r"(c1), "r"(c2), "l"(pol) : "memory");
}
__device__ __forceinline__ void tma_load3_mc(uint32_t dst, const CUtensorMap* m, int c0, int c1, int c2, uint32_t bar) {
  asm volatile(ELECT "cp.async.bulk.tensor.3d.shared::cluster.global.mbarrier::complete_tx::bytes.multicast::cluster [%0], [%1, {%3, %4, %5}], [%2], %6;\n}"
               ::"r"(dst), "l"(m), "r"(bar), "r"(c0), "r"(c1), "r"(c2), "h"((uint16_t)3) : "memory");
}
__device__ __forceinline__ void bulk_push(uint32_t dst, uint32_t src, uint32_t bytes, uint32_t bar) {
  asm volatile(ELECT "cp.async.bulk.shared::cluster.shared::cta.mbarrier::complete_tx::bytes [%0], [%1], %2, [%3];\n}"
               ::"r"(dst), "r"(src), "r"(bytes), "r"(bar) : "memory");
}
template <int N> __device__ __forceinline__ void regs_inc() { asm volatile("setmaxnreg.inc.sync.aligned.u32 %0;" ::"n"(N)); }
template <int N> __device__ __forceinline__ void regs_dec() { asm volatile("setmaxnreg.dec.sync.aligned.u32 %0;" ::"n"(N)); }
__device__ __forceinline__ void tma_prefetch2(const CUtensorMap* m, int c0, int c1) {
  asm volatile(ELECT "cp.async.bulk.prefetch.tensor.2d.L2.global [%0, {%1, %2}];\n}" ::"l"(m), "r"(c0), "r"(c1) : "memory");
}
__device__ __forceinline__ void bulk_prefetch(const void* p, uint32_t bytes) {
  asm volatile(ELECT "cp.async.bulk.prefetch.L2.global [%0], %1;\n}" ::"l"(p), "r"(bytes) : "memory");
}
__device__ __forceinline__ void tma_store(const CUtensorMap* m, uint32_t src, int c0, int c1) {
  asm volatile(ELECT "cp.async.bulk.tensor.2d.global.shared::cta.bulk_group [%0, {%2, %3}], [%1];\n}"
               ::"l"(m), "r"(src), "r"(c0), "r"(c1) : "memory");
}
__device__ __forceinline__ void bulk_load(uint32_t dst, const void* src, uint32_t bytes, uint32_t bar) {
  asm volatile(ELECT "cp.async.bulk.shared::cluster.global.mbarrier::complete_tx::bytes [%0], [%1], %2, [%3];\n}"
               ::"r"(dst), "l"(src), "r"(bytes), "r"(bar) : "memory");
}
__device__ __forceinline__ void bulk_load_h(uint32_t dst, const void* src, uint32_t bytes, uint32_t bar, uint64_t pol) {
  asm volatile(ELECT "cp.async.bulk.shared::cluster.global.mbarrier::complete_tx::bytes.L2::cache_hint [%0], [%1], %2, [%3], %4;\n}"
               ::"r"(dst), "l"(src), "r"(bytes), "r"(bar), "l"(pol) : "memory");
}
__device__ __forceinline__ void bulk_store(void* dst, uint32_t src, uint32_t bytes) {
  asm volatile(ELECT "cp.async.bulk.global.shared::cta.bulk_group [%0], [%1], %2;\n}" ::"l"(dst), "r"(src), "r"(bytes) : "memory");
}
__device__ __forceinline__ void bulk_commit() { asm volatile("cp.async.bulk.commit_group;" ::: "memory"); }
__device__ __forceinline__ void bulk_wait_all() { asm volatile("cp.async.bulk.wait_group 0;" ::: "memory"); }
__device__ __forceinline__ void fence_async_smem() { asm volatile("fence.proxy.async.shared::cta;" ::: "memory"); }
__device__ __forceinline__ void fence_async_global() { asm volatile("fence.proxy.async.global;" ::: "memory"); }
__device__ __forceinline__ void fence_release() { asm volatile("fence.release.gpu;" ::: "memory"); }
__device__ __forceinline__ void l2_prefetch_line(const void* p) { asm volatile("prefetch.global.L2 [%0];" ::"l"(p) : "memory"); }
__device__ __forceinline__ void prefetch_tmap(const CUtensorMap* m) { asm volatile("prefetch.tensormap [%0];" ::"l"(m) : "memory"); }
__device__ __forceinline__ void named_bar(int id, int n) { asm volatile("bar.sync %0, %1;" ::"r"(id), "r"(n) : "memory"); }
__device__ __forceinline__ bool bar_red_or(int id, int n, bool v) {
  uint32_t r;
  asm volatile("{\n.reg .pred p, q;\nsetp.ne.u32 q, %3, 0;\nbarrier.cta.red.or.pred p, %1, %2, q;\nselp.u32 %0, 1, 0, p;\n}"
               : "=r"(r) : "r"(id), "r"(n), "r"((uint32_t)v) : "memory");
  return r != 0;
}
__device__ __forceinline__ void cluster_arrive() { asm volatile("barrier.cluster.arrive.relaxed.aligned;" ::: "memory"); }
__device__ __forceinline__ void cluster_wait() { asm volatile("barrier.cluster.wait.aligned;" ::: "memory"); }
__device__ __forceinline__ uint32_t cluster_rank() { uint32_t r; asm volatile("mov.u32 %0, %%cluster_ctarank;" : "=r"(r)); return r; }
__device__ __forceinline__ unsigned ld_relaxed(const unsigned* p) {
  unsigned v; asm volatile("ld.relaxed.gpu.global.u32 %0, [%1];" : "=r"(v) : "l"(p) : "memory"); return v;
}
__device__ __forceinline__ uint4 ld_relaxed4(const uint4* p) {
  uint4 v; asm volatile("ld.relaxed.gpu.global.v4.u32 {%0, %1, %2, %3}, [%4];" : "=r"(v.x), "=r"(v.y), "=r"(v.z), "=r"(v.w) : "l"(p) : "memory"); return v;
}
__device__ __forceinline__ void st_relaxed(unsigned* p, unsigned v) {
  asm volatile("st.relaxed.gpu.global.u32 [%0], %1;" ::"l"(p), "r"(v) : "memory");
}
__device__ __forceinline__ uint2 ld_relaxed2(const void* p) {
  uint2 v; asm volatile("ld.relaxed.gpu.global.v2.u32 {%0, %1}, [%2];" : "=r"(v.x), "=r"(v.y) : "l"(p) : "memory"); return v;
}
__device__ __forceinline__ void st_relaxed4(uint4* p, uint4 v) {
  asm volatile("st.relaxed.gpu.global.v4.u32 [%0], {%1, %2, %3, %4};" ::"l"(p), "r"(v.x), "r"(v.y), "r"(v.z), "r"(v.w) : "memory");
}
__device__ __forceinline__ bool valid4(uint4 v) { return v.x != SENT && v.y != SENT && v.z != SENT && v.w != SENT; }
__device__ __forceinline__ uint4 poll4(const uint4* p) {
  uint4 v;
  uint32_t spins = 0;
#pragma unroll 1
  do { v = ld_relaxed4(p); } while (!valid4(v) && ++spins < SPIN_LIMIT);
  return v;
}
__device__ __forceinline__ void set_flag(unsigned* p, unsigned tag) {
  asm volatile(ELECT "st.release.gpu.global.u32 [%0], %1;\n}" ::"l"(p), "r"(tag) : "memory");
}
__device__ __forceinline__ void poll_flag(const unsigned* p, unsigned tag) {
#pragma unroll 1
  for (uint32_t spins = 0; !__all_sync(0xffffffffu, ld_relaxed(p) == tag) && spins < SPIN_LIMIT; spins++) {}
  asm volatile("fence.acquire.gpu;" ::: "memory");
}
__device__ __forceinline__ uint32_t enc(float x) { return __float_as_uint(x + 0.0f) ^ 0x80000000u; }
__device__ __forceinline__ float dec(uint32_t u) { return __uint_as_float(u ^ 0x80000000u); }
__device__ __forceinline__ uint32_t f2u(float x) { uint32_t u = __float_as_uint(x); return u == SENT ? 0x7FFFFFFFu : u; }
__device__ __forceinline__ uint32_t nosent(uint32_t u) { return u == SENT ? 0x7FFF7FFFu : u; }
__device__ __forceinline__ uint32_t hadd_bf2(uint32_t a, uint32_t b) {
  uint32_t r; asm("add.rn.bf16x2 %0, %1, %2;" : "=r"(r) : "r"(a), "r"(b)); return r;
}
__device__ __forceinline__ uint32_t hsub_bf2(uint32_t a, uint32_t b) {
  uint32_t r; asm("sub.rn.bf16x2 %0, %1, %2;" : "=r"(r) : "r"(a), "r"(b)); return r;
}
__device__ __forceinline__ void wg_fence() { asm volatile("wgmma.fence.sync.aligned;" ::: "memory"); }
__device__ __forceinline__ void wg_commit() { asm volatile("wgmma.commit_group.sync.aligned;" ::: "memory"); }
template <int N> __device__ __forceinline__ void wg_wait() { asm volatile("wgmma.wait_group.sync.aligned %0;" ::"n"(N) : "memory"); }
template <int R> __device__ __forceinline__ void fence_regs(float* d) {
#pragma unroll
  for (int i = 0; i < R; i++) asm volatile("" : "+f"(d[i])::"memory");
}
template <int R> __device__ __forceinline__ void fence_regs_u(uint32_t* d) {
#pragma unroll
  for (int i = 0; i < R; i++) asm volatile("" : "+r"(d[i])::"memory");
}
__host__ __device__ constexpr uint32_t dlo(uint32_t addr, uint32_t lbo) { return ((addr & 0x3FFFF) >> 4) | ((lbo >> 4) << 16); }
constexpr uint32_t H128 = 0x40000040u, H64 = 0x80000020u;
__device__ __forceinline__ void stsm_x4(uint32_t addr, uint32_t r0, uint32_t r1, uint32_t r2, uint32_t r3) {
  asm volatile("stmatrix.sync.aligned.m8n8.x4.shared.b16 [%0], {%1, %2, %3, %4};"
               ::"r"(addr), "r"(r0), "r"(r1), "r"(r2), "r"(r3) : "memory");
}
__device__ __forceinline__ void ldsm_x4(uint32_t addr, uint32_t& r0, uint32_t& r1, uint32_t& r2, uint32_t& r3) {
  asm volatile("ldmatrix.sync.aligned.m8n8.x4.shared.b16 {%0, %1, %2, %3}, [%4];"
               : "=r"(r0), "=r"(r1), "=r"(r2), "=r"(r3) : "r"(addr) : "memory");
}
__device__ __forceinline__ void ldsm_x4_t(uint32_t addr, uint32_t& r0, uint32_t& r1, uint32_t& r2, uint32_t& r3) {
  asm volatile("ldmatrix.sync.aligned.m8n8.x4.trans.shared.b16 {%0, %1, %2, %3}, [%4];"
               : "=r"(r0), "=r"(r1), "=r"(r2), "=r"(r3) : "r"(addr) : "memory");
}
__device__ __forceinline__ void mma_16816(float* d, uint32_t a0, uint32_t a1, uint32_t a2, uint32_t a3, uint32_t b0, uint32_t b1) {
  asm volatile("mma.sync.aligned.m16n8k16.row.col.f32.bf16.bf16.f32 {%0, %1, %2, %3}, {%4, %5, %6, %7}, {%8, %9}, {%0, %1, %2, %3};"
               : "+f"(d[0]), "+f"(d[1]), "+f"(d[2]), "+f"(d[3]) : "r"(a0), "r"(a1), "r"(a2), "r"(a3), "r"(b0), "r"(b1));
}
__device__ __forceinline__ void spin_cycles(int n) {
  const int t0 = (int)clock();
#pragma unroll 1
  while ((int)clock() - t0 < n) {}
}
__device__ __forceinline__ uint32_t pack_bf16(float lo, float hi) {
  uint32_t r; asm("cvt.rn.bf16x2.f32 %0, %1, %2;" : "=r"(r) : "f"(hi), "f"(lo)); return r;
}
__device__ __forceinline__ float bf_lo(uint32_t v) { return __uint_as_float(v << 16); }
__device__ __forceinline__ float bf_hi(uint32_t v) { return __uint_as_float(v & 0xffff0000u); }
__device__ __forceinline__ float rbf(float x) { return __bfloat162float(__float2bfloat16_rn(x)); }
__device__ __forceinline__ float ex2(float x) { float y; asm("ex2.approx.ftz.f32 %0, %1;" : "=f"(y) : "f"(x)); return y; }
__device__ __forceinline__ float rcp(float x) { float y; asm("rcp.approx.ftz.f32 %0, %1;" : "=f"(y) : "f"(x)); return y; }
__device__ __forceinline__ uint32_t shl_clamp(uint32_t v, uint32_t n) {
  uint32_t r; asm("shl.b32 %0, %1, %2;" : "=r"(r) : "r"(v), "r"(n)); return r;
}
__device__ __forceinline__ float warp_sum(float v) {
#pragma unroll
  for (int o = 16; o > 0; o >>= 1) v += __shfl_xor_sync(0xffffffffu, v, o);
  return v;
}
__device__ __forceinline__ float ln_inv(float var) {
  float r;
  asm("sqrt.approx.ftz.f32 %0, %1;" : "=f"(r) : "f"(rbf(rbf(var) + LN_EPS)));
  asm("rcp.approx.ftz.f32 %0, %1;" : "=f"(r) : "f"(rbf(r)));
  return r;
}
__device__ __forceinline__ uint32_t ln_pair(uint32_t x, uint32_t mean2, float inv) {
  const uint32_t d = hsub_bf2(x, mean2);
  return pack_bf16(bf_lo(d) * inv, bf_hi(d) * inv);
}
__device__ __forceinline__ uint32_t add_ln_pair(uint32_t x, uint32_t mean2, float inv) { return hadd_bf2(x, ln_pair(x, mean2, inv)); }
__device__ __forceinline__ uint32_t router_key(float r_bf, int row) {
  uint32_t u = __float_as_uint(r_bf);
  u = (u & 0x80000000u) ? ~u : (u | 0x80000000u);
  return (u & 0xFFFF0000u) | 0x8000u | (uint32_t)(SEQ - 1 - row);
}

template <uint32_t HA = 0x40000040u, uint32_t HB = 0x40000040u>
__device__ __forceinline__ void wg_ss192t(float* d, uint32_t da, uint32_t db, int scale_d) {
  asm volatile("{\n.reg .pred p;\n.reg .b64 dA, dB;\nmov.b64 dA, {%96, %99};\nmov.b64 dB, {%97, %100};\nsetp.ne.b32 p, %98, 0;\n"
    "wgmma.mma_async.sync.aligned.m64n192k16.f32.bf16.bf16 "
    "{%0, %1, %2, %3, %4, %5, %6, %7, %8, %9, %10, %11, %12, %13, %14, %15, "
    "%16, %17, %18, %19, %20, %21, %22, %23, %24, %25, %26, %27, %28, %29, %30, %31, "
    "%32, %33, %34, %35, %36, %37, %38, %39, %40, %41, %42, %43, %44, %45, %46, %47, "
    "%48, %49, %50, %51, %52, %53, %54, %55, %56, %57, %58, %59, %60, %61, %62, %63, "
    "%64, %65, %66, %67, %68, %69, %70, %71, %72, %73, %74, %75, %76, %77, %78, %79, "
    "%80, %81, %82, %83, %84, %85, %86, %87, %88, %89, %90, %91, %92, %93, %94, %95}, "
    "dA, dB, p, 1, 1, 0, 1;\n}\n"
    : "+f"(d[0]), "+f"(d[1]), "+f"(d[2]), "+f"(d[3]), "+f"(d[4]), "+f"(d[5]), "+f"(d[6]), "+f"(d[7]),
      "+f"(d[8]), "+f"(d[9]), "+f"(d[10]), "+f"(d[11]), "+f"(d[12]), "+f"(d[13]), "+f"(d[14]), "+f"(d[15]),
      "+f"(d[16]), "+f"(d[17]), "+f"(d[18]), "+f"(d[19]), "+f"(d[20]), "+f"(d[21]), "+f"(d[22]), "+f"(d[23]),
      "+f"(d[24]), "+f"(d[25]), "+f"(d[26]), "+f"(d[27]), "+f"(d[28]), "+f"(d[29]), "+f"(d[30]), "+f"(d[31]),
      "+f"(d[32]), "+f"(d[33]), "+f"(d[34]), "+f"(d[35]), "+f"(d[36]), "+f"(d[37]), "+f"(d[38]), "+f"(d[39]),
      "+f"(d[40]), "+f"(d[41]), "+f"(d[42]), "+f"(d[43]), "+f"(d[44]), "+f"(d[45]), "+f"(d[46]), "+f"(d[47]),
      "+f"(d[48]), "+f"(d[49]), "+f"(d[50]), "+f"(d[51]), "+f"(d[52]), "+f"(d[53]), "+f"(d[54]), "+f"(d[55]),
      "+f"(d[56]), "+f"(d[57]), "+f"(d[58]), "+f"(d[59]), "+f"(d[60]), "+f"(d[61]), "+f"(d[62]), "+f"(d[63]),
      "+f"(d[64]), "+f"(d[65]), "+f"(d[66]), "+f"(d[67]), "+f"(d[68]), "+f"(d[69]), "+f"(d[70]), "+f"(d[71]),
      "+f"(d[72]), "+f"(d[73]), "+f"(d[74]), "+f"(d[75]), "+f"(d[76]), "+f"(d[77]), "+f"(d[78]), "+f"(d[79]),
      "+f"(d[80]), "+f"(d[81]), "+f"(d[82]), "+f"(d[83]), "+f"(d[84]), "+f"(d[85]), "+f"(d[86]), "+f"(d[87]),
      "+f"(d[88]), "+f"(d[89]), "+f"(d[90]), "+f"(d[91]), "+f"(d[92]), "+f"(d[93]), "+f"(d[94]), "+f"(d[95])
    : "r"(da), "r"(db), "r"(scale_d), "n"(HA), "n"(HB));
}
template <uint32_t HA = 0x40000040u, uint32_t HB = 0x40000040u>
__device__ __forceinline__ void wg_ss192t_z(float* d, uint32_t da, uint32_t db) {
  asm volatile("{\n.reg .pred p;\n.reg .b64 dA, dB;\nmov.b64 dA, {%96, %98};\nmov.b64 dB, {%97, %99};\nsetp.ne.b32 p, 0, 0;\n"
    "wgmma.mma_async.sync.aligned.m64n192k16.f32.bf16.bf16 "
    "{%0, %1, %2, %3, %4, %5, %6, %7, %8, %9, %10, %11, %12, %13, %14, %15, "
    "%16, %17, %18, %19, %20, %21, %22, %23, %24, %25, %26, %27, %28, %29, %30, %31, "
    "%32, %33, %34, %35, %36, %37, %38, %39, %40, %41, %42, %43, %44, %45, %46, %47, "
    "%48, %49, %50, %51, %52, %53, %54, %55, %56, %57, %58, %59, %60, %61, %62, %63, "
    "%64, %65, %66, %67, %68, %69, %70, %71, %72, %73, %74, %75, %76, %77, %78, %79, "
    "%80, %81, %82, %83, %84, %85, %86, %87, %88, %89, %90, %91, %92, %93, %94, %95}, "
    "dA, dB, p, 1, 1, 0, 1;\n}\n"
    : "=f"(d[0]), "=f"(d[1]), "=f"(d[2]), "=f"(d[3]), "=f"(d[4]), "=f"(d[5]), "=f"(d[6]), "=f"(d[7]),
      "=f"(d[8]), "=f"(d[9]), "=f"(d[10]), "=f"(d[11]), "=f"(d[12]), "=f"(d[13]), "=f"(d[14]), "=f"(d[15]),
      "=f"(d[16]), "=f"(d[17]), "=f"(d[18]), "=f"(d[19]), "=f"(d[20]), "=f"(d[21]), "=f"(d[22]), "=f"(d[23]),
      "=f"(d[24]), "=f"(d[25]), "=f"(d[26]), "=f"(d[27]), "=f"(d[28]), "=f"(d[29]), "=f"(d[30]), "=f"(d[31]),
      "=f"(d[32]), "=f"(d[33]), "=f"(d[34]), "=f"(d[35]), "=f"(d[36]), "=f"(d[37]), "=f"(d[38]), "=f"(d[39]),
      "=f"(d[40]), "=f"(d[41]), "=f"(d[42]), "=f"(d[43]), "=f"(d[44]), "=f"(d[45]), "=f"(d[46]), "=f"(d[47]),
      "=f"(d[48]), "=f"(d[49]), "=f"(d[50]), "=f"(d[51]), "=f"(d[52]), "=f"(d[53]), "=f"(d[54]), "=f"(d[55]),
      "=f"(d[56]), "=f"(d[57]), "=f"(d[58]), "=f"(d[59]), "=f"(d[60]), "=f"(d[61]), "=f"(d[62]), "=f"(d[63]),
      "=f"(d[64]), "=f"(d[65]), "=f"(d[66]), "=f"(d[67]), "=f"(d[68]), "=f"(d[69]), "=f"(d[70]), "=f"(d[71]),
      "=f"(d[72]), "=f"(d[73]), "=f"(d[74]), "=f"(d[75]), "=f"(d[76]), "=f"(d[77]), "=f"(d[78]), "=f"(d[79]),
      "=f"(d[80]), "=f"(d[81]), "=f"(d[82]), "=f"(d[83]), "=f"(d[84]), "=f"(d[85]), "=f"(d[86]), "=f"(d[87]),
      "=f"(d[88]), "=f"(d[89]), "=f"(d[90]), "=f"(d[91]), "=f"(d[92]), "=f"(d[93]), "=f"(d[94]), "=f"(d[95])
    : "r"(da), "r"(db), "n"(HA), "n"(HB));
}
template <uint32_t HA = 0x40000040u, uint32_t HB = 0x40000040u>
__device__ __forceinline__ void wg_ss128t(float* d, uint32_t da, uint32_t db, int scale_d) {
  asm volatile("{\n.reg .pred p;\n.reg .b64 dA, dB;\nmov.b64 dA, {%64, %67};\nmov.b64 dB, {%65, %68};\nsetp.ne.b32 p, %66, 0;\n"
    "wgmma.mma_async.sync.aligned.m64n128k16.f32.bf16.bf16 "
    "{%0, %1, %2, %3, %4, %5, %6, %7, %8, %9, %10, %11, %12, %13, %14, %15, "
    "%16, %17, %18, %19, %20, %21, %22, %23, %24, %25, %26, %27, %28, %29, %30, %31, "
    "%32, %33, %34, %35, %36, %37, %38, %39, %40, %41, %42, %43, %44, %45, %46, %47, "
    "%48, %49, %50, %51, %52, %53, %54, %55, %56, %57, %58, %59, %60, %61, %62, %63}, "
    "dA, dB, p, 1, 1, 0, 1;\n}\n"
    : "+f"(d[0]), "+f"(d[1]), "+f"(d[2]), "+f"(d[3]), "+f"(d[4]), "+f"(d[5]), "+f"(d[6]), "+f"(d[7]),
      "+f"(d[8]), "+f"(d[9]), "+f"(d[10]), "+f"(d[11]), "+f"(d[12]), "+f"(d[13]), "+f"(d[14]), "+f"(d[15]),
      "+f"(d[16]), "+f"(d[17]), "+f"(d[18]), "+f"(d[19]), "+f"(d[20]), "+f"(d[21]), "+f"(d[22]), "+f"(d[23]),
      "+f"(d[24]), "+f"(d[25]), "+f"(d[26]), "+f"(d[27]), "+f"(d[28]), "+f"(d[29]), "+f"(d[30]), "+f"(d[31]),
      "+f"(d[32]), "+f"(d[33]), "+f"(d[34]), "+f"(d[35]), "+f"(d[36]), "+f"(d[37]), "+f"(d[38]), "+f"(d[39]),
      "+f"(d[40]), "+f"(d[41]), "+f"(d[42]), "+f"(d[43]), "+f"(d[44]), "+f"(d[45]), "+f"(d[46]), "+f"(d[47]),
      "+f"(d[48]), "+f"(d[49]), "+f"(d[50]), "+f"(d[51]), "+f"(d[52]), "+f"(d[53]), "+f"(d[54]), "+f"(d[55]),
      "+f"(d[56]), "+f"(d[57]), "+f"(d[58]), "+f"(d[59]), "+f"(d[60]), "+f"(d[61]), "+f"(d[62]), "+f"(d[63])
    : "r"(da), "r"(db), "r"(scale_d), "n"(HA), "n"(HB));
}
template <uint32_t HB = 0x40000040u>
__device__ __forceinline__ void wg_rs64(float* d, uint32_t a0, uint32_t a1, uint32_t a2, uint32_t a3, uint32_t db, int scale_d) {
  asm volatile("{\n.reg .pred p;\n.reg .b64 dB;\nmov.b64 dB, {%36, %38};\nsetp.ne.b32 p, %37, 0;\n"
    "wgmma.mma_async.sync.aligned.m64n64k16.f32.bf16.bf16 "
    "{%0, %1, %2, %3, %4, %5, %6, %7, %8, %9, %10, %11, %12, %13, %14, %15, "
    "%16, %17, %18, %19, %20, %21, %22, %23, %24, %25, %26, %27, %28, %29, %30, %31}, "
    "{%32, %33, %34, %35}, dB, p, 1, 1, 0;\n}\n"
    : "+f"(d[0]), "+f"(d[1]), "+f"(d[2]), "+f"(d[3]), "+f"(d[4]), "+f"(d[5]), "+f"(d[6]), "+f"(d[7]),
      "+f"(d[8]), "+f"(d[9]), "+f"(d[10]), "+f"(d[11]), "+f"(d[12]), "+f"(d[13]), "+f"(d[14]), "+f"(d[15]),
      "+f"(d[16]), "+f"(d[17]), "+f"(d[18]), "+f"(d[19]), "+f"(d[20]), "+f"(d[21]), "+f"(d[22]), "+f"(d[23]),
      "+f"(d[24]), "+f"(d[25]), "+f"(d[26]), "+f"(d[27]), "+f"(d[28]), "+f"(d[29]), "+f"(d[30]), "+f"(d[31])
    : "r"(a0), "r"(a1), "r"(a2), "r"(a3), "r"(db), "r"(scale_d), "n"(HB));
}
template <uint32_t HB = 0x40000040u>
__device__ __forceinline__ void wg_rs64_z(float* d, uint32_t a0, uint32_t a1, uint32_t a2, uint32_t a3, uint32_t db) {
  asm volatile("{\n.reg .pred p;\n.reg .b64 dB;\nmov.b64 dB, {%36, %37};\nsetp.ne.b32 p, 0, 0;\n"
    "wgmma.mma_async.sync.aligned.m64n64k16.f32.bf16.bf16 "
    "{%0, %1, %2, %3, %4, %5, %6, %7, %8, %9, %10, %11, %12, %13, %14, %15, "
    "%16, %17, %18, %19, %20, %21, %22, %23, %24, %25, %26, %27, %28, %29, %30, %31}, "
    "{%32, %33, %34, %35}, dB, p, 1, 1, 0;\n}\n"
    : "=f"(d[0]), "=f"(d[1]), "=f"(d[2]), "=f"(d[3]), "=f"(d[4]), "=f"(d[5]), "=f"(d[6]), "=f"(d[7]),
      "=f"(d[8]), "=f"(d[9]), "=f"(d[10]), "=f"(d[11]), "=f"(d[12]), "=f"(d[13]), "=f"(d[14]), "=f"(d[15]),
      "=f"(d[16]), "=f"(d[17]), "=f"(d[18]), "=f"(d[19]), "=f"(d[20]), "=f"(d[21]), "=f"(d[22]), "=f"(d[23]),
      "=f"(d[24]), "=f"(d[25]), "=f"(d[26]), "=f"(d[27]), "=f"(d[28]), "=f"(d[29]), "=f"(d[30]), "=f"(d[31])
    : "r"(a0), "r"(a1), "r"(a2), "r"(a3), "r"(db), "n"(HB));
}
template <uint32_t HB = 0x40000040u>
__device__ __forceinline__ void wg_rs32(float* d, uint32_t a0, uint32_t a1, uint32_t a2, uint32_t a3, uint32_t db, int scale_d) {
  asm volatile("{\n.reg .pred p;\n.reg .b64 dB;\nmov.b64 dB, {%20, %22};\nsetp.ne.b32 p, %21, 0;\n"
    "wgmma.mma_async.sync.aligned.m64n32k16.f32.bf16.bf16 "
    "{%0, %1, %2, %3, %4, %5, %6, %7, %8, %9, %10, %11, %12, %13, %14, %15}, "
    "{%16, %17, %18, %19}, dB, p, 1, 1, 0;\n}\n"
    : "+f"(d[0]), "+f"(d[1]), "+f"(d[2]), "+f"(d[3]), "+f"(d[4]), "+f"(d[5]), "+f"(d[6]), "+f"(d[7]),
      "+f"(d[8]), "+f"(d[9]), "+f"(d[10]), "+f"(d[11]), "+f"(d[12]), "+f"(d[13]), "+f"(d[14]), "+f"(d[15])
    : "r"(a0), "r"(a1), "r"(a2), "r"(a3), "r"(db), "r"(scale_d), "n"(HB));
}
template <uint32_t HB = 0x40000040u>
__device__ __forceinline__ void wg_rs32_z(float* d, uint32_t a0, uint32_t a1, uint32_t a2, uint32_t a3, uint32_t db) {
  asm volatile("{\n.reg .pred p;\n.reg .b64 dB;\nmov.b64 dB, {%20, %21};\nsetp.ne.b32 p, 0, 0;\n"
    "wgmma.mma_async.sync.aligned.m64n32k16.f32.bf16.bf16 "
    "{%0, %1, %2, %3, %4, %5, %6, %7, %8, %9, %10, %11, %12, %13, %14, %15}, "
    "{%16, %17, %18, %19}, dB, p, 1, 1, 0;\n}\n"
    : "=f"(d[0]), "=f"(d[1]), "=f"(d[2]), "=f"(d[3]), "=f"(d[4]), "=f"(d[5]), "=f"(d[6]), "=f"(d[7]),
      "=f"(d[8]), "=f"(d[9]), "=f"(d[10]), "=f"(d[11]), "=f"(d[12]), "=f"(d[13]), "=f"(d[14]), "=f"(d[15])
    : "r"(a0), "r"(a1), "r"(a2), "r"(a3), "r"(db), "n"(HB));
}
template <uint32_t HB = 0x40000040u>
__device__ __forceinline__ void wg_rs40t(float* d, uint32_t a0, uint32_t a1, uint32_t a2, uint32_t a3, uint32_t db, int scale_d) {
  asm volatile("{\n.reg .pred p;\n.reg .b64 dB;\nmov.b64 dB, {%24, %26};\nsetp.ne.b32 p, %25, 0;\n"
    "wgmma.mma_async.sync.aligned.m64n40k16.f32.bf16.bf16 "
    "{%0, %1, %2, %3, %4, %5, %6, %7, %8, %9, %10, %11, %12, %13, %14, %15, "
    "%16, %17, %18, %19}, "
    "{%20, %21, %22, %23}, dB, p, 1, 1, 1;\n}\n"
    : "+f"(d[0]), "+f"(d[1]), "+f"(d[2]), "+f"(d[3]), "+f"(d[4]), "+f"(d[5]), "+f"(d[6]), "+f"(d[7]),
      "+f"(d[8]), "+f"(d[9]), "+f"(d[10]), "+f"(d[11]), "+f"(d[12]), "+f"(d[13]), "+f"(d[14]), "+f"(d[15]),
      "+f"(d[16]), "+f"(d[17]), "+f"(d[18]), "+f"(d[19])
    : "r"(a0), "r"(a1), "r"(a2), "r"(a3), "r"(db), "r"(scale_d), "n"(HB));
}
template <uint32_t HB = 0x40000040u>
__device__ __forceinline__ void wg_rs40t_z(float* d, uint32_t a0, uint32_t a1, uint32_t a2, uint32_t a3, uint32_t db) {
  asm volatile("{\n.reg .pred p;\n.reg .b64 dB;\nmov.b64 dB, {%24, %25};\nsetp.ne.b32 p, 0, 0;\n"
    "wgmma.mma_async.sync.aligned.m64n40k16.f32.bf16.bf16 "
    "{%0, %1, %2, %3, %4, %5, %6, %7, %8, %9, %10, %11, %12, %13, %14, %15, "
    "%16, %17, %18, %19}, "
    "{%20, %21, %22, %23}, dB, p, 1, 1, 1;\n}\n"
    : "=f"(d[0]), "=f"(d[1]), "=f"(d[2]), "=f"(d[3]), "=f"(d[4]), "=f"(d[5]), "=f"(d[6]), "=f"(d[7]),
      "=f"(d[8]), "=f"(d[9]), "=f"(d[10]), "=f"(d[11]), "=f"(d[12]), "=f"(d[13]), "=f"(d[14]), "=f"(d[15]),
      "=f"(d[16]), "=f"(d[17]), "=f"(d[18]), "=f"(d[19])
    : "r"(a0), "r"(a1), "r"(a2), "r"(a3), "r"(db), "n"(HB));
}

constexpr uint32_t SOFF = 1024;
constexpr int STG = 57344, QE = 28672, SL_W = 16384, SL_HD = 12288, SL_F = 3 * STG, AT_ST = 131072;
constexpr int OFF_ONES = 4 * STG;
constexpr int OFF_PATCH = OFF_ONES + 1024;
constexpr int OFF_CS = OFF_PATCH + 768;
constexpr int OFF_BAR = OFF_CS + 768;
constexpr int OFF_MISC = OFF_BAR + 416;
constexpr int SMEM_BYTES = OFF_MISC + 96;
enum { B_FULL = 0, B_EMPTY = 6, B_HALO = 12, B_CS = 15, B_KVREADY, B_QDONE = B_KVREADY + 2, B_QREADY, B_OST, B_ADONE = B_OST + 2,
       B_QFREE, B_WS, B_WFULL, B_WEMPTY = B_WFULL + 4, B_GU = B_WEMPTY + 4, B_RES = B_GU + 2, B_DN,
       B_HX = B_DN + 2, B_RST, B_UNIT, B_COUNT = B_UNIT + 8 };
static_assert(B_COUNT <= 52, "barrier area");
__host__ __device__ constexpr int bar_count(int i) {
  return i >= B_EMPTY && i < B_HALO ? 17 : i == B_CS ? 5 : i == B_QFREE ? 16
       : i == B_KVREADY || i == B_KVREADY + 1 || i == B_QREADY ? 8 : i == B_ADONE ? 32 : i == B_OST ? 2 : i >= B_UNIT ? 4
       : i == B_QDONE || (i >= B_WEMPTY && i < B_GU) ? 16 : i == B_RST ? 4 : i == B_RES ? 2 : 1;
}
enum { M_KEY = 0, M_MEAN, M_INV, M_WSUM, M_TAG, M_SEL0, M_PMEAN, M_PINV, M_XQ = 8, M_KEYS = 12, M_PROG = 20 };
constexpr int FFN_PIECE = 14336;
constexpr int T_XS = 163840, T_HP = T_XS + 1024;
constexpr float LSUM_MIN = 5.421010862427522e-20f, LSUM_MAX = 1.8446744073709552e19f;
constexpr float SM_C = 0.17677669529663687f * 1.4426950408889634f;
constexpr uint32_t VSTEP = 64u - (64u << 16);
#define D_SPLIT 1
#define WS1_PACE 1000
#define WS_AT 5
#define WS_PACE 1000
#define GUB_PACE 800
#define ULIST1 0x854
#define ULIST2 0x8721
#define SOLO 1
#define HID_H 1
#define PRE_N 2
#define RES_K 6
#define FAKE 0
#define X_STAGGER 500
#define GU_PACE1 1600
#define GU_PACE 2500
#define DELAY_P 600
#define DELAY_S 2400
#define DELAY_Y 400

struct Params {
  CUtensorMap mapA[2], mapW, mapWo, mapRes[2], mapXst[2], mapG, mapU, mapD, mapWs;
  const bf16 *x, *wqkv, *wo, *w_r, *w_g, *w_u, *w_d;
  bf16* out;
};

template <int N> __device__ __forceinline__ void exp_pack(const float* s, uint32_t* p) {
#pragma unroll
  for (int b = 0; b < N; b++) {
    p[2 * b] = pack_bf16(ex2(s[4 * b]), ex2(s[4 * b + 1]));
    p[2 * b + 1] = pack_bf16(ex2(s[4 * b + 2]), ex2(s[4 * b + 3]));
  }
}
template <int KIND> __device__ __forceinline__ void edge16(const float* sd, const float* st, uint32_t* pd, uint32_t* pt, int dl, uint32_t mt) {
  if (KIND == 0) { exp_pack<2>(sd, pd); pt[0] = pt[1] = pt[2] = pt[3] = 0; }
  else if (KIND == 1) { exp_pack<2>(st, pt); pd[0] = pd[1] = pd[2] = pd[3] = 0; }
  else {
    const uint32_t a = pack_bf16(ex2(dl >= 0 ? sd[0] : st[0]), ex2(dl >= 1 ? sd[1] : st[1]));
    const uint32_t c = pack_bf16(ex2(dl >= 0 ? sd[6] : st[6]), ex2(dl >= 1 ? sd[7] : st[7]));
    pd[0] = a & ~mt; pt[0] = a & mt; pd[3] = c & ~mt; pt[3] = c & mt;
    pd[1] = pack_bf16(ex2(sd[2]), ex2(sd[3])); pt[1] = 0;
    pt[2] = pack_bf16(ex2(st[4]), ex2(st[5])); pd[2] = 0;
  }
}
__device__ __forceinline__ void edge32(const float* sd, const float* st, uint32_t* pd, uint32_t* pt, int rel, int dl, uint32_t mt) {
  if (rel > 1) { edge16<0>(sd, st, pd, pt, dl, mt); edge16<0>(sd + 8, st + 8, pd + 4, pt + 4, dl, mt); }
  else if (rel == 1) { edge16<0>(sd, st, pd, pt, dl, mt); edge16<2>(sd + 8, st + 8, pd + 4, pt + 4, dl, mt); }
  else if (rel == 0) { edge16<2>(sd, st, pd, pt, dl, mt); edge16<1>(sd + 8, st + 8, pd + 4, pt + 4, dl, mt); }
  else { edge16<1>(sd, st, pd, pt, dl, mt); edge16<1>(sd + 8, st + 8, pd + 4, pt + 4, dl, mt); }
}
__device__ __forceinline__ void qk64(float* s, const uint32_t* qf, uint32_t kd) {
  wg_rs64_z<H64>(s, qf[0], qf[1], qf[2], qf[3], kd);
  wg_rs64<H64>(s, qf[4], qf[5], qf[6], qf[7], kd + 2, 1);
}
__device__ __forceinline__ void qk32x2(float* a, float* b, const uint32_t* qf, uint32_t ka, uint32_t kb) {
  wg_rs32_z<H64>(a, qf[0], qf[1], qf[2], qf[3], ka); wg_rs32_z<H64>(b, qf[0], qf[1], qf[2], qf[3], kb);
  wg_rs32<H64>(a, qf[4], qf[5], qf[6], qf[7], ka + 2, 1); wg_rs32<H64>(b, qf[4], qf[5], qf[6], qf[7], kb + 2, 1);
}
__device__ __forceinline__ void pv32(float* o, const uint32_t* p, uint32_t vd) {
  wg_rs40t<H64>(o, p[0], p[1], p[2], p[3], vd, 1);
  wg_rs40t<H64>(o, p[4], p[5], p[6], p[7], vd + VSTEP, 1);
}

__device__ __forceinline__ void fma8(float* d, uint4 w, float x) {
  d[0] += x * bf_lo(w.x); d[1] += x * bf_hi(w.x); d[2] += x * bf_lo(w.y); d[3] += x * bf_hi(w.y);
  d[4] += x * bf_lo(w.z); d[5] += x * bf_hi(w.z); d[6] += x * bf_lo(w.w); d[7] += x * bf_hi(w.w);
}

__device__ __forceinline__ int fresh_tid() { int r; asm volatile("mov.u32 %0, %%tid.x;" : "=r"(r)); return r; }
__device__ __forceinline__ int fresh_bid() { int r; asm volatile("mov.u32 %0, %%ctaid.x;" : "=r"(r)); return r; }
#define PHASE_IDS                                                                                                              \
  const uint32_t sbase = smem_u32(smem);                                                                                       \
  const int tid = fresh_tid(), bid = fresh_bid();                                                                              \
  const int warp = __shfl_sync(0xffffffffu, tid >> 5, 0), lane = tid & 31;                                                     \
  const int rank = bid & 1, cl = bid >> 1, rb = bid & 7, hp = bid >> 3;                  \
  const int mb = 2 * rb + (hp >> 3), nb = hp & 7;                                            \
  const int wg = warp >> 2, wi = warp & 3, g = lane >> 2, q = lane & 3;                                                        \
  const int mi = lane >> 3, srow = wi * 16 + (mi & 1) * 8 + (lane & 7);      \
  auto bar = [&](int i) { return sbase + OFF_BAR + 8 * i; };                                                                   \
  volatile uint32_t* s_misc = (volatile uint32_t*)(smem + OFF_MISC);                                                           \
  auto load_w = [&](int s, int kt) {                           \
    tma_load3_mc(sbase + s * QE + SL_W + rank * 6144, &P.mapW, hp * 64, kt * 32 + rank * 16, 0, bar(B_FULL + s));              \
  };                                                                                                                           \
  auto load_a = [&](int s, int kt, int layer) { mbar_expect_tx(bar(B_FULL + s), QE); tma_load2(sbase + s * QE, &P.mapA[layer], kt * 32, rb * 256, bar(B_FULL + s)); }; \
  auto load_wo = [&](int k) {                                                 \
    mbar_expect_tx(bar(B_WFULL + (k & 3)), 32768);                                                                             \
    tma_load3_mc(sbase + (k & 3) * 32768 + 16384 + rank * 8192, &P.mapWo, nb * 128 + rank * 64, (k >> 3) * 32, (k & 7) * 2, bar(B_WFULL + (k & 3))); \
  };                                                                                                                           \
  auto load_o = [&](int k) {                                                            \
    bulk_load_h(sbase + (k & 3) * 32768, g_o + (size_t)(mb * 16 + k) * 16384, 16384, bar(B_WFULL + (k & 3)), policy_evict_first());                    \
  };                                                                                                                           \
  auto import_halo = [&](int layer, int h) {                                   \
    poll_flag(&g_kvflag[(rb - 1) >> 1][hp][h].v[layer], s_misc[M_TAG]);                                                        \
    fence_async_global();                                                                                                      \
    const uint8_t* src = g_kv + (size_t)(((rb - 1) >> 1) * 16 + hp) * 65536 + h * 32768;                                       \
    mbar_expect_tx(bar(B_HALO + 2 * h), 16384 << h);                                                                           \
    bulk_load_h(sbase + (h ? 65536 : 16384), src + (h ? 0 : 16384), 16384 << h, bar(B_HALO + 2 * h), policy_evict_first());    \
    if (h == 0) { mbar_expect_tx(bar(B_HALO + 1), 16384); bulk_load_h(sbase, src, 16384, bar(B_HALO + 1), policy_evict_first()); } \
  };                                                                                                                           \
  auto load_res = [&](int half, int layer) {                                                  \
    mbar_expect_tx(bar(B_RES), 16384);                                                                                         \
    tma_load2_h(sbase + AT_ST + half * 16384, &P.mapRes[layer], nb * 128, mb * 128 + half * 64, bar(B_RES), policy_evict_first());                     \
    tma_load2_h(sbase + AT_ST + half * 16384 + 8192, &P.mapRes[layer], nb * 128 + 64, mb * 128 + half * 64, bar(B_RES), policy_evict_first());         \
  };                                                                                                                           \
  auto store_tile = [&](int layer, int skip, bool wait) {                                           \
    _Pragma("unroll 1")                                                                                                        \
    for (int j = 0; j < 4; j++)                                                                                                \
      if ((j & 1) != skip) tma_store(&P.mapXst[layer], sbase + AT_ST + (j & 1) * 16384 + (j >> 1) * 8192, nb * 128 + (j >> 1) * 64, mb * 128 + (j & 1) * 64); \
    bulk_commit();                                                                                                             \
    if (wait) bulk_wait_all();                                                                                                 \
  };                                                                                                                           \
  auto load_ws = [&](int pace) {                                    \
    mbar_expect_tx(bar(B_WS), 4 * SL_HD);                                                                                      \
    _Pragma("unroll 1")                                                                                                        \
    for (int j = 0; j < 4; j++) {                                                                                              \
      tma_load3(sbase + SL_F + j * SL_HD, &P.mapWs, hp * 64, rb * 128 + j * 32, 0, bar(B_WS));                                 \
      if (pace) spin_cycles(pace);                                                                                             \
    }                                                                                                                          \
  };                                                                                                                           \
  auto load_gu = [&](int half, int pace) {                             \
    mbar_expect_tx(bar(B_GU + half), 4 * FFN_PIECE);                                                                           \
    _Pragma("unroll 1")                                                                                                        \
    for (int j = 0; j < 4; j++) {                                                                                              \
      tma_load2_h(sbase + SL_F + j * FFN_PIECE, &P.mapG + (j >> 1), cl * 56, rank * 512 + half * 256 + (j & 1) * 128, bar(B_GU + half), policy_evict_first()); \
      if (j < 3) spin_cycles(pace);                                                                                            \
    }                                                                                                                          \
  };                                                                                                                           \
  auto fetch_gu = [&](uint32_t* a, int ks, int ct) {                 \
    ldsm_x4_t(sbase + SL_F + (mi & 1) * 2 * FFN_PIECE + (ks * 16 + (mi >> 1) * 8 + (lane & 7)) * 112 + ct * 16, a[0], a[1], a[2], a[3]); \
  };                                                                                                                           \
  auto send_gu = [&](float gate, float up, int ct, int part) {        \
    const int u = 8 * ct + g, own = u >= 28;                                                                                   \
    if (q == 0) st_async2(mapa(sbase + T_HP + ((rank * 5 + part) * 28 + u - 28 * own) * 8, own), gate, up, mapa(bar(B_HX), own)); \
  };                                                                                                                           \
  auto hidden = [&]() {                                     \
    const float2* hpart = (const float2*)(smem + T_HP) + min(lane, 27);                                                        \
    float gs[2] = {0.f, 0.f}, us[2] = {0.f, 0.f};                                                                              \
    _Pragma("unroll")                                                                                                          \
    for (int j = 0; j < 10; j++) { const float2 v = hpart[j * 28]; gs[j & 1] += v.x; us[j & 1] += v.y; }                       \
    const float gb = rbf(gs[0] + gs[1]), ub = rbf(us[0] + us[1]);                                                              \
    return lane < 28 ? rbf(__fdividef(gb, 1.f + __expf(-gb))) * ub : 0.f;                                                      \
  };                                                                                                                           \
  (void)load_wo; (void)load_o; (void)import_halo; (void)load_res; (void)store_tile; (void)fetch_gu; (void)load_ws; (void)load_gu; (void)send_gu; (void)hidden; (void)cl; (void)mb; (void)nb; (void)wg; (void)g; (void)q; (void)srow; (void)s_misc; (void)load_w; (void)load_a;

__global__ void __launch_bounds__(512, 1) mega_kernel(const __grid_constant__ Params P) {
  extern __shared__ __align__(1024) uint8_t smem[];
  {
    PHASE_IDS
    if (warp == 0) {
      if (lane == 0) {
        prefetch_tmap(&P.mapA[0]); prefetch_tmap(&P.mapW);
#pragma unroll
        for (int i = 0; i < 6; i++) mbar_init(bar(B_FULL + i), 1);
        asm volatile("fence.mbarrier_init.release.cluster;" ::: "memory");
      }
      __syncwarp();
#pragma unroll 1
      for (int i = 0; i < SOLO; i++) {
        load_a(i, i, 0);
        tma_load3(sbase + i * QE + SL_W, &P.mapW, hp * 64, i * 32, 0, bar(B_FULL + i));
        tma_load3(sbase + i * QE + SL_W + 6144, &P.mapW, hp * 64, i * 32 + 16, 0, bar(B_FULL + i));
      }
      load_a(SOLO, SOLO, 0);
    } else if (tid == 32) {
#pragma unroll
      for (int i = 6; i < B_COUNT; i++) mbar_init(bar(i), bar_count(i));
      asm volatile("fence.mbarrier_init.release.cluster;" ::: "memory");
    } else if (warp == 8) {
      ((uint4*)(smem + OFF_ONES))[lane] = make_uint4(0x3F803F80u, 0x3F803F80u, 0x3F803F80u, 0x3F803F80u);
      ((uint4*)(smem + OFF_ONES))[lane + 32] = make_uint4(0x3F803F80u, 0x3F803F80u, 0x3F803F80u, 0x3F803F80u);
    }
    __syncwarp();
    cluster_arrive(); cluster_wait();
    if (warp == 0) {
      PROFL(0, 1);
      load_w(SOLO, SOLO);
#pragma unroll 1
      for (int i = SOLO + 1; i < PRE_N; i++) { load_a(i, i, 0); load_w(i, i); }
    } else if (tid == 96) {
      if ((sbase & 0x3FFFF) != SOFF) __trap();
    }
    __syncwarp();
  }

  regs_dec<120>();
#pragma unroll 1
  for (unsigned pass_v = 0;;) {
    const unsigned pass = __shfl_sync(0xffffffffu, pass_v, 0);
    if (__shfl_sync(0xffffffffu, fresh_tid() >> 8, 0)) {
      if (pass > 0) {
        const unsigned layer = pass - 1;
        uint32_t xr[32];
        {
          PHASE_IDS
          float acc[64];
#pragma unroll
          for (int i = 0; i < 64; i++) acc[i] = 0.f;
          const uint32_t da0 = dlo(SOFF, 16) + (wg - 2) * 256;
          constexpr uint32_t db0 = dlo(SOFF + 16384, 8192);
#pragma unroll 1
          for (int k4 = 0; k4 < 4; k4++) {
#pragma unroll
            for (int st = 0; st < 4; st++) {
              mbar_wait(bar(B_WFULL + st), k4 & 1);
              wg_fence();
#pragma unroll
              for (int kk = 0; kk < 4; kk++)
                wg_ss128t<H64, H128>(acc, da0 + ((st * 32768) >> 4) + (kk >> 1) * 512 + (kk & 1) * 2, db0 + ((st * 32768) >> 4) + kk * 128, 1);
              wg_commit();
              if (st == 0 && k4 == 0 && warp == 9) PROF(10);
              if (warp == 9) STEPT(16 + k4 * 4 + st);
              wg_wait<1>();
              if (lane < 2 && (st == 0 ? k4 > 0 : (st < 3 || k4 < 3))) mbar_arrive_cluster(bar(B_WEMPTY + ((st + 3) & 3)), lane);
            }
          }
          mbar_wait(bar(B_RES), layer);
          mbar_wait(bar(B_RST), layer);
          const uint32_t zoff = AT_ST + (wg - 2) * 16384;
#pragma unroll
          for (int j = 0; j < 8; j++)
            ldsm_x4(sbase + zoff + srow * 128 + (j >> 2) * 8192 + ((((2 * j + (mi >> 1)) & 7) ^ (srow & 7)) << 4), xr[4 * j], xr[4 * j + 1], xr[4 * j + 2], xr[4 * j + 3]);
          wg_wait<0>();
          fence_regs<64>(acc);
          if (warp == 9) PROF(11);
          if (layer == 0 && lane < 2) mbar_arrive_cluster(bar(B_QFREE), lane);
#pragma unroll
          for (int j = 0; j < 32; j++) xr[j] = hadd_bf2(xr[j], pack_bf16(acc[2 * j], acc[2 * j + 1]));
        }
        PHASE_IDS
        const uint32_t tag = s_misc[M_TAG];
        const int grow = mb * 128 + (warp - 8) * 16 + g;
        {
          float d[6][4];
#pragma unroll
          for (int i = 0; i < 6; i++) d[i][0] = d[i][1] = d[i][2] = d[i][3] = 0.f;
          const uint4* tab = (const uint4*)(smem + OFF_PATCH + (g == 1 ? q * 64 : (g == 0 ? 256 : 320)));
#pragma unroll
          for (int j2 = 0; j2 < 4; j2++) {
            const uint4 w = tab[j2];
#pragma unroll
            for (int jj = 0; jj < 2; jj++) {
              const uint32_t* a = &xr[8 * j2 + 4 * jj];
              mma_16816(d[jj], a[0], a[1], a[2], a[3], jj ? w.z : w.x, jj ? w.w : w.y);
              mma_16816(d[2 + jj], a[0], a[1], a[2], a[3], a[0], a[2]);
              mma_16816(d[4 + jj], a[0], a[1], a[2], a[3], a[1], a[3]);
            }
          }
          const float sq0 = __shfl_sync(0xffffffffu, (g & 1) ? d[2][1] + d[3][1] : d[2][0] + d[3][0], g * 4 + (g >> 1));
          const float sq1 = __shfl_sync(0xffffffffu, (g & 1) ? d[4][3] + d[5][3] : d[4][2] + d[5][2], g * 4 + (g >> 1));
          uint4* dst = &g_part[layer][nb * SEQ + grow];
          if (q == 0) {
            st_relaxed4(dst, make_uint4(__float_as_uint(d[0][0] + d[1][0]), __float_as_uint(sq0), __float_as_uint(d[0][1] + d[1][1]), tag));
            st_relaxed4(dst + 8, make_uint4(__float_as_uint(d[0][2] + d[1][2]), __float_as_uint(sq1), __float_as_uint(d[0][3] + d[1][3]), tag));
          }
        }
        if (warp == 9) PROF(12);
        asm volatile("bar.arrive 6, 320;" ::: "memory");
        const int t_p = (int)clock();
        const uint32_t zrow = sbase + AT_ST + (wg - 2) * 16384 + srow * 128;
        if (layer == 0) {
#pragma unroll
          for (int j = 0; j < 8; j++)
            stsm_x4(zrow + (j >> 2) * 8192 + ((((2 * j + (mi >> 1)) & 7) ^ (srow & 7)) << 4), xr[4 * j], xr[4 * j + 1], xr[4 * j + 2], xr[4 * j + 3]);
          fence_async_smem();
          asm volatile("bar.arrive 8, 288;" ::: "memory");
        }
#pragma unroll 1
        while ((int)clock() - t_p < DELAY_P) {}
        {
          const uint4* src = &g_part[layer][2 * q * SEQ + grow];
          uint4 pp[4];
          uint32_t spins = 0;
#pragma unroll 1
          do {
            pp[0] = ld_relaxed4(src); pp[1] = ld_relaxed4(src + SEQ); pp[2] = ld_relaxed4(src + 8); pp[3] = ld_relaxed4(src + SEQ + 8);
          } while (!__all_sync(0xffffffffu, pp[0].w == tag && pp[1].w == tag && pp[2].w == tag && pp[3].w == tag) && ++spins < SPIN_LIMIT);
          if (warp == 9) PROF(13);
          const int rr = q >> 1;
          float s3[3];
#pragma unroll
          for (int c = 0; c < 3; c++) {
            const float lo = __uint_as_float(c == 0 ? pp[0].x : c == 1 ? pp[0].y : pp[0].z) + __uint_as_float(c == 0 ? pp[1].x : c == 1 ? pp[1].y : pp[1].z);
            const float hi = __uint_as_float(c == 0 ? pp[2].x : c == 1 ? pp[2].y : pp[2].z) + __uint_as_float(c == 0 ? pp[3].x : c == 1 ? pp[3].y : pp[3].z);
            s3[c] = (rr ? hi : lo) + __shfl_xor_sync(0xffffffffu, rr ? lo : hi, 2);
            s3[c] += __shfl_xor_sync(0xffffffffu, s3[c], 1);
          }
          const float mu = s3[0] * (1.f / DM), var = fmaxf(fmaf(-mu, mu, s3[1] * (1.f / DM)), 0.f);
          const float mn = rbf(mu), iv = ln_inv(var);
          const uint32_t ky = router_key(rbf((s3[2] - mn * __uint_as_float(s_misc[M_WSUM])) * iv), grow + 8 * rr);
          const uint32_t wbest = __reduce_max_sync(0xffffffffu, ky);
          s_misc[M_KEYS + warp - 8] = wbest;
          named_bar(5, 256);
          if (__reduce_max_sync(0xffffffffu, s_misc[M_KEYS + (lane & 7)]) == wbest) {
            if (nb == 0 && ky == wbest && (q & 1) == 0) st_relaxed4(&g_slot[layer][mb * 8], make_uint4(ky, __float_as_uint(mn), __float_as_uint(iv), tag));
            const int r = ~wbest & 15;
            if ((r & 7) == g) {
#pragma unroll
              for (int j = 0; j < 4; j++) {
                const uint32_t* a = &xr[8 * j];
                st_relaxed4(&g_cand[layer][mb * 128 + nb * 16 + q * 4 + j],
                            r < 8 ? make_uint4(nosent(a[0]), nosent(a[2]), nosent(a[4]), nosent(a[6])) : make_uint4(nosent(a[1]), nosent(a[3]), nosent(a[5]), nosent(a[7])));
              }
            }
            __syncwarp();
          }
          if (warp == 9) PROF(14);
          if (layer == 0) {
            if ((q & 1) == 0) {
              g_rowln[nb][grow + 8 * rr] = make_float2(mn, iv);
              if (warp - 8 == nb) {
                const float mu2 = mu + (mu - mn) * iv, inv2 = ln_inv(var * (1.f + iv) * (1.f + iv));
                st_relaxed4(&g_rowab[1][grow + 8 * rr], make_uint4(__float_as_uint((1.f + iv) * inv2), __float_as_uint((mn * iv + rbf(mu2)) * inv2), tag, 0));
              }
            }
            __syncwarp();
          } else {
            const float mo = __shfl_xor_sync(0xffffffffu, mn, 2), io = __shfl_xor_sync(0xffffffffu, iv, 2);
            const uint32_t m0 = pack_bf16(rr ? mo : mn, rr ? mo : mn), m1 = pack_bf16(rr ? mn : mo, rr ? mn : mo);
            const float i0 = rr ? io : iv, i1 = rr ? iv : io;
#pragma unroll
            for (int j = 0; j < 8; j++)
              stsm_x4(zrow + (j >> 2) * 8192 + ((((2 * j + (mi >> 1)) & 7) ^ (srow & 7)) << 4), add_ln_pair(xr[4 * j], m0, i0),
                      add_ln_pair(xr[4 * j + 1], m1, i1), add_ln_pair(xr[4 * j + 2], m0, i0), add_ln_pair(xr[4 * j + 3], m1, i1));
            fence_async_smem();
          }
          if (warp == 15) asm volatile("bar.arrive 7, 512;" ::: "memory");
        }
        if (warp < 15) {
          uint32_t gu[64];
          mbar_wait(bar(B_GU + 1), layer);
#pragma unroll
          for (int j = 0; j < 16; j++) fetch_gu(gu + 4 * j, j, warp - 8);
          fence_async_smem();
          float d[4][4] = {};
          named_bar(7, 512);
#pragma unroll
          for (int hf = 0; hf < 2; hf++) {
            uint4 xv[4] = {};
            if (g == 0) {
#pragma unroll
              for (int j = 0; j < 4; j++) xv[j] = ((const uint4*)(smem + T_XS))[32 + hf * 16 + j * 4 + q];
            }
            __syncwarp();
#pragma unroll
            for (int j = 0; j < 4; j++) {
              const uint32_t* a = gu + hf * 32 + j * 8;
              mma_16816(d[(j & 1) * 2], a[0], a[1], a[2], a[3], xv[j].x, xv[j].y);
              mma_16816(d[(j & 1) * 2 + 1], a[4], a[5], a[6], a[7], xv[j].z, xv[j].w);
            }
          }
          send_gu((d[0][0] + d[1][0]) + (d[2][0] + d[3][0]), (d[0][2] + d[1][2]) + (d[2][2] + d[3][2]), warp - 8, 4);
          __syncwarp();
        }
        if (layer == 0) asm volatile("bar.arrive 9, 512;" ::: "memory");
        else {
        uint32_t wd[64];
        mbar_wait(bar(B_DN), layer);
#pragma unroll
        for (int j = 0; j < 16; j++) {
          const uint32_t row = sbase + ((warp - 8) * 2 + (j >> 3)) * 3584 + min((j & 1) * 16 + (mi >> 1) * 8 + (lane & 7), 27) * 128;
          ldsm_x4_t(row + ((((j & 6) + (mi & 1)) ^ ((row >> 7) & 7)) << 4), wd[4 * j], wd[4 * j + 1], wd[4 * j + 2], wd[4 * j + 3]);
        }
        fence_regs_u<64>(wd);
        uint32_t hf[4];
        if (HID_H) {
          named_bar(10, 288);
          *(uint4*)hf = *(const uint4*)(smem + OFF_PATCH + 256 + q * 16);
        } else {
          mbar_wait_cluster(bar(B_HX), layer);
          const float hv = hidden();
          const uint32_t hp2 = pack_bf16(hv, __shfl_down_sync(0xffffffffu, hv, 1));
#pragma unroll
          for (int j = 0; j < 4; j++) hf[j] = __shfl_sync(0xffffffffu, hp2, 8 * j + 2 * q);
        }
        if (warp == 9) PROF(19);
        float y[4][4] = {};
#pragma unroll
        for (int j = 0; j < 16; j++)
          mma_16816(y[j & 3], wd[4 * j], wd[4 * j + 1], wd[4 * j + 2], wd[4 * j + 3], g == j >> 1 ? hf[(j & 1) * 2] : 0u, g == j >> 1 ? hf[(j & 1) * 2 + 1] : 0u);
        {
          float e[4];
#pragma unroll
          for (int c = 0; c < 4; c++) { const int i = (c & 1) * 2 + (c >> 1); e[c] = (y[0][i] + y[1][i]) + (y[2][i] + y[3][i]); }
          const bool b0 = g & 1, b1 = g & 2;
          float t0 = __shfl_xor_sync(0xffffffffu, b0 ? e[0] : e[1], 4), t1 = __shfl_xor_sync(0xffffffffu, b0 ? e[2] : e[3], 4);
          const float f0 = b0 ? t0 : e[0], f1 = b0 ? e[1] : t0, f2 = b0 ? t1 : e[2], f3 = b0 ? e[3] : t1;
          t0 = __shfl_xor_sync(0xffffffffu, b1 ? f0 : f2, 8); t1 = __shfl_xor_sync(0xffffffffu, b1 ? f1 : f3, 8);
          st_relaxed4(&g_ypart[layer][bid * 256 + (warp - 8) * 32 + (q * 4 + (g & 3)) * 2 + (g >> 2)],
                      b1 ? make_uint4(f2u(t0), f2u(t1), f2u(f2), f2u(f3)) : make_uint4(f2u(f0), f2u(f1), f2u(t0), f2u(t1)));
        }
        if (warp == 9) PROF(20);
        asm volatile("bar.arrive 9, 384;" ::: "memory");
        cluster_arrive(); cluster_wait();
        return;
        }
      }
      const unsigned layer = pass;
      named_bar(1 + (fresh_tid() >> 7), 128);
      regs_inc<224>();
      float acc[2][96];
      {
        PHASE_IDS
        const uint32_t da0 = dlo(SOFF, 16) + (wg - 2) * 256;
        constexpr uint32_t db0 = dlo(SOFF + SL_W, 2048);
        if (warp == 9) PROF(19 - 2 * layer);
        mbar_wait(bar(B_FULL), 0);
        if (warp == 9) PROF(29);
        if (warp == 9) STEPT(0);
        wg_fence();
        wg_ss192t_z<H64, H128>(acc[0], da0, db0); wg_ss192t_z<H64, H128>(acc[1], da0 + 512, db0);
        wg_ss192t<H64, H128>(acc[0], da0 + 2, db0 + 384, 1); wg_ss192t<H64, H128>(acc[1], da0 + 514, db0 + 384, 1);
        wg_commit();
        int s = 1, u = 0;
#pragma unroll 1
        for (int i = 1; i < 32; i++) {
          const uint32_t da = da0 + s * (QE >> 4), db = db0 + s * (QE >> 4);
          mbar_wait(bar(B_FULL + s), (u + (s > 1 ? layer : 0)) & 1);
          if (warp == 9 && !(i & 1)) STEPT(i >> 1);
          wg_fence();
          wg_ss192t<H64, H128>(acc[0], da, db, 1); wg_ss192t<H64, H128>(acc[1], da + 512, db, 1);
          wg_ss192t<H64, H128>(acc[0], da + 2, db + 384, 1); wg_ss192t<H64, H128>(acc[1], da + 514, db + 384, 1);
          wg_commit();
          wg_wait<1>();
          if (lane < 2 && i < 27) mbar_arrive_cluster(bar(B_EMPTY + (s == 0 ? 5 : s - 1)), lane);
          if (++s == 6) { s = 0; u++; }
        }
      }
      PHASE_IDS
      mbar_wait(bar(B_CS), layer);
      float pa[2][2], pb[2][2];
      {
        const uint32_t tag = s_misc[M_TAG];
        const uint4* src = &g_rowab[layer][rb * 256 + (wg - 2 + (lane >> 4) * 2) * 64 + wi * 16 + (lane & 15)];
        uint4 v;
        uint32_t spins = 0;
#pragma unroll 1
        do { v = ld_relaxed4(src); } while (!__all_sync(0xffffffffu, v.z == tag) && ++spins < SPIN_LIMIT);
#pragma unroll
        for (int j = 0; j < 4; j++) {
          pa[j >> 1][j & 1] = __uint_as_float(__shfl_sync(0xffffffffu, v.x, g + 8 * j));
          pb[j >> 1][j & 1] = __uint_as_float(__shfl_sync(0xffffffffu, v.y, g + 8 * j));
        }
      }
      const int prow = (int)s_misc[M_SEL0] - rb * 256;
      const bool patch = ((prow - (wg - 2) * 64 - wi * 16) & ~0x8F) == 0;
      const float* cs = (const float*)(smem + OFF_CS);
      auto finish = [&](int m, int b, float2 c, uint32_t* dst) {
        dst[0] = pack_bf16(acc[m][4 * b] * pa[m][0] - c.x * pb[m][0], acc[m][4 * b + 1] * pa[m][0] - c.y * pb[m][0]);
        dst[1] = pack_bf16(acc[m][4 * b + 2] * pa[m][1] - c.x * pb[m][1], acc[m][4 * b + 3] * pa[m][1] - c.y * pb[m][1]);
      };
      wg_wait<0>();
      fence_regs<96>(acc[0]); fence_regs<96>(acc[1]);
      if (warp != 9) STEPT(1);
      if (lane < 2) mbar_arrive_cluster(bar(B_QDONE), lane);
      if (warp == 9) PROF(2);
#pragma unroll
      for (int h = 0; h < 2; h++) {
        const uint32_t dst = sbase + (h * 8 + 2 + wg) * 8192 + srow * 64;
#pragma unroll
        for (int jj = 0; jj < 4; jj++) {
          const int b = 8 + (jj >> 1) * 8 + h * 4 + (jj & 1) * 2;
          const float2 c0 = *(const float2*)&cs[8 * b + 2 * q], c1 = *(const float2*)&cs[8 * b + 8 + 2 * q];
          uint32_t r[2][4];
#pragma unroll
          for (int m = 0; m < 2; m++) { finish(m, b, c0, r[m]); finish(m, b + 1, c1, r[m] + 2); }
          if (h == 0 && jj == 0) named_bar(5, 256);
#pragma unroll
          for (int m = 0; m < 2; m++)
            stsm_x4(dst + m * 16384 + (jj >> 1) * 4096 + ((((jj & 1) * 2 + (mi >> 1)) ^ ((srow >> 1) & 3)) << 4), r[m][0], r[m][1], r[m][2], r[m][3]);
        }
        if (patch) {
          __syncwarp();
          if (lane < 8)
            *(uint4*)(smem + (h * 8 + 4 + (prow >> 6)) * 8192 + g * 4096 + (prow & 63) * 64 + ((q ^ ((prow >> 1) & 3)) << 4)) =
                *(const uint4*)(smem + OFF_PATCH + 128 + g * 128 + h * 64 + q * 16);
        }
        fence_async_smem();
        __syncwarp();
        mbar_arrive_e(bar(B_KVREADY + h));
        if (warp != 9) STEPT(2 + h);
      }
#pragma unroll
      for (int j = 0; j < 4; j++) { pa[j >> 1][j & 1] *= SM_C; pb[j >> 1][j & 1] *= SM_C; }
#pragma unroll
      for (int jj = 0; jj < 4; jj++) {
        const float2 c0 = *(const float2*)&cs[16 * jj + 2 * q], c1 = *(const float2*)&cs[16 * jj + 8 + 2 * q];
#pragma unroll
        for (int m = 0; m < 2; m++) {
          uint32_t r[4];
          finish(m, 2 * jj, c0, r); finish(m, 2 * jj + 1, c1, r + 2);
          *(uint4*)(smem + AT_ST + ((jj >> 1) * 16 + warp - 8 + 8 * m) * 1024 + (jj & 1) * 512 + lane * 16) = make_uint4(r[0], r[1], r[2], r[3]);
        }
      }
      __syncwarp();
      if (patch) {
        *(uint32_t*)(smem + AT_ST + ((lane >> 4) * 16 + (prow >> 4)) * 1024 + (mi & 1) * 512 + ((prow & 7) * 4 + q) * 16 + ((g & 1) * 2 + ((prow >> 3) & 1)) * 4) =
            *(const uint32_t*)(smem + OFF_PATCH + lane * 4);
        __syncwarp();
      }
      if (warp == 9) PROF(3);
      mbar_arrive_e(bar(B_QREADY));
      regs_dec<120>();
    } else {
      if (pass > 0) {
        const unsigned layer = pass - 1;
        PHASE_IDS
        const uint32_t tag = s_misc[M_TAG];
        if (warp == 7) {
              uint32_t* tab = (uint32_t*)(smem + OFF_PATCH);
#pragma unroll
              for (int j = 0; j < 2; j++) { const int w = lane + 32 * j; tab[(w & 3) * 16 + (w >> 2)] = ((const uint32_t*)P.w_r)[nb * 64 + w]; }
              tab[64 + lane] = lane < 16 ? 0x3F803F80u : 0u;
              float tot = 0.f;
#pragma unroll
              for (int j = 0; j < 4; j++) {
                const uint4 u = ((const uint4*)P.w_r)[lane + 32 * j];
                tot += bf_lo(u.x) + bf_hi(u.x) + bf_lo(u.y) + bf_hi(u.y) + bf_lo(u.z) + bf_hi(u.z) + bf_lo(u.w) + bf_hi(u.w);
              }
              s_misc[M_WSUM] = __float_as_uint(warp_sum(tot));
        }
              if (layer == 1) {
                const float2 ln = g_rowln[nb][mb * 128 + tid - 128];
                const uint32_t m2 = pack_bf16(ln.x, ln.x);
                uint8_t* row = smem + AT_ST + (wi >> 1) * 16384 + (tid & 63) * 128;
                mbar_wait(bar(B_RES), 1);
#pragma unroll 1
                for (int j = 0; j < 8; j++) {
                  uint4* c = (uint4*)(row + (((j + lane) & 7) << 4));
                  const uint4 v = c[0], w = c[512];
                  c[0] = make_uint4(add_ln_pair(v.x, m2, ln.y), add_ln_pair(v.y, m2, ln.y), add_ln_pair(v.z, m2, ln.y), add_ln_pair(v.w, m2, ln.y));
                  c[512] = make_uint4(add_ln_pair(w.x, m2, ln.y), add_ln_pair(w.y, m2, ln.y), add_ln_pair(w.z, m2, ln.y), add_ln_pair(w.w, m2, ln.y));
                }
                const int prow = (int)s_misc[M_SEL0] - mb * 128;
                __syncwarp();
                if (prow >> 5 == wi && lane < 16)
                  *(uint4*)(smem + AT_ST + (prow >> 6) * 16384 + (lane >> 3) * 8192 + (prow & 63) * 128 + (((lane ^ prow) & 7) << 4)) = poll4(&g_x2row[(nb * 16 + lane) * 2]);
                PROF(30);
              }
              __syncwarp();
              mbar_arrive_e(bar(B_RST));
        if (warp == 4) {
            named_bar(6, 320);
            spin_cycles(DELAY_S);
            uint4 c, u0, u1;
            uint32_t u2, best = 0, spins = 0;
            int src;
#pragma unroll 1
            for (;;) {
              src = (~best & 0x7FFu) >> 7;
              const uint4* xsel = &g_cand[layer][src * 128];
              c = ld_relaxed4(&g_slot[layer][(lane & 15) * 8]);
              u0 = ld_relaxed4(xsel + rank * 64 + lane); u1 = ld_relaxed4(xsel + rank * 64 + 32 + lane);
              u2 = ld_relaxed((const uint32_t*)(xsel + (bid >> 4) * 16 + q * 4) + (bid & 15));
              const uint32_t prev = best;
              best = __reduce_max_sync(0xffffffffu, c.w == tag ? c.x : 0u);
              if ((__all_sync(0xffffffffu, c.w == tag && valid4(u0) && valid4(u1) && u2 != SENT) && best == prev) || ++spins > SPIN_LIMIT) break;
            }
            const float sel_m = __uint_as_float(__shfl_sync(0xffffffffu, c.y, src)), sel_inv = __uint_as_float(__shfl_sync(0xffffffffu, c.z, src));
            const uint32_t m2 = pack_bf16(sel_m, sel_m);
            uint4* xs = (uint4*)(smem + T_XS) + (lane & 16) + q * 4 + (g & 3);
            xs[0] = make_uint4(ln_pair(u0.x, m2, sel_inv), ln_pair(u0.y, m2, sel_inv), ln_pair(u0.z, m2, sel_inv), ln_pair(u0.w, m2, sel_inv));
            xs[32] = make_uint4(ln_pair(u1.x, m2, sel_inv), ln_pair(u1.y, m2, sel_inv), ln_pair(u1.z, m2, sel_inv), ln_pair(u1.w, m2, sel_inv));
            s_misc[M_KEY] = best; s_misc[M_MEAN] = __float_as_uint(sel_m); s_misc[M_INV] = __float_as_uint(sel_inv);
            s_misc[M_XQ + q] = u2;
            PROF(16);
        }
        if (layer == 1) {
          named_bar(7, 512);
          const int sel = SEQ - 1 - (int)(s_misc[M_KEY] & 0x7FFFu), skip = sel >> 7 == mb ? (sel >> 6) & 1 : -1;
          if (warp == 7) store_tile(1, skip, false);
          if (HID_H && warp == 4) {
            mbar_wait_cluster(bar(B_HX), 1);
            ((bf16*)(smem + OFF_PATCH + 256))[((lane >> 1) & 3) * 8 + (lane >> 3) * 2 + (lane & 1)] = __float2bfloat16_rn(hidden());
            asm volatile("bar.arrive 10, 288;" ::: "memory");
          }
#pragma unroll 1
          for (int c = tid - 128; c < 1024 && skip >= 0; c += 128) {
            const int r = c >> 4;
            if (r != (sel & 63))
              *(uint4*)(P.out + (size_t)(mb * 128 + skip * 64 + r) * DM + nb * 128 + (c & 15) * 8) =
                  *(const uint4*)(smem + AT_ST + skip * 16384 + ((c >> 3) & 1) * 8192 + r * 128 + (((c ^ r) & 7) << 4));
          }
          __syncwarp();
        } else asm volatile("bar.arrive 7, 512;" ::: "memory");
        if (warp == 5 && layer == 0) {
              named_bar(8, 288);
              if (nb > 0) spin_cycles(X_STAGGER);
              store_tile(0, -1, true);
              set_flag(&g_xflag[mb][nb].v[0], tag);
              PROF(17);
              poll_flag(&g_xflag[2 * rb + (lane & 1)][0].v[0], tag);
              fence_async_global();
#pragma unroll 1
              for (int i = 0; i < 4; i++) load_a(i, i, 1);
              PROFL(1, 1);
        }
      }
      named_bar(1 + (fresh_tid() >> 7), 128);
      regs_dec<32>();
#pragma unroll 1
      for (;;) {
      const unsigned pass = __shfl_sync(0xffffffffu, pass_v, 0);
      if (pass > 0) {
        const unsigned layer = pass - 1;
        PHASE_IDS
        const uint32_t tag = s_misc[M_TAG], bkey = s_misc[M_KEY];
        const int sel = SEQ - 1 - (int)(bkey & 0x7FFFu);
        if (warp == 3) {
          if (layer == 1) {
#pragma unroll
            for (int j = 0; j < 3; j++) ((uint4*)g_vw)[bid * 96 + j * 32 + lane] = make_uint4(0, 0, 0, 0);
          } else s_misc[M_SEL0] = sel;
          if (bid == 0 && lane == 0) g_sel[layer] = sel;
        }
        __syncwarp();
        if (layer == 0) {
          auto load_down = [&](int j) {
            mbar_expect_tx(bar(B_DN + j), 2 * FFN_PIECE);
            bulk_load_h(sbase + SL_F + j * 2 * FFN_PIECE, P.w_d + (size_t)(bid * 28 + j * 14) * DM, 2 * FFN_PIECE, bar(B_DN + j), policy_evict_first());
          };
          if (warp == 5) {
            poll_flag(&g_xflag[2 * rb + (lane & 1)][(lane >> 1) & 7].v[0], tag);
            fence_async_global();
            load_a(4, 4, 1); load_a(5, 5, 1);
          }
          float hv = 0.f;
          if (wg == 1) { mbar_wait_cluster(bar(B_HX), 0); hv = rbf(hidden()); fence_regs<1>(&hv); }
          named_bar(9, 512);
          if (warp == 0) {
            fence_async_smem();
            if (lane < 16) mbar_arrive_cluster(bar(B_QFREE), lane & 1);
            mbar_wait(bar(B_QFREE), 1);
            load_w(4, 4); load_w(5, 5);
            load_down(0);
          } else if (wg == 1) {
            if (warp == 4) { mbar_wait(bar(B_DN), 0); load_down(1); }
            float d[8] = {0.f, 0.f, 0.f, 0.f, 0.f, 0.f, 0.f, 0.f};
#pragma unroll 1
            for (int j = 0; j < 28; j += 2) {
              if (j == 0 || j == 14) mbar_wait(bar(B_DN + (j > 0)), 0);
              const uint4 w0 = *(const uint4*)(smem + SL_F + j * 2048 + (tid - 128) * 16), w1 = *(const uint4*)(smem + SL_F + j * 2048 + 2048 + (tid - 128) * 16);
              fma8(d, w0, __shfl_sync(0xffffffffu, hv, j));
              fma8(d, w1, __shfl_sync(0xffffffffu, hv, j + 1));
            }
            uint4* dst = &g_ypart[0][bid * 256 + (tid - 128) * 2];
            st_relaxed4(dst, make_uint4(f2u(d[0]), f2u(d[1]), f2u(d[2]), f2u(d[3])));
            st_relaxed4(dst + 1, make_uint4(f2u(d[4]), f2u(d[5]), f2u(d[6]), f2u(d[7])));
            asm volatile("bar.arrive 11, 160;" ::: "memory");
            PROF(20);
          } else if (warp == 2) {
            named_bar(11, 160);
            fence_async_smem();
            load_ws(WS1_PACE);
          }
        } else {
          if (wg == 1) named_bar(9, 384);
          cluster_arrive();
        }
        if (wg == 1) {
          const int t_y = (int)clock();
          const uint32_t xw = s_misc[M_XQ + ((lane & 7) >> 1)];
          const float x = (lane & 1) ? bf_hi(xw) : bf_lo(xw);
          float xn = rbf(rbf(x - __uint_as_float(s_misc[M_MEAN])) * __uint_as_float(s_misc[M_INV]));
          uint32_t u = bkey & 0xFFFF0000u;
          u = (u & 0x80000000u) ? (u & 0x7FFFFFFFu) : (~u & 0xFFFF0000u);
          float sg = rbf(__fdividef(1.f, 1.f + __expf(-__uint_as_float(u))));
          uint32_t* dst = (layer == 0 ? (uint32_t*)&g_x2row[bid * 2] : (uint32_t*)(P.out + (size_t)sel * DM + bid * 8)) + (lane >> 1);
          asm volatile("" : "+f"(xn), "+f"(sg), "+l"(dst));
#pragma unroll 1
          while ((int)clock() - t_y < DELAY_Y) {}
          const uint4* src = &g_ypart[layer][((tid - 128) >> 1) * 256 + bid * 2 + (tid & 1)];
          uint4 v, w;
          uint32_t spins = 0;
#pragma unroll 1
          do { v = ld_relaxed4(src); w = ld_relaxed4(src + 64 * 256); } while (!__all_sync(0xffffffffu, valid4(v) && valid4(w)) && ++spins < SPIN_LIMIT);
          float a[4] = {__uint_as_float(v.x) + __uint_as_float(w.x), __uint_as_float(v.y) + __uint_as_float(w.y),
                        __uint_as_float(v.z) + __uint_as_float(w.z), __uint_as_float(v.w) + __uint_as_float(w.w)};
          const bool b1 = lane & 2, b2 = lane & 4;
          float c0 = (b1 ? a[1] : a[0]) + __shfl_xor_sync(0xffffffffu, b1 ? a[0] : a[1], 2);
          float c1 = (b1 ? a[3] : a[2]) + __shfl_xor_sync(0xffffffffu, b1 ? a[2] : a[3], 2);
          float y = (b2 ? c1 : c0) + __shfl_xor_sync(0xffffffffu, b2 ? c0 : c1, 4);
          y += __shfl_xor_sync(0xffffffffu, y, 8);
          y += __shfl_xor_sync(0xffffffffu, y, 16);
          float* red = (float*)(smem + OFF_PATCH);
          red[wi * 8 + (lane & 1) * 4 + ((lane >> 1) & 3)] = y;
          named_bar(2, 128);
          if (warp == 4) {
            PROF(21);
            y = (red[lane & 7] + red[8 + (lane & 7)]) + (red[16 + (lane & 7)] + red[24 + (lane & 7)]);
            const float res = x + rbf(xn + rbf(rbf(y) * sg));
            const uint32_t pr = nosent(pack_bf16(res, __shfl_down_sync(0xffffffffu, res, 1)));
            if (lane < 8 && (lane & 1) == 0) st_relaxed(dst, pr);
            PROF(22);
          }
        }
        if (pass == 2) {
          if (bid == 0 && tid == 128) g_epoch = tag;
          bulk_wait_all();
          __syncwarp();
          cluster_wait();
          return;
        }
      }
      const unsigned layer = pass;
      if (__shfl_sync(0xffffffffu, fresh_tid() >> 5, 0) > 1 - (int)layer) {
        PHASE_IDS
        uint4* xrow = (uint4*)(smem + SL_F + 4 * SL_HD);
        if (wg == 1) {
          if (layer == 0) {
            xrow[tid - 128] = make_uint4(0x3F803F80u, 0x3F803F80u, 0x3F803F80u, 0x3F803F80u);
            if (warp == 5) {
              mbar_wait(bar(B_FULL + WS_AT), 0);
              if (lane == 0) {
#pragma unroll 1
                for (int i = 11; i > 0; i--) prefetch_tmap(&P.mapA[0] + i);
              }
              __syncwarp();
              load_ws(WS_PACE);
            }
          } else xrow[tid - 128] = poll4(&g_x2row[(tid - 128) * 2]);
          PROF(23);
        }
        named_bar(12, 192 + 32 * layer);
        if (warp == 1) {
          float mean = 0.f;
#pragma unroll 1
          for (int pass2 = 0; pass2 < 2; pass2++) {
            float acc = 0.f;
#pragma unroll 1
            for (int j = lane; j < 128; j += 32) {
              const uint4 v = xrow[j];
              const uint32_t w[4] = {v.x, v.y, v.z, v.w};
#pragma unroll
              for (int c = 0; c < 4; c++) {
                const float d0 = bf_lo(w[c]) - mean, d1 = bf_hi(w[c]) - mean;
                acc += pass2 ? d0 * d0 + d1 * d1 : d0 + d1;
              }
            }
            acc = warp_sum(acc) * (1.f / DM);
            if (pass2 == 0) mean = acc;
            else { s_misc[M_PMEAN] = __float_as_uint(rbf(mean)); s_misc[M_PINV] = __float_as_uint(ln_inv(acc)); }
          }
        } else {
          mbar_wait(bar(B_WS), layer);
          const uint8_t* wa = smem + SL_F + (g >> 1) * SL_HD + ((warp - 2) >> 1) * 4096 + (g & 1) * 2048;
          const uint32_t* xs = (const uint32_t*)xrow + rb * 64 + g * 8;
          const int ch = (warp & 1) * 4 + q;
          float d[8] = {0.f, 0.f, 0.f, 0.f, 0.f, 0.f, 0.f, 0.f};
#pragma unroll 1
          for (int j0 = 0; j0 < 16; j0 += 2) {
            const int j = j0 ^ ((g & 1) * 4);
            const uint4 w0 = *(const uint4*)(wa + j * 128 + (((ch ^ j) & 7) << 4)), w1 = *(const uint4*)(wa + j * 128 + 128 + (((ch ^ (j + 1)) & 7) << 4));
            const uint32_t xx = xs[j >> 1];
            fma8(d, w0, bf_lo(xx)); fma8(d, w1, bf_hi(xx));
          }
#pragma unroll
          for (int c = 0; c < 4; c++) d[c] = ((g & 4) ? d[c + 4] : d[c]) + __shfl_xor_sync(0xffffffffu, (g & 4) ? d[c] : d[c + 4], 16);
#pragma unroll
          for (int c = 0; c < 2; c++) d[c] = ((g & 2) ? d[c + 2] : d[c]) + __shfl_xor_sync(0xffffffffu, (g & 2) ? d[c] : d[c + 2], 8);
          d[0] = ((g & 1) ? d[1] : d[0]) + __shfl_xor_sync(0xffffffffu, (g & 1) ? d[0] : d[1], 4);
          st_relaxed(&g_vw[layer][rb][((warp - 2) >> 1) * DM + hp * 64 + ch * 8 + g], enc(d[0]));
        }
        named_bar(12, 192 + 32 * layer);
        PROF(24);
      }
      PHASE_IDS
      if (wg == 0) {
        if (warp == 0) {
          if (layer == 0) {
#pragma unroll 1
            for (int i = PRE_N; i < 6; i++) { load_a(i, i, 0); load_w(i, i); }
          }
          int s = 0, u = 0;
#pragma unroll 1
          for (int i = 6; i < 32; i++) {
            if (layer == 1) mbar_arrive_e(bar(B_EMPTY + s));
            mbar_wait(bar(B_EMPTY + s), (u + (s > 1 ? 0 : layer)) & 1);
            load_w(s, i);
            load_a(s, i, layer);
            if (++s == 6) { s = 0; u++; }
          }
        } else if (warp == 1) {
          if (layer == 0) {
            const uint32_t tag = ld_relaxed(&g_epoch) + 1;
            if (lane < 16) g_rowab[0][rb * 256 + hp * 16 + lane] = make_uint4(0, 0, 0, 0);
            float shift = 0.f, sum = 0.f, sq = 0.f;
            const int r = hp * 16 + (lane >> 1);
#pragma unroll 1
            for (int i = 0; i < 32; i++) {
              mbar_wait(bar(B_FULL + i % 6), (i / 6) & 1);
              const uint8_t* base = smem + (i % 6) * QE + r * 64 + (lane & 1) * 32;
              uint4 v[2];
#pragma unroll
              for (int j = 0; j < 2; j++) v[j] = *(const uint4*)(base + ((j ^ ((r >> 1) & 1)) << 4));
              if (i == 0) shift = __shfl_sync(0xffffffffu, bf_lo(v[0].x), lane & ~1);
#pragma unroll
              for (int j = 0; j < 2; j++) {
                const uint32_t w[4] = {v[j].x, v[j].y, v[j].z, v[j].w};
#pragma unroll
                for (int c = 0; c < 4; c++) {
                  const float d0 = bf_lo(w[c]) - shift, d1 = bf_hi(w[c]) - shift;
                  sum += d0 + d1; sq = fmaf(d0, d0, fmaf(d1, d1, sq));
                }
              }
              fence_async_smem();
              __syncwarp();
              if (i < 26) mbar_arrive_e(bar(B_EMPTY + i % 6));
            }
            sum += __shfl_xor_sync(0xffffffffu, sum, 1); sq += __shfl_xor_sync(0xffffffffu, sq, 1);
            const float dm = sum * (1.f / DM), var = fmaxf(sq * (1.f / DM) - dm * dm, 0.f), mean = shift + dm;
            const float inv = ln_inv(var);
            if ((lane & 1) == 0) st_relaxed4(&g_rowab[0][rb * 256 + r], make_uint4(__float_as_uint(inv), __float_as_uint(rbf(mean) * inv), tag, 0));
          }
          if (rb == 0) {
            mbar_wait(bar(B_QDONE), layer);
#pragma unroll 1
            for (int j = lane; j < 512; j += 32) ((uint4*)(smem + 65536))[j] = make_uint4(0, 0, 0, 0);
            fence_async_smem();
            __syncwarp();
            if (lane < 3) mbar_arrive(bar(B_HALO + lane));
          }
        } else if (warp == 3) {
          fence_async_smem();
          load_gu(0, layer ? GU_PACE1 : GU_PACE);
          PROF(27);
        } else {
          const uint4 sent = make_uint4(SENT, SENT, SENT, SENT), zero = make_uint4(0, 0, 0, 0);
          if (layer == 0) {
            const int f = lane >> 1;
            Flag* fl = f < 2 ? &g_kvflag[rb >> 1][hp][f] : f < 4 ? &g_oflag[rb][f & 1][hp] : &g_xflag[mb][nb];
            if (f < 5 && (f >= 2 || (rank == 1 && rb < 7))) ((uint4*)fl)[lane & 1] = zero;
          }
#pragma unroll 1
          for (int t = lane; t < 128; t += 32) {
            g_ypart[layer][bid * 256 + t] = sent; g_ypart[layer][bid * 256 + 128 + t] = sent;
            g_part[layer][nb * SEQ + mb * 128 + t] = zero;
            if (t < 16) g_cand[layer][mb * 128 + nb * 16 + t] = sent;
            else if (t < 18) { if (nb == 0) g_slot[layer][mb * 8 + t - 16] = zero; }
            else if (t < 20) { if (layer == 0) g_x2row[bid * 2 + t - 18] = sent; }
          }
          __syncwarp();
          mbar_arrive_e(bar(B_CS));
        }
        __syncwarp();
        if (rank == 0) {
          if (warp == 0) {
            mbar_wait(bar(B_QDONE), layer);
#pragma unroll 1
            for (int j = 0; j < 3; j++) {
              const int o = j == 0 ? 16384 : (j == 1 ? 0 : 65536);
              mbar_wait(bar(B_KVREADY + (j >> 1)), layer);
              bulk_push(mapa(sbase + o, 1), sbase + 32768 + o, j == 2 ? 32768 : 16384, mapa(bar(B_HALO + j), 1));
            }
          } else if (warp < 3 && rb > 0) {
            mbar_wait(bar(B_QREADY), layer);
            if (warp == 2) spin_cycles(1000);
            import_halo(layer, warp - 1);
            if (warp == 1) PROF(5);
          }
        } else if (warp == 2) {
          mbar_expect_tx(bar(B_HALO), 16384); mbar_expect_tx(bar(B_HALO + 1), 16384); mbar_expect_tx(bar(B_HALO + 2), 32768);
        } else if (warp < 2 && rb < 7) {
          mbar_wait(bar(B_KVREADY + warp), layer);
          if (warp == 1) named_bar(13, 64);
          bulk_store(g_kv + (size_t)((rb >> 1) * 16 + hp) * 65536 + warp * 32768, sbase + 32768 + warp * 65536, 32768);
          bulk_commit();
          bulk_wait_all();
          if (warp == 0) asm volatile("bar.arrive 13, 64;" ::: "memory");
          set_flag(&g_kvflag[rb >> 1][hp][warp].v[layer], s_misc[M_TAG]);
          if (warp == 0) PROF(4);
        }
      } else {
        const int t = tid - 128, go = (t >> 5) * DM + hp * 64 + (t & 31) * 2;
        if (layer == 0 && t == 96) { s_misc[M_TAG] = ld_relaxed(&g_epoch) + 1; s_misc[M_SEL0] = 0xFFFFFFFFu; s_misc[M_PROG] = s_misc[M_PROG + 1] = 0; }
        if ((layer == 0 || (int)s_misc[M_SEL0] >> 8 == rb) && warp < 7) {
          spin_cycles(layer ? 300 : 1500);
          uint2 w[8];
          uint32_t spins = 0;
          bool ok;
#pragma unroll 1
          do {
            ok = true;
#pragma unroll
            for (int j = 0; j < 8; j++) w[j] = ld_relaxed2(&g_vw[layer][j][go]);
#pragma unroll
            for (int j = 0; j < 8; j++) ok = ok && w[j].x && w[j].y;
          } while (!__all_sync(0xffffffffu, ok) && ++spins < SPIN_LIMIT);
          float s0 = 0.f, s1 = 0.f;
#pragma unroll
          for (int j = 0; j < 8; j++) { s0 += dec(w[j].x); s1 += dec(w[j].y); }
          if (layer == 0) ((float2*)(smem + OFF_CS))[t] = make_float2(s0, s1);
          else {
            const float2 c = ((const float2*)(smem + OFF_CS))[t];
            const float a = __uint_as_float(s_misc[M_PINV]) * (warp == 4 ? SM_C : 1.f), b = __uint_as_float(s_misc[M_PMEAN]) * a;
            ((uint32_t*)(smem + OFF_PATCH))[t] = pack_bf16(s0 * a - c.x * b, s1 * a - c.y * b);
          }
          PROF(25);
        }
        __syncwarp();
        mbar_arrive_e(bar(B_CS));
      }
      __syncwarp();
      if (wi == 0) mbar_wait(bar(B_QREADY), layer);
      named_bar(1 + (fresh_tid() >> 7), 128);
      if (__shfl_sync(0xffffffffu, fresh_tid() >> 7, 0) == 0) {
        regs_inc<152>();
        uint32_t gu[112];
        {
          PHASE_IDS
          const uint32_t tag = s_misc[M_TAG];
          mbar_wait(bar(B_GU), layer);
#pragma unroll
          for (int j = 0; j < 28; j++) fetch_gu(gu + 4 * j, warp * 4 + (j & 3), j >> 2);
          fence_async_smem();
          named_bar(1, 128);
          if (warp == 0) {
            mbar_wait(bar(B_ADONE), layer);
#pragma unroll 1
            for (int k = 2; k < 16; k++) {
#pragma unroll 1
              for (uint32_t spins = 0; (int)s_misc[M_PROG + (k >> 3)] <= (k & 7) + 16 * (int)layer && spins < SPIN_LIMIT; spins++) {}
              if (k >= 4) mbar_wait(bar(B_WEMPTY + (k & 3)), ((k >> 2) - 1 + ((k & 2) ? layer : 0)) & 1);
              load_o(k); load_wo(k);
              STEPT(16 + k);
              if (k == RES_K) { mbar_wait(bar(B_OST + 1), layer); load_res(1, layer); }
            }
            if (layer == 1) {
              mbar_wait(bar(B_WEMPTY + 1), 1);
              if (FAKE & 2) mbar_arrive_e(bar(B_DN)); else mbar_expect_tx(bar(B_DN), 4 * FFN_PIECE);
              if (!(FAKE & 2)) tma_load3_h(sbase, &P.mapD, 0, bid * 28, 0, bar(B_DN), policy_evict_first());
              if (D_SPLIT == 0) tma_load3_h(sbase + 2 * FFN_PIECE, &P.mapD, 0, bid * 28, 8, bar(B_DN), policy_evict_first());
            }
            named_bar(6, 320);
            if (layer == 0) {
              mbar_wait(bar(B_QFREE), 0);
#pragma unroll 1
              for (int i = 0; i < 4; i++) load_w(i, i);
            } else if (D_SPLIT == 1 && !(FAKE & 2)) tma_load3_h(sbase + 2 * FFN_PIECE, &P.mapD, 0, bid * 28, 8, bar(B_DN), policy_evict_first());
          } else if (warp < 3) {
            const int h = warp - 1;
#pragma unroll 1
            for (int qb = 3; qb >= 0; qb--) {
              mbar_wait(bar(B_UNIT + h * 4 + 3 - qb), layer);
              bulk_store(g_o + (size_t)((((rb * 2 + (qb >> 1)) * 2 + h) * 16 + hp) * 2 + (qb & 1)) * 4096, sbase + AT_ST + (h * 4 + qb) * 4096, 4096);
            }
            bulk_commit();
            if (h == 0 && lane < 2) mbar_arrive_cluster(bar(B_OST), lane);
            bulk_wait_all();
            if (h == 1) mbar_arrive_e(bar(B_OST + 1));
            set_flag(&g_oflag[rb][h][hp].v[layer], tag);
            PROF(28 + 3 * h);
            if (h == 0) { load_res(0, layer); mbar_wait(bar(B_OST), layer); load_wo(0); load_wo(1); }
            int n = 0, first = h;
#pragma unroll 1
            for (uint32_t spins = 0; n < 8 && spins < SPIN_LIMIT; spins++) {
              n = (__ffs(__ballot_sync(0xffffffffu, ld_relaxed(&g_oflag[rb][h][lane & 15].v[layer]) != tag || lane == 16)) - 1) >> 1;
              asm volatile("fence.acquire.gpu;" ::: "memory");
              fence_async_global();
              if (!first && n >= 2) {
                first = 1;
                load_o(0); load_o(1);
                PROF(15);
              }
              s_misc[M_PROG + h] = n + 16 * layer;
            }
            if (h) PROF(26);
          } else {
            mbar_expect_tx(bar(B_HX), 2240);
            mbar_wait(bar(B_HALO + 2), layer);
            if (rb == 0) spin_cycles(2000);
            PROF(6);
            load_gu(1, GUB_PACE);
          }
        }
        PHASE_IDS
        uint4 xa = {}, xb = {};
        named_bar(7, 512);
        if (g == 0) { xa = ((const uint4*)(smem + T_XS))[warp * 8 + q]; xb = ((const uint4*)(smem + T_XS))[warp * 8 + 4 + q]; }
        __syncwarp();
        float d[7][4] = {};
#pragma unroll
        for (int j = 0; j < 28; j++) {
          const int ks = j / 7, ct = j % 7;
          const uint32_t* a = gu + ct * 16 + ks * 4;
          mma_16816(d[ct], a[0], a[1], a[2], a[3], ks == 0 ? xa.x : ks == 1 ? xa.z : ks == 2 ? xb.x : xb.z, ks == 0 ? xa.y : ks == 1 ? xa.w : ks == 2 ? xb.y : xb.w);
        }
#pragma unroll
        for (int ct = 0; ct < 7; ct++) send_gu(d[ct][0], d[ct][2], ct, warp);
        __syncwarp();
        if (warp == 2) PROF(18);
        regs_dec<32>();
        pass_v = pass + 1;
        continue;
      }
      break;
      }
      regs_inc<120>();
    }
    const unsigned layer = pass;
    {
      PHASE_IDS
      mbar_wait(bar(B_QREADY), layer);
      if (warp != 9) STEPT(7);
      auto kdesc = [&](int h, int b) { return dlo(SOFF, 16) + (rb == 0 && b < 4 ? 4096 : h * 4096 + b * 512); };
      auto vdesc = [&](int h, int b) { return rb == 0 && b < 4 ? dlo(SOFF + 65536, 4096) : dlo(SOFF + 4096, OFF_ONES - 4096) + (h * 8 + b) * 8 * VSTEP; };
      const int units = wg == 3 ? 0x8630 : (wg == 2 ? ULIST2 : ULIST1);
      auto need = [&](int h, int b) { if (b == 3 || b == 1) mbar_wait(bar(B_HALO + (h ? 2 : b == 1)), layer); };
      auto load_q = [&](uint32_t* qf, int u) {
        *(uint4*)&qf[0] = *(const uint4*)(smem + AT_ST + ((u ^ 3) * 4 + wi) * 1024 + lane * 16);
        *(uint4*)&qf[4] = *(const uint4*)(smem + AT_ST + ((u ^ 3) * 4 + wi) * 1024 + 512 + lane * 16);
      };
      auto store_o = [&](const float* o, int u) {
        const float i0 = rcp(o[16]), i1 = rcp(o[18]);
        const int v = u ^ 3;
        if (u >= 4 && lane < 2) mbar_arrive_cluster(bar(B_ADONE), lane);
#pragma unroll
        for (int j = 0; j < 2; j++)
          stsm_x4(sbase + AT_ST + v * 4096 + srow * 64 + (((2 * j + (mi >> 1)) ^ ((srow >> 1) & 3)) << 4),
                  pack_bf16(o[8 * j] * i0, o[8 * j + 1] * i0), pack_bf16(o[8 * j + 2] * i1, o[8 * j + 3] * i1),
                  pack_bf16(o[8 * j + 4] * i0, o[8 * j + 5] * i0), pack_bf16(o[8 * j + 6] * i1, o[8 * j + 7] * i1));
        fence_async_smem();
        __syncwarp();
        mbar_arrive_e(bar(B_UNIT + u));
      };
      int redo = 0;
      {
        const int dl = g - 2 * q;
        const uint32_t mt = shl_clamp(0xFFFFFFFFu, max(16 * dl + 16, 0));
        uint32_t qf[8];
        float s[32];
        load_q(qf, units & 7);
        wg_fence();
        qk64(s, qf, kdesc((units >> 2) & 1, 6 - (units & 3)));
        wg_commit();
        wg_wait<0>();
        fence_regs<32>(s);
#pragma unroll 1
        for (int ul = units; ul != 8; ul >>= 4) {
          const int u = ul & 7, h = u >> 2, qb = 3 - (u & 3);
          float o[20];
          uint32_t p1[16], p2[16], p3[16], p4[16], p5[16];
          if (warp != 9) STEPT(8 + nu * 8);
          exp_pack<8>(s, p1);
          fence_regs_u<16>(p1);
          need(h, qb + 2);
          {
            float s2[32];
            const uint32_t vd = vdesc(h, qb + 3);
            wg_fence();
            qk64(s2, qf, kdesc(h, qb + 2));
            wg_commit();
            wg_rs40t_z<H64>(o, p1[0], p1[1], p1[2], p1[3], vd);
            wg_rs40t<H64>(o, p1[4], p1[5], p1[6], p1[7], vd + VSTEP, 1);
            pv32(o, p1 + 8, vd + 2 * VSTEP);
            wg_commit();
            wg_wait<1>();
            fence_regs<32>(s2);
            if (warp != 9) STEPT(9 + nu * 8);
            exp_pack<8>(s2, p2);
            fence_regs_u<16>(p2);
            wg_wait<0>();
            fence_regs<20>(o);
          }
          need(h, qb + 1);
          {
            float s3[32];
            wg_fence();
            qk64(s3, qf, kdesc(h, qb + 1));
            wg_commit();
            pv32(o, p2, vdesc(h, qb + 2)); pv32(o, p2 + 8, vdesc(h, qb + 2) + 2 * VSTEP);
            wg_commit();
            wg_wait<1>();
            fence_regs<32>(s3);
            if (warp != 9) STEPT(10 + nu * 8);
            exp_pack<8>(s3, p3);
            fence_regs_u<16>(p3);
            wg_wait<0>();
            fence_regs<20>(o);
          }
          need(h, qb);
          const uint32_t kd = kdesc(h, qb + 4), kt = kdesc(h, qb), vd = vdesc(h, qb + 4), vt = vdesc(h, qb);
          {
            float sd[16], st[16];
            wg_fence();
            qk32x2(sd, st, qf, kd, kt);
            wg_commit();
            pv32(o, p3, vdesc(h, qb + 1)); pv32(o, p3 + 8, vdesc(h, qb + 1) + 2 * VSTEP);
            wg_commit();
            wg_wait<1>();
            fence_regs<16>(sd); fence_regs<16>(st);
            if (warp != 9) STEPT(11 + nu * 8);
            edge32(sd, st, p4, p4 + 8, wi, dl, mt);
            fence_regs_u<16>(p4);
            wg_wait<0>();
            fence_regs<20>(o);
          }
          const int un = (ul >> 4) == 8 ? 4 : (ul >> 4) & 7;
          {
            float sd[16], st[16];
            wg_fence();
            qk32x2(sd, st, qf, kd + 128, kt + 128);
            wg_commit();
            pv32(o, p4, vd); pv32(o, p4 + 8, vt);
            wg_commit();
            wg_wait<1>();
            fence_regs<16>(sd); fence_regs<16>(st);
            load_q(qf, un);
            edge32(sd, st, p5, p5 + 8, wi - 2, dl, mt);
            fence_regs_u<16>(p5);
          }
          need(un >> 2, 6 - (un & 3));
          wg_fence();
          pv32(o, p5, vd + 2 * VSTEP); pv32(o, p5 + 8, vt + 2 * VSTEP);
          wg_commit();
          qk64(s, qf, kdesc(un >> 2, 6 - (un & 3)));
          wg_commit();
          wg_wait<1>();
          fence_regs<20>(o);
          if (warp != 9) STEPT(12 + nu * 8);
          const bool unsafe = !(o[16] >= LSUM_MIN && o[16] <= LSUM_MAX && o[18] >= LSUM_MIN && o[18] <= LSUM_MAX);
          if (__any_sync(0xffffffffu, unsafe)) redo |= 1 << u;
          else store_o(o, u);
          wg_wait<0>();
          fence_regs<32>(s);
        }
      }
      if (warp != 9) STEPT(31);
      if (bar_red_or(1 + wg, 128, redo)) {
#pragma unroll 1
        for (int ul = units; ul != 8; ul >>= 4) {
          const int u = ul & 7;
          if (!bar_red_or(1 + wg, 128, redo >> u & 1)) continue;
          const int h = u >> 2, qb = 3 - (u & 3);
          uint32_t qf[8], p[16];
          float o[20], m0 = -INFINITY, m1 = -INFINITY;
          load_q(qf, u);
#pragma unroll
          for (int i = 0; i < 20; i++) o[i] = 0.f;
#pragma unroll 1
          for (int j = 0; j <= (rb == 0 ? qb : 4); j++) {
            const int b = qb + 4 - j;
            float s[32];
            wg_fence();
            qk64(s, qf, kdesc(h, b));
            wg_commit();
            wg_wait<0>();
            fence_regs<32>(s);
            float mx0 = m0, mx1 = m1;
#pragma unroll
            for (int c = 0; c < 8; c++) {
#pragma unroll
              for (int i = 0; i < 4; i++) {
                const int diff = j * 64 + (16 * wi + g + (i >> 1) * 8) - (8 * c + 2 * q + (i & 1));
                if (diff < 0 || diff > 255) s[4 * c + i] = -INFINITY;
              }
              mx0 = fmaxf(mx0, fmaxf(s[4 * c], s[4 * c + 1]));
              mx1 = fmaxf(mx1, fmaxf(s[4 * c + 2], s[4 * c + 3]));
            }
            mx0 = fmaxf(mx0, __shfl_xor_sync(0xffffffffu, mx0, 1)); mx1 = fmaxf(mx1, __shfl_xor_sync(0xffffffffu, mx1, 1));
            mx0 = fmaxf(mx0, __shfl_xor_sync(0xffffffffu, mx0, 2)); mx1 = fmaxf(mx1, __shfl_xor_sync(0xffffffffu, mx1, 2));
            const float r0 = j == 0 ? 0.f : ex2(m0 - mx0), r1 = j == 0 ? 0.f : ex2(m1 - mx1);
            m0 = mx0; m1 = mx1;
#pragma unroll
            for (int i = 0; i < 5; i++) { o[4 * i] *= r0; o[4 * i + 1] *= r0; o[4 * i + 2] *= r1; o[4 * i + 3] *= r1; }
#pragma unroll
            for (int c = 0; c < 8; c++) { s[4 * c] -= m0; s[4 * c + 1] -= m0; s[4 * c + 2] -= m1; s[4 * c + 3] -= m1; }
            exp_pack<8>(s, p);
            fence_regs<20>(o); fence_regs_u<16>(p);
            wg_fence();
            pv32(o, p, vdesc(h, b)); pv32(o, p + 8, vdesc(h, b) + 2 * VSTEP);
            wg_commit();
            wg_wait<0>();
            fence_regs<20>(o);
          }
          named_bar(1 + wg, 128);
          if (redo >> u & 1) store_o(o, u);
          __syncwarp();
        }
      }
      if (wi == 0) PROF(6 + wg);
    }
    pass_v = pass + 1;
  }
}

}

typedef CUresult (*EncodeFn)(CUtensorMap*, CUtensorMapDataType, cuuint32_t, void*, const cuuint64_t*, const cuuint64_t*,
                             const cuuint32_t*, const cuuint32_t*, CUtensorMapInterleave, CUtensorMapSwizzle,
                             CUtensorMapL2promotion, CUtensorMapFloatOOBfill);
static EncodeFn g_encode = nullptr;
struct Dim { uint64_t size, stride; uint32_t box; };
template <int N> static CUtensorMap make_map(const void* ptr, const Dim (&d)[N], int swizzle) {
  CUtensorMap m;
  cuuint64_t dims[N], strides[N];
  cuuint32_t box[N], es[N];
  for (int i = 0; i < N; i++) { dims[i] = d[i].size; strides[i] = d[i].stride; box[i] = d[i].box; es[i] = 1; }
  g_encode(&m, CU_TENSOR_MAP_DATA_TYPE_BFLOAT16, N, const_cast<void*>(ptr), dims, strides + 1, box, es, CU_TENSOR_MAP_INTERLEAVE_NONE,
           swizzle == 128 ? CU_TENSOR_MAP_SWIZZLE_128B : (swizzle == 64 ? CU_TENSOR_MAP_SWIZZLE_64B : CU_TENSOR_MAP_SWIZZLE_NONE),
           swizzle ? CU_TENSOR_MAP_L2_PROMOTION_L2_256B : CU_TENSOR_MAP_L2_PROMOTION_L2_128B, CU_TENSOR_MAP_FLOAT_OOB_FILL_NONE);
  return m;
}
static CUtensorMap map2(const void* ptr, uint64_t inner, uint64_t outer, uint32_t bi, uint32_t bo, int swizzle) {
  const Dim d[2] = {{inner, 0, bi}, {outer, inner * 2, bo}};
  return make_map(ptr, d, swizzle);
}
template <class T> static void* sym_addr(T& sym) { void* p = nullptr; cudaGetSymbolAddress(&p, sym); return p; }

static Params h_p;
static const void* h_key[9];

static cudaLaunchConfig_t launch_cfg(int grid, cudaLaunchAttribute* at) {
  cudaLaunchConfig_t cfg = {};
  cfg.gridDim = dim3(grid); cfg.blockDim = dim3(512); cfg.dynamicSmemBytes = SMEM_BYTES; cfg.stream = cudaStreamPerThread;
  at[0].id = cudaLaunchAttributeClusterDimension;
  at[0].val.clusterDim.x = 2; at[0].val.clusterDim.y = 1; at[0].val.clusterDim.z = 1;
  cfg.attrs = at; cfg.numAttrs = 1;
  return cfg;
}

extern "C" void kernel_launch(void* const* d_in, const int* in_sizes, int n_in, void* d_out, int out_size) {
  const bf16* x = (const bf16*)d_in[0];
  const bf16* wqkv = (const bf16*)d_in[1];
  const bf16* wo = (const bf16*)d_in[2];
  cudaLaunchAttribute at[1];
  bool fresh = g_encode != nullptr && h_key[8] == d_out;
  for (int i = 0; i < 8; i++) fresh = fresh && h_key[i] == d_in[i];
  if (!fresh) {
    if (!g_encode) {
      void* fn = nullptr;
      cudaDriverEntryPointQueryResult st;
      cudaGetDriverEntryPoint("cuTensorMapEncodeTiled", &fn, cudaEnableDefault, &st);
      g_encode = (EncodeFn)fn;
      cudaFuncSetAttribute(mega_kernel, cudaFuncAttributeMaxDynamicSharedMemorySize, SMEM_BYTES);
    }
    bf16* x1 = (bf16*)sym_addr(g_x1);
    Params& p = h_p;
    p.x = x; p.wqkv = wqkv; p.wo = wo; p.w_r = (const bf16*)d_in[4]; p.w_g = (const bf16*)d_in[5]; p.w_u = (const bf16*)d_in[6]; p.w_d = (const bf16*)d_in[7];
    p.out = (bf16*)d_out;
    p.mapA[0] = map2(x, DM, SEQ, 32, 256, 64);
    p.mapA[1] = map2(x1, DM, SEQ, 32, 256, 64);
    { const Dim d[3] = {{DM, 0, 64}, {DM, 3 * DM * 2, 16}, {3, DM * 2, 3}}; p.mapW = make_map(wqkv, d, 128); }
    { const Dim d[3] = {{DM, 0, 64}, {DM, 3 * DM * 2, 32}, {3, DM * 2, 3}}; p.mapWs = make_map(wqkv, d, 128); }
    { const Dim d[3] = {{DM, 0, 64}, {64, DM * 2, 32}, {16, 64 * DM * 2, 2}}; p.mapWo = make_map(wo, d, 128); }
    p.mapRes[0] = map2(x, DM, SEQ, 64, 64, 128);
    p.mapRes[1] = p.mapXst[0] = map2(x1, DM, SEQ, 64, 64, 128);
    p.mapXst[1] = map2(d_out, DM, SEQ, 64, 64, 128);
    p.mapG = map2(p.w_g, FF, DM, 56, 128, 0);
    p.mapU = map2(p.w_u, FF, DM, 56, 128, 0);
    { const Dim d[3] = {{64, 0, 64}, {FF, DM * 2, 28}, {DM / 64, 128, 8}}; p.mapD = make_map(p.w_d, d, 128); }
    for (int i = 0; i < 8; i++) h_key[i] = d_in[i];
    h_key[8] = d_out;
  }
  void* a0[] = {&h_p};
  cudaLaunchConfig_t cfg = launch_cfg(128, at);
  cudaLaunchKernelExC(&cfg, (const void*)mega_kernel, a0);
}
```

```cpp
#include <cuda_runtime.h>
#include <cuda_bf16.h>
#include <cuda.h>
#include <stdint.h>

namespace {

constexpr int SEQ = 2048, DM = 1024, FF = 3584;
constexpr float LN_EPS = 1e-5f;
typedef __nv_bfloat16 bf16;

__device__ __align__(1024) uint8_t g_kv[3 * 16 * 65536];
__device__ __align__(1024) uint8_t g_o[SEQ * DM * 2];
__device__ __align__(1024) bf16 g_x1[SEQ * DM];
__device__ unsigned g_epoch;
struct __align__(128) Flag { unsigned v[32]; };
__device__ Flag g_kvflag[3][16][2], g_oflag[8][2][16], g_xflag[16][8];
__device__ uint4 g_rowab[2][SEQ];
__device__ __align__(16) uint32_t g_vw[2][8][3 * DM];
constexpr uint32_t SENT = 0xFFFFFFFFu;
__device__ uint4 g_part[2][8 * SEQ];
__device__ uint4 g_slot[2][16 * 8];
__device__ uint4 g_cand[2][16 * 128];
__device__ uint4 g_ypart[2][128 * DM / 4];
__device__ uint4 g_x2row[128 * 2];
__device__ float2 g_rowln[8][SEQ];
__device__ int g_sel[2];

#define PROFL(l, e)
#define PROF(e) PROFL(layer, e)
#define STEPT(i)
#define SPIN_LIMIT 4000000u
__device__ __forceinline__ uint32_t smem_u32(const void* p) { return (uint32_t)__cvta_generic_to_shared(p); }
__device__ __forceinline__ void mbar_init(uint32_t bar, uint32_t cnt) {
  asm volatile("mbarrier.init.shared::cta.b64 [%0], %1;" ::"r"(bar), "r"(cnt) : "memory");
}
#define ELECT "{\n.reg .pred e;\nelect.sync _|e, 0xffffffff;\n@e "
__device__ __forceinline__ void mbar_expect_tx(uint32_t bar, uint32_t bytes) {
  asm volatile(ELECT "mbarrier.arrive.expect_tx.shared::cta.b64 _, [%0], %1;\n}" ::"r"(bar), "r"(bytes) : "memory");
}
__device__ __forceinline__ void mbar_arrive(uint32_t bar) {
  asm volatile("mbarrier.arrive.shared::cta.b64 _, [%0];" ::"r"(bar) : "memory");
}
__device__ __forceinline__ void mbar_arrive_e(uint32_t bar) {
  asm volatile(ELECT "mbarrier.arrive.shared::cta.b64 _, [%0];\n}" ::"r"(bar) : "memory");
}
__device__ __forceinline__ uint32_t mapa(uint32_t addr, uint32_t cta) {
  uint32_t r; asm("mapa.shared::cluster.u32 %0, %1, %2;" : "=r"(r) : "r"(addr), "r"(cta)); return r;
}
__device__ __forceinline__ void mbar_arrive_cluster(uint32_t bar, uint32_t cta) {
  asm volatile("mbarrier.arrive.shared::cluster.b64 _, [%0];" ::"r"(mapa(bar, cta)) : "memory");
}
#define MBAR_WAIT_ASM(QUAL)                                                                                                \
  asm volatile("{\n.reg .pred p;\nWAIT_LOOP:\n.pragma \"nounroll\";\nmbarrier.try_wait.parity" QUAL ".shared::cta.b64 p, [%0], %1;\n" \
               "@!p bra WAIT_LOOP;\n}" ::"r"(bar), "r"(parity) : "memory")
__device__ __forceinline__ void mbar_wait(uint32_t bar, uint32_t parity) { MBAR_WAIT_ASM(""); }
__device__ __forceinline__ void mbar_wait_cluster(uint32_t bar, uint32_t parity) { MBAR_WAIT_ASM(".acquire.cluster"); }
__device__ __forceinline__ void st_async2(uint32_t addr, float a, float b, uint32_t bar) {
  asm volatile("st.async.weak.shared::cluster.mbarrier::complete_tx::bytes.v2.f32 [%0], {%1, %2}, [%3];"
               ::"r"(addr), "f"(a), "f"(b), "r"(bar) : "memory");
}
__device__ __forceinline__ uint64_t policy_evict_first() {
  uint64_t p; asm volatile("createpolicy.fractional.L2::evict_first.b64 %0, 1.0;" : "=l"(p)); return p;
}
__device__ __forceinline__ void tma_load2(uint32_t dst, const CUtensorMap* m, int c0, int c1, uint32_t bar) {
  asm volatile(ELECT "cp.async.bulk.tensor.2d.shared::cluster.global.mbarrier::complete_tx::bytes [%0], [%1, {%3, %4}], [%2];\n}"
               ::"r"(dst), "l"(m), "r"(bar), "r"(c0), "r"(c1) : "memory");
}
__device__ __forceinline__ void tma_load2_h(uint32_t dst, const CUtensorMap* m, int c0, int c1, uint32_t bar, uint64_t pol) {
  asm volatile(ELECT "cp.async.bulk.tensor.2d.shared::cluster.global.mbarrier::complete_tx::bytes.L2::cache_hint [%0], [%1, {%3, %4}], [%2], %5;\n}"
               ::"r"(dst), "l"(m), "r"(bar), "r"(c0), "r"(c1), "l"(pol) : "memory");
}
__device__ __forceinline__ void tma_load3(uint32_t dst, const CUtensorMap* m, int c0, int c1, int c2, uint32_t bar) {
  asm volatile(ELECT "cp.async.bulk.tensor.3d.shared::cluster.global.mbarrier::complete_tx::bytes [%0], [%1, {%3, %4, %5}], [%2];\n}"
               ::"r"(dst), "l"(m), "r"(bar), "r"(c0), "r"(c1), "r"(c2) : "memory");
}
__device__ __forceinline__ void tma_load3_h(uint32_t dst, const CUtensorMap* m, int c0, int c1, int c2, uint32_t bar, uint64_t pol) {
  asm volatile(ELECT "cp.async.bulk.tensor.3d.shared::cluster.global.mbarrier::complete_tx::bytes.L2::cache_hint [%0], [%1, {%3, %4, %5}], [%2], %6;\n}"
               ::"r"(dst), "l"(m), "r"(bar), "r"(c0), "r"(c1), "r"(c2), "l"(pol) : "memory");
}
__device__ __forceinline__ void tma_load3_mc(uint32_t dst, const CUtensorMap* m, int c0, int c1, int c2, uint32_t bar) {
  asm volatile(ELECT "cp.async.bulk.tensor.3d.shared::cluster.global.mbarrier::complete_tx::bytes.multicast::cluster [%0], [%1, {%3, %4, %5}], [%2], %6;\n}"
               ::"r"(dst), "l"(m), "r"(bar), "r"(c0), "r"(c1), "r"(c2), "h"((uint16_t)3) : "memory");
}
__device__ __forceinline__ void bulk_push(uint32_t dst, uint32_t src, uint32_t bytes, uint32_t bar) {
  asm volatile(ELECT "cp.async.bulk.shared::cluster.shared::cta.mbarrier::complete_tx::bytes [%0], [%1], %2, [%3];\n}"
               ::"r"(dst), "r"(src), "r"(bytes), "r"(bar) : "memory");
}
template <int N> __device__ __forceinline__ void regs_inc() { asm volatile("setmaxnreg.inc.sync.aligned.u32 %0;" ::"n"(N)); }
template <int N> __device__ __forceinline__ void regs_dec() { asm volatile("setmaxnreg.dec.sync.aligned.u32 %0;" ::"n"(N)); }
__device__ __forceinline__ void tma_prefetch2(const CUtensorMap* m, int c0, int c1) {
  asm volatile(ELECT "cp.async.bulk.prefetch.tensor.2d.L2.global [%0, {%1, %2}];\n}" ::"l"(m), "r"(c0), "r"(c1) : "memory");
}
__device__ __forceinline__ void bulk_prefetch(const void* p, uint32_t bytes) {
  asm volatile(ELECT "cp.async.bulk.prefetch.L2.global [%0], %1;\n}" ::"l"(p), "r"(bytes) : "memory");
}
__device__ __forceinline__ void tma_store(const CUtensorMap* m, uint32_t src, int c0, int c1) {
  asm volatile(ELECT "cp.async.bulk.tensor.2d.global.shared::cta.bulk_group [%0, {%2, %3}], [%1];\n}"
               ::"l"(m), "r"(src), "r"(c0), "r"(c1) : "memory");
}
__device__ __forceinline__ void bulk_load(uint32_t dst, const void* src, uint32_t bytes, uint32_t bar) {
  asm volatile(ELECT "cp.async.bulk.shared::cluster.global.mbarrier::complete_tx::bytes [%0], [%1], %2, [%3];\n}"
               ::"r"(dst), "l"(src), "r"(bytes), "r"(bar) : "memory");
}
__device__ __forceinline__ void bulk_load_h(uint32_t dst, const void* src, uint32_t bytes, uint32_t bar, uint64_t pol) {
  asm volatile(ELECT "cp.async.bulk.shared::cluster.global.mbarrier::complete_tx::bytes.L2::cache_hint [%0], [%1], %2, [%3], %4;\n}"
               ::"r"(dst), "l"(src), "r"(bytes), "r"(bar), "l"(pol) : "memory");
}
__device__ __forceinline__ void bulk_store(void* dst, uint32_t src, uint32_t bytes) {
  asm volatile(ELECT "cp.async.bulk.global.shared::cta.bulk_group [%0], [%1], %2;\n}" ::"l"(dst), "r"(src), "r"(bytes) : "memory");
}
__device__ __forceinline__ void bulk_commit() { asm volatile("cp.async.bulk.commit_group;" ::: "memory"); }
__device__ __forceinline__ void bulk_wait_all() { asm volatile("cp.async.bulk.wait_group 0;" ::: "memory"); }
__device__ __forceinline__ void fence_async_smem() { asm volatile("fence.proxy.async.shared::cta;" ::: "memory"); }
__device__ __forceinline__ void fence_async_global() { asm volatile("fence.proxy.async.global;" ::: "memory"); }
__device__ __forceinline__ void fence_release() { asm volatile("fence.release.gpu;" ::: "memory"); }
__device__ __forceinline__ void l2_prefetch_line(const void* p) { asm volatile("prefetch.global.L2 [%0];" ::"l"(p) : "memory"); }
__device__ __forceinline__ void prefetch_tmap(const CUtensorMap* m) { asm volatile("prefetch.tensormap [%0];" ::"l"(m) : "memory"); }
__device__ __forceinline__ void named_bar(int id, int n) { asm volatile("bar.sync %0, %1;" ::"r"(id), "r"(n) : "memory"); }
__device__ __forceinline__ bool bar_red_or(int id, int n, bool v) {
  uint32_t r;
  asm volatile("{\n.reg .pred p, q;\nsetp.ne.u32 q, %3, 0;\nbarrier.cta.red.or.pred p, %1, %2, q;\nselp.u32 %0, 1, 0, p;\n}"
               : "=r"(r) : "r"(id), "r"(n), "r"((uint32_t)v) : "memory");
  return r != 0;
}
__device__ __forceinline__ void cluster_arrive() { asm volatile("barrier.cluster.arrive.relaxed.aligned;" ::: "memory"); }
__device__ __forceinline__ void cluster_wait() { asm volatile("barrier.cluster.wait.aligned;" ::: "memory"); }
__device__ __forceinline__ uint32_t cluster_rank() { uint32_t r; asm volatile("mov.u32 %0, %%cluster_ctarank;" : "=r"(r)); return r; }
__device__ __forceinline__ unsigned ld_relaxed(const unsigned* p) {
  unsigned v; asm volatile("ld.relaxed.gpu.global.u32 %0, [%1];" : "=r"(v) : "l"(p) : "memory"); return v;
}
__device__ __forceinline__ uint4 ld_relaxed4(const uint4* p) {
  uint4 v; asm volatile("ld.relaxed.gpu.global.v4.u32 {%0, %1, %2, %3}, [%4];" : "=r"(v.x), "=r"(v.y), "=r"(v.z), "=r"(v.w) : "l"(p) : "memory"); return v;
}
__device__ __forceinline__ void st_relaxed(unsigned* p, unsigned v) {
  asm volatile("st.relaxed.gpu.global.u32 [%0], %1;" ::"l"(p), "r"(v) : "memory");
}
__device__ __forceinline__ uint2 ld_relaxed2(const void* p) {
  uint2 v; asm volatile("ld.relaxed.gpu.global.v2.u32 {%0, %1}, [%2];" : "=r"(v.x), "=r"(v.y) : "l"(p) : "memory"); return v;
}
__device__ __forceinline__ void st_relaxed4(uint4* p, uint4 v) {
  asm volatile("st.relaxed.gpu.global.v4.u32 [%0], {%1, %2, %3, %4};" ::"l"(p), "r"(v.x), "r"(v.y), "r"(v.z), "r"(v.w) : "memory");
}
__device__ __forceinline__ bool valid4(uint4 v) { return v.x != SENT && v.y != SENT && v.z != SENT && v.w != SENT; }
__device__ __forceinline__ uint4 poll4(const uint4* p) {
  uint4 v;
  uint32_t spins = 0;
#pragma unroll 1
  do { v = ld_relaxed4(p); } while (!valid4(v) && ++spins < SPIN_LIMIT);
  return v;
}
__device__ __forceinline__ void set_flag(unsigned* p, unsigned tag) {
  asm volatile(ELECT "st.release.gpu.global.u32 [%0], %1;\n}" ::"l"(p), "r"(tag) : "memory");
}
__device__ __forceinline__ void poll_flag(const unsigned* p, unsigned tag) {
#pragma unroll 1
  for (uint32_t spins = 0; !__all_sync(0xffffffffu, ld_relaxed(p) == tag) && spins < SPIN_LIMIT; spins++) {}
  asm volatile("fence.acquire.gpu;" ::: "memory");
}
__device__ __forceinline__ uint32_t enc(float x) { return __float_as_uint(x + 0.0f) ^ 0x80000000u; }
__device__ __forceinline__ float dec(uint32_t u) { return __uint_as_float(u ^ 0x80000000u); }
__device__ __forceinline__ uint32_t hadd_bf2(uint32_t a, uint32_t b) {
  uint32_t r; asm("add.rn.bf16x2 %0, %1, %2;" : "=r"(r) : "r"(a), "r"(b)); return r;
}
__device__ __forceinline__ uint32_t hsub_bf2(uint32_t a, uint32_t b) {
  uint32_t r; asm("sub.rn.bf16x2 %0, %1, %2;" : "=r"(r) : "r"(a), "r"(b)); return r;
}
__device__ __forceinline__ void wg_fence() { asm volatile("wgmma.fence.sync.aligned;" ::: "memory"); }
__device__ __forceinline__ void wg_commit() { asm volatile("wgmma.commit_group.sync.aligned;" ::: "memory"); }
template <int N> __device__ __forceinline__ void wg_wait() { asm volatile("wgmma.wait_group.sync.aligned %0;" ::"n"(N) : "memory"); }
template <int R> __device__ __forceinline__ void fence_regs(float* d) {
#pragma unroll
  for (int i = 0; i < R; i++) asm volatile("" : "+f"(d[i])::"memory");
}
template <int R> __device__ __forceinline__ void fence_regs_u(uint32_t* d) {
#pragma unroll
  for (int i = 0; i < R; i++) asm volatile("" : "+r"(d[i])::"memory");
}
__host__ __device__ constexpr uint32_t dlo(uint32_t addr, uint32_t lbo) { return ((addr & 0x3FFFF) >> 4) | ((lbo >> 4) << 16); }
constexpr uint32_t H128 = 0x40000040u, H64 = 0x80000020u;
__device__ __forceinline__ void stsm_x4(uint32_t addr, uint32_t r0, uint32_t r1, uint32_t r2, uint32_t r3) {
  asm volatile("stmatrix.sync.aligned.m8n8.x4.shared.b16 [%0], {%1, %2, %3, %4};"
               ::"r"(addr), "r"(r0), "r"(r1), "r"(r2), "r"(r3) : "memory");
}
__device__ __forceinline__ void ldsm_x4(uint32_t addr, uint32_t& r0, uint32_t& r1, uint32_t& r2, uint32_t& r3) {
  asm volatile("ldmatrix.sync.aligned.m8n8.x4.shared.b16 {%0, %1, %2, %3}, [%4];"
               : "=r"(r0), "=r"(r1), "=r"(r2), "=r"(r3) : "r"(addr) : "memory");
}
__device__ __forceinline__ void ldsm_x4_t(uint32_t addr, uint32_t& r0, uint32_t& r1, uint32_t& r2, uint32_t& r3) {
  asm volatile("ldmatrix.sync.aligned.m8n8.x4.trans.shared.b16 {%0, %1, %2, %3}, [%4];"
               : "=r"(r0), "=r"(r1), "=r"(r2), "=r"(r3) : "r"(addr) : "memory");
}
__device__ __forceinline__ void mma_16816(float* d, uint32_t a0, uint32_t a1, uint32_t a2, uint32_t a3, uint32_t b0, uint32_t b1) {
  asm volatile("mma.sync.aligned.m16n8k16.row.col.f32.bf16.bf16.f32 {%0, %1, %2, %3}, {%4, %5, %6, %7}, {%8, %9}, {%0, %1, %2, %3};"
               : "+f"(d[0]), "+f"(d[1]), "+f"(d[2]), "+f"(d[3]) : "r"(a0), "r"(a1), "r"(a2), "r"(a3), "r"(b0), "r"(b1));
}
__device__ __forceinline__ void spin_cycles(int n) {
  const int t0 = (int)clock();
#pragma unroll 1
  while ((int)clock() - t0 < n) {}
}
__device__ __forceinline__ uint32_t pack_bf16(float lo, float hi) {
  uint32_t r; asm("cvt.rn.bf16x2.f32 %0, %1, %2;" : "=r"(r) : "f"(hi), "f"(lo)); return r;
}
__device__ __forceinline__ float bf_lo(uint32_t v) { return __uint_as_float(v << 16); }
__device__ __forceinline__ float bf_hi(uint32_t v) { return __uint_as_float(v & 0xffff0000u); }
__device__ __forceinline__ float rbf(float x) { return __bfloat162float(__float2bfloat16_rn(x)); }
__device__ __forceinline__ float ex2(float x) { float y; asm("ex2.approx.ftz.f32 %0, %1;" : "=f"(y) : "f"(x)); return y; }
__device__ __forceinline__ float rcp(float x) { float y; asm("rcp.approx.ftz.f32 %0, %1;" : "=f"(y) : "f"(x)); return y; }
__device__ __forceinline__ uint32_t shl_clamp(uint32_t v, uint32_t n) {
  uint32_t r; asm("shl.b32 %0, %1, %2;" : "=r"(r) : "r"(v), "r"(n)); return r;
}
__device__ __forceinline__ float warp_sum(float v) {
#pragma unroll
  for (int o = 16; o > 0; o >>= 1) v += __shfl_xor_sync(0xffffffffu, v, o);
  return v;
}
__device__ __forceinline__ float ln_inv(float var) {
  float r;
  asm("sqrt.approx.ftz.f32 %0, %1;" : "=f"(r) : "f"(rbf(rbf(var) + LN_EPS)));
  asm("rcp.approx.ftz.f32 %0, %1;" : "=f"(r) : "f"(rbf(r)));
  return r;
}
__device__ __forceinline__ uint32_t ln_pair(uint32_t x, uint32_t mean2, float inv) {
  const uint32_t d = hsub_bf2(x, mean2);
  return pack_bf16(bf_lo(d) * inv, bf_hi(d) * inv);
}
__device__ __forceinline__ uint32_t add_ln_pair(uint32_t x, uint32_t mean2, float inv) { return hadd_bf2(x, ln_pair(x, mean2, inv)); }
__device__ __forceinline__ uint32_t router_key(float r_bf, int row) {
  uint32_t u = __float_as_uint(r_bf);
  u = (u & 0x80000000u) ? ~u : (u | 0x80000000u);
  return (u & 0xFFFF0000u) | 0x8000u | (uint32_t)(SEQ - 1 - row);
}

template <uint32_t HA = 0x40000040u, uint32_t HB = 0x40000040u>
__device__ __forceinline__ void wg_ss192t(float* d, uint32_t da, uint32_t db, int scale_d) {
  asm volatile("{\n.reg .pred p;\n.reg .b64 dA, dB;\nmov.b64 dA, {%96, %99};\nmov.b64 dB, {%97, %100};\nsetp.ne.b32 p, %98, 0;\n"
    "wgmma.mma_async.sync.aligned.m64n192k16.f32.bf16.bf16 "
    "{%0, %1, %2, %3, %4, %5, %6, %7, %8, %9, %10, %11, %12, %13, %14, %15, "
    "%16, %17, %18, %19, %20, %21, %22, %23, %24, %25, %26, %27, %28, %29, %30, %31, "
    "%32, %33, %34, %35, %36, %37, %38, %39, %40, %41, %42, %43, %44, %45, %46, %47, "
    "%48, %49, %50, %51, %52, %53, %54, %55, %56, %57, %58, %59, %60, %61, %62, %63, "
    "%64, %65, %66, %67, %68, %69, %70, %71, %72, %73, %74, %75, %76, %77, %78, %79, "
    "%80, %81, %82, %83, %84, %85, %86, %87, %88, %89, %90, %91, %92, %93, %94, %95}, "
    "dA, dB, p, 1, 1, 0, 1;\n}\n"
    : "+f"(d[0]), "+f"(d[1]), "+f"(d[2]), "+f"(d[3]), "+f"(d[4]), "+f"(d[5]), "+f"(d[6]), "+f"(d[7]),
      "+f"(d[8]), "+f"(d[9]), "+f"(d[10]), "+f"(d[11]), "+f"(d[12]), "+f"(d[13]), "+f"(d[14]), "+f"(d[15]),
      "+f"(d[16]), "+f"(d[17]), "+f"(d[18]), "+f"(d[19]), "+f"(d[20]), "+f"(d[21]), "+f"(d[22]), "+f"(d[23]),
      "+f"(d[24]), "+f"(d[25]), "+f"(d[26]), "+f"(d[27]), "+f"(d[28]), "+f"(d[29]), "+f"(d[30]), "+f"(d[31]),
      "+f"(d[32]), "+f"(d[33]), "+f"(d[34]), "+f"(d[35]), "+f"(d[36]), "+f"(d[37]), "+f"(d[38]), "+f"(d[39]),
      "+f"(d[40]), "+f"(d[41]), "+f"(d[42]), "+f"(d[43]), "+f"(d[44]), "+f"(d[45]), "+f"(d[46]), "+f"(d[47]),
      "+f"(d[48]), "+f"(d[49]), "+f"(d[50]), "+f"(d[51]), "+f"(d[52]), "+f"(d[53]), "+f"(d[54]), "+f"(d[55]),
      "+f"(d[56]), "+f"(d[57]), "+f"(d[58]), "+f"(d[59]), "+f"(d[60]), "+f"(d[61]), "+f"(d[62]), "+f"(d[63]),
      "+f"(d[64]), "+f"(d[65]), "+f"(d[66]), "+f"(d[67]), "+f"(d[68]), "+f"(d[69]), "+f"(d[70]), "+f"(d[71]),
      "+f"(d[72]), "+f"(d[73]), "+f"(d[74]), "+f"(d[75]), "+f"(d[76]), "+f"(d[77]), "+f"(d[78]), "+f"(d[79]),
      "+f"(d[80]), "+f"(d[81]), "+f"(d[82]), "+f"(d[83]), "+f"(d[84]), "+f"(d[85]), "+f"(d[86]), "+f"(d[87]),
      "+f"(d[88]), "+f"(d[89]), "+f"(d[90]), "+f"(d[91]), "+f"(d[92]), "+f"(d[93]), "+f"(d[94]), "+f"(d[95])
    : "r"(da), "r"(db), "r"(scale_d), "n"(HA), "n"(HB));
}
template <uint32_t HA = 0x40000040u, uint32_t HB = 0x40000040u>
__device__ __forceinline__ void wg_ss192t_z(float* d, uint32_t da, uint32_t db) {
  asm volatile("{\n.reg .pred p;\n.reg .b64 dA, dB;\nmov.b64 dA, {%96, %98};\nmov.b64 dB, {%97, %99};\nsetp.ne.b32 p, 0, 0;\n"
    "wgmma.mma_async.sync.aligned.m64n192k16.f32.bf16.bf16 "
    "{%0, %1, %2, %3, %4, %5, %6, %7, %8, %9, %10, %11, %12, %13, %14, %15, "
    "%16, %17, %18, %19, %20, %21, %22, %23, %24, %25, %26, %27, %28, %29, %30, %31, "
    "%32, %33, %34, %35, %36, %37, %38, %39, %40, %41, %42, %43, %44, %45, %46, %47, "
    "%48, %49, %50, %51, %52, %53, %54, %55, %56, %57, %58, %59, %60, %61, %62, %63, "
    "%64, %65, %66, %67, %68, %69, %70, %71, %72, %73, %74, %75, %76, %77, %78, %79, "
    "%80, %81, %82, %83, %84, %85, %86, %87, %88, %89, %90, %91, %92, %93, %94, %95}, "
    "dA, dB, p, 1, 1, 0, 1;\n}\n"
    : "=f"(d[0]), "=f"(d[1]), "=f"(d[2]), "=f"(d[3]), "=f"(d[4]), "=f"(d[5]), "=f"(d[6]), "=f"(d[7]),
      "=f"(d[8]), "=f"(d[9]), "=f"(d[10]), "=f"(d[11]), "=f"(d[12]), "=f"(d[13]), "=f"(d[14]), "=f"(d[15]),
      "=f"(d[16]), "=f"(d[17]), "=f"(d[18]), "=f"(d[19]), "=f"(d[20]), "=f"(d[21]), "=f"(d[22]), "=f"(d[23]),
      "=f"(d[24]), "=f"(d[25]), "=f"(d[26]), "=f"(d[27]), "=f"(d[28]), "=f"(d[29]), "=f"(d[30]), "=f"(d[31]),
      "=f"(d[32]), "=f"(d[33]), "=f"(d[34]), "=f"(d[35]), "=f"(d[36]), "=f"(d[37]), "=f"(d[38]), "=f"(d[39]),
      "=f"(d[40]), "=f"(d[41]), "=f"(d[42]), "=f"(d[43]), "=f"(d[44]), "=f"(d[45]), "=f"(d[46]), "=f"(d[47]),
      "=f"(d[48]), "=f"(d[49]), "=f"(d[50]), "=f"(d[51]), "=f"(d[52]), "=f"(d[53]), "=f"(d[54]), "=f"(d[55]),
      "=f"(d[56]), "=f"(d[57]), "=f"(d[58]), "=f"(d[59]), "=f"(d[60]), "=f"(d[61]), "=f"(d[62]), "=f"(d[63]),
      "=f"(d[64]), "=f"(d[65]), "=f"(d[66]), "=f"(d[67]), "=f"(d[68]), "=f"(d[69]), "=f"(d[70]), "=f"(d[71]),
      "=f"(d[72]), "=f"(d[73]), "=f"(d[74]), "=f"(d[75]), "=f"(d[76]), "=f"(d[77]), "=f"(d[78]), "=f"(d[79]),
      "=f"(d[80]), "=f"(d[81]), "=f"(d[82]), "=f"(d[83]), "=f"(d[84]), "=f"(d[85]), "=f"(d[86]), "=f"(d[87]),
      "=f"(d[88]), "=f"(d[89]), "=f"(d[90]), "=f"(d[91]), "=f"(d[92]), "=f"(d[93]), "=f"(d[94]), "=f"(d[95])
    : "r"(da), "r"(db), "n"(HA), "n"(HB));
}
template <uint32_t HA = 0x40000040u, uint32_t HB = 0x40000040u>
__device__ __forceinline__ void wg_ss128t(float* d, uint32_t da, uint32_t db, int scale_d) {
  asm volatile("{\n.reg .pred p;\n.reg .b64 dA, dB;\nmov.b64 dA, {%64, %67};\nmov.b64 dB, {%65, %68};\nsetp.ne.b32 p, %66, 0;\n"
    "wgmma.mma_async.sync.aligned.m64n128k16.f32.bf16.bf16 "
    "{%0, %1, %2, %3, %4, %5, %6, %7, %8, %9, %10, %11, %12, %13, %14, %15, "
    "%16, %17, %18, %19, %20, %21, %22, %23, %24, %25, %26, %27, %28, %29, %30, %31, "
    "%32, %33, %34, %35, %36, %37, %38, %39, %40, %41, %42, %43, %44, %45, %46, %47, "
    "%48, %49, %50, %51, %52, %53, %54, %55, %56, %57, %58, %59, %60, %61, %62, %63}, "
    "dA, dB, p, 1, 1, 0, 1;\n}\n"
    : "+f"(d[0]), "+f"(d[1]), "+f"(d[2]), "+f"(d[3]), "+f"(d[4]), "+f"(d[5]), "+f"(d[6]), "+f"(d[7]),
      "+f"(d[8]), "+f"(d[9]), "+f"(d[10]), "+f"(d[11]), "+f"(d[12]), "+f"(d[13]), "+f"(d[14]), "+f"(d[15]),
      "+f"(d[16]), "+f"(d[17]), "+f"(d[18]), "+f"(d[19]), "+f"(d[20]), "+f"(d[21]), "+f"(d[22]), "+f"(d[23]),
      "+f"(d[24]), "+f"(d[25]), "+f"(d[26]), "+f"(d[27]), "+f"(d[28]), "+f"(d[29]), "+f"(d[30]), "+f"(d[31]),
      "+f"(d[32]), "+f"(d[33]), "+f"(d[34]), "+f"(d[35]), "+f"(d[36]), "+f"(d[37]), "+f"(d[38]), "+f"(d[39]),
      "+f"(d[40]), "+f"(d[41]), "+f"(d[42]), "+f"(d[43]), "+f"(d[44]), "+f"(d[45]), "+f"(d[46]), "+f"(d[47]),
      "+f"(d[48]), "+f"(d[49]), "+f"(d[50]), "+f"(d[51]), "+f"(d[52]), "+f"(d[53]), "+f"(d[54]), "+f"(d[55]),
      "+f"(d[56]), "+f"(d[57]), "+f"(d[58]), "+f"(d[59]), "+f"(d[60]), "+f"(d[61]), "+f"(d[62]), "+f"(d[63])
    : "r"(da), "r"(db), "r"(scale_d), "n"(HA), "n"(HB));
}
template <uint32_t HB = 0x40000040u>
__device__ __forceinline__ void wg_rs64(float* d, uint32_t a0, uint32_t a1, uint32_t a2, uint32_t a3, uint32_t db, int scale_d) {
  asm volatile("{\n.reg .pred p;\n.reg .b64 dB;\nmov.b64 dB, {%36, %38};\nsetp.ne.b32 p, %37, 0;\n"
    "wgmma.mma_async.sync.aligned.m64n64k16.f32.bf16.bf16 "
    "{%0, %1, %2, %3, %4, %5, %6, %7, %8, %9, %10, %11, %12, %13, %14, %15, "
    "%16, %17, %18, %19, %20, %21, %22, %23, %24, %25, %26, %27, %28, %29, %30, %31}, "
    "{%32, %33, %34, %35}, dB, p, 1, 1, 0;\n}\n"
    : "+f"(d[0]), "+f"(d[1]), "+f"(d[2]), "+f"(d[3]), "+f"(d[4]), "+f"(d[5]), "+f"(d[6]), "+f"(d[7]),
      "+f"(d[8]), "+f"(d[9]), "+f"(d[10]), "+f"(d[11]), "+f"(d[12]), "+f"(d[13]), "+f"(d[14]), "+f"(d[15]),
      "+f"(d[16]), "+f"(d[17]), "+f"(d[18]), "+f"(d[19]), "+f"(d[20]), "+f"(d[21]), "+f"(d[22]), "+f"(d[23]),
      "+f"(d[24]), "+f"(d[25]), "+f"(d[26]), "+f"(d[27]), "+f"(d[28]), "+f"(d[29]), "+f"(d[30]), "+f"(d[31])
    : "r"(a0), "r"(a1), "r"(a2), "r"(a3), "r"(db), "r"(scale_d), "n"(HB));
}
template <uint32_t HB = 0x40000040u>
__device__ __forceinline__ void wg_rs64_z(float* d, uint32_t a0, uint32_t a1, uint32_t a2, uint32_t a3, uint32_t db) {
  asm volatile("{\n.reg .pred p;\n.reg .b64 dB;\nmov.b64 dB, {%36, %37};\nsetp.ne.b32 p, 0, 0;\n"
    "wgmma.mma_async.sync.aligned.m64n64k16.f32.bf16.bf16 "
    "{%0, %1, %2, %3, %4, %5, %6, %7, %8, %9, %10, %11, %12, %13, %14, %15, "
    "%16, %17, %18, %19, %20, %21, %22, %23, %24, %25, %26, %27, %28, %29, %30, %31}, "
    "{%32, %33, %34, %35}, dB, p, 1, 1, 0;\n}\n"
    : "=f"(d[0]), "=f"(d[1]), "=f"(d[2]), "=f"(d[3]), "=f"(d[4]), "=f"(d[5]), "=f"(d[6]), "=f"(d[7]),
      "=f"(d[8]), "=f"(d[9]), "=f"(d[10]), "=f"(d[11]), "=f"(d[12]), "=f"(d[13]), "=f"(d[14]), "=f"(d[15]),
      "=f"(d[16]), "=f"(d[17]), "=f"(d[18]), "=f"(d[19]), "=f"(d[20]), "=f"(d[21]), "=f"(d[22]), "=f"(d[23]),
      "=f"(d[24]), "=f"(d[25]), "=f"(d[26]), "=f"(d[27]), "=f"(d[28]), "=f"(d[29]), "=f"(d[30]), "=f"(d[31])
    : "r"(a0), "r"(a1), "r"(a2), "r"(a3), "r"(db), "n"(HB));
}
template <uint32_t HB = 0x40000040u>
__device__ __forceinline__ void wg_rs32(float* d, uint32_t a0, uint32_t a1, uint32_t a2, uint32_t a3, uint32_t db, int scale_d) {
  asm volatile("{\n.reg .pred p;\n.reg .b64 dB;\nmov.b64 dB, {%20, %22};\nsetp.ne.b32 p, %21, 0;\n"
    "wgmma.mma_async.sync.aligned.m64n32k16.f32.bf16.bf16 "
    "{%0, %1, %2, %3, %4, %5, %6, %7, %8, %9, %10, %11, %12, %13, %14, %15}, "
    "{%16, %17, %18, %19}, dB, p, 1, 1, 0;\n}\n"
    : "+f"(d[0]), "+f"(d[1]), "+f"(d[2]), "+f"(d[3]), "+f"(d[4]), "+f"(d[5]), "+f"(d[6]), "+f"(d[7]),
      "+f"(d[8]), "+f"(d[9]), "+f"(d[10]), "+f"(d[11]), "+f"(d[12]), "+f"(d[13]), "+f"(d[14]), "+f"(d[15])
    : "r"(a0), "r"(a1), "r"(a2), "r"(a3), "r"(db), "r"(scale_d), "n"(HB));
}
template <uint32_t HB = 0x40000040u>
__device__ __forceinline__ void wg_rs32_z(float* d, uint32_t a0, uint32_t a1, uint32_t a2, uint32_t a3, uint32_t db) {
  asm volatile("{\n.reg .pred p;\n.reg .b64 dB;\nmov.b64 dB, {%20, %21};\nsetp.ne.b32 p, 0, 0;\n"
    "wgmma.mma_async.sync.aligned.m64n32k16.f32.bf16.bf16 "
    "{%0, %1, %2, %3, %4, %5, %6, %7, %8, %9, %10, %11, %12, %13, %14, %15}, "
    "{%16, %17, %18, %19}, dB, p, 1, 1, 0;\n}\n"
    : "=f"(d[0]), "=f"(d[1]), "=f"(d[2]), "=f"(d[3]), "=f"(d[4]), "=f"(d[5]), "=f"(d[6]), "=f"(d[7]),
      "=f"(d[8]), "=f"(d[9]), "=f"(d[10]), "=f"(d[11]), "=f"(d[12]), "=f"(d[13]), "=f"(d[14]), "=f"(d[15])
    : "r"(a0), "r"(a1), "r"(a2), "r"(a3), "r"(db), "n"(HB));
}
template <uint32_t HB = 0x40000040u>
__device__ __forceinline__ void wg_rs40t(float* d, uint32_t a0, uint32_t a1, uint32_t a2, uint32_t a3, uint32_t db, int scale_d) {
  asm volatile("{\n.reg .pred p;\n.reg .b64 dB;\nmov.b64 dB, {%24, %26};\nsetp.ne.b32 p, %25, 0;\n"
    "wgmma.mma_async.sync.aligned.m64n40k16.f32.bf16.bf16 "
    "{%0, %1, %2, %3, %4, %5, %6, %7, %8, %9, %10, %11, %12, %13, %14, %15, "
    "%16, %17, %18, %19}, "
    "{%20, %21, %22, %23}, dB, p, 1, 1, 1;\n}\n"
    : "+f"(d[0]), "+f"(d[1]), "+f"(d[2]), "+f"(d[3]), "+f"(d[4]), "+f"(d[5]), "+f"(d[6]), "+f"(d[7]),
      "+f"(d[8]), "+f"(d[9]), "+f"(d[10]), "+f"(d[11]), "+f"(d[12]), "+f"(d[13]), "+f"(d[14]), "+f"(d[15]),
      "+f"(d[16]), "+f"(d[17]), "+f"(d[18]), "+f"(d[19])
    : "r"(a0), "r"(a1), "r"(a2), "r"(a3), "r"(db), "r"(scale_d), "n"(HB));
}
template <uint32_t HB = 0x40000040u>
__device__ __forceinline__ void wg_rs40t_z(float* d, uint32_t a0, uint32_t a1, uint32_t a2, uint32_t a3, uint32_t db) {
  asm volatile("{\n.reg .pred p;\n.reg .b64 dB;\nmov.b64 dB, {%24, %25};\nsetp.ne.b32 p, 0, 0;\n"
    "wgmma.mma_async.sync.aligned.m64n40k16.f32.bf16.bf16 "
    "{%0, %1, %2, %3, %4, %5, %6, %7, %8, %9, %10, %11, %12, %13, %14, %15, "
    "%16, %17, %18, %19}, "
    "{%20, %21, %22, %23}, dB, p, 1, 1, 1;\n}\n"
    : "=f"(d[0]), "=f"(d[1]), "=f"(d[2]), "=f"(d[3]), "=f"(d[4]), "=f"(d[5]), "=f"(d[6]), "=f"(d[7]),
      "=f"(d[8]), "=f"(d[9]), "=f"(d[10]), "=f"(d[11]), "=f"(d[12]), "=f"(d[13]), "=f"(d[14]), "=f"(d[15]),
      "=f"(d[16]), "=f"(d[17]), "=f"(d[18]), "=f"(d[19])
    : "r"(a0), "r"(a1), "r"(a2), "r"(a3), "r"(db), "n"(HB));
}

constexpr uint32_t SOFF = 1024;
constexpr int STG = 57344, QE = 28672, SL_W = 16384, SL_HD = 12288, SL_F = 3 * STG, X_ST = 131072;
__host__ __device__ constexpr int kv_off(int h, int b) { return 16384 + h * 81920 + (b ^ (6 * h)) * 8192; }
__host__ __device__ constexpr int qo_off(int h, int qb) { return (qb >> 1) * 81920 + h * 8192 + (qb & 1) * 4096; }
__host__ __device__ constexpr int wo_off(int st) { return 16384 + st * 32768 + (st >> 1) * 16384; }
constexpr int OFF_ONES = 4 * STG;
constexpr int OFF_PATCH = OFF_ONES + 1024;
constexpr int OFF_CS = OFF_PATCH + 768;
constexpr int OFF_BAR = OFF_CS + 768;
constexpr int OFF_MISC = OFF_BAR + 416;
constexpr int SMEM_BYTES = OFF_MISC + 96;
enum { B_FULL = 0, B_EMPTY = 6, B_HALO = 12, B_CS = 15, B_KVREADY, B_QDONE = B_KVREADY + 2, B_QREADY, B_OST, B_ADONE = B_OST + 2,
       B_QFREE, B_WS, B_WFULL, B_WEMPTY = B_WFULL + 4, B_GU = B_WEMPTY + 4, B_RES = B_GU + 2, B_DN,
       B_HX = B_DN + 2, B_RST, B_E23, B_UNIT, B_COUNT = B_UNIT + 8 };
static_assert(B_COUNT <= 52, "barrier area");
__host__ __device__ constexpr int bar_count(int i) {
  return i >= B_EMPTY && i < B_HALO ? 17 : i == B_CS ? 5 : i == B_QFREE ? 16
       : i == B_KVREADY || i == B_KVREADY + 1 || i == B_QREADY || i == B_E23 ? 8 : i == B_ADONE ? 32 : i == B_OST ? 2 : i >= B_UNIT ? 4
       : i == B_QDONE || (i >= B_WEMPTY && i < B_GU) ? 16 : i == B_RST ? 4 : i == B_RES ? 2 : 1;
}
enum { M_KEY = 0, M_MEAN, M_INV, M_WSUM, M_TAG, M_SEL0, M_PMEAN, M_PINV, M_XQ = 8, M_KEYS = 12, M_PROG = 20 };
constexpr int FFN_PIECE = 14336;
constexpr int T_XS = 163840, T_HP = T_XS + 1024;
constexpr float LSUM_MIN = 5.421010862427522e-20f, LSUM_MAX = 1.8446744073709552e19f;
constexpr float SM_C = 0.17677669529663687f * 1.4426950408889634f;
constexpr uint32_t VSTEP = 64u - (64u << 16);
#define WS1_PACE 1000
#define WS_AT 5
#define WS_PACE 1000
#define GUB_PACE 800
#define ULIST1 0x854
#define ULIST2 0x8721
#define SOLO 1
#define HID_H 1
#define PRE_N 2
#define P1_DELAY 800
#define AB_AT 2
#define B_AT1 0
#define B_AT2 4
#define B_AT3 8
#define RES_K 6
#define X_STAGGER 500
#define GU_PACE1 1600
#define GU_PACE 2500
#define DELAY_P 600
#define DELAY_S 2400
#define DELAY_Y 400

struct Params {
  CUtensorMap mapA[2], mapW, mapWo, mapRes[2], mapXst[2], mapG, mapU, mapD, mapWs;
  const bf16 *x, *wqkv, *wo, *w_r, *w_g, *w_u, *w_d;
  bf16* out;
};

template <int N> __device__ __forceinline__ void exp_pack(const float* s, uint32_t* p) {
#pragma unroll
  for (int b = 0; b < N; b++) {
    p[2 * b] = pack_bf16(ex2(s[4 * b]), ex2(s[4 * b + 1]));
    p[2 * b + 1] = pack_bf16(ex2(s[4 * b + 2]), ex2(s[4 * b + 3]));
  }
}
template <int KIND> __device__ __forceinline__ void edge16(const float* sd, const float* st, uint32_t* pd, uint32_t* pt, int dl, uint32_t mt) {
  if (KIND == 0) { exp_pack<2>(sd, pd); pt[0] = pt[1] = pt[2] = pt[3] = 0; }
  else if (KIND == 1) { exp_pack<2>(st, pt); pd[0] = pd[1] = pd[2] = pd[3] = 0; }
  else {
    const uint32_t a = pack_bf16(ex2(dl >= 0 ? sd[0] : st[0]), ex2(dl >= 1 ? sd[1] : st[1]));
    const uint32_t c = pack_bf16(ex2(dl >= 0 ? sd[6] : st[6]), ex2(dl >= 1 ? sd[7] : st[7]));
    pd[0] = a & ~mt; pt[0] = a & mt; pd[3] = c & ~mt; pt[3] = c & mt;
    pd[1] = pack_bf16(ex2(sd[2]), ex2(sd[3])); pt[1] = 0;
    pt[2] = pack_bf16(ex2(st[4]), ex2(st[5])); pd[2] = 0;
  }
}
__device__ __forceinline__ void edge32(const float* sd, const float* st, uint32_t* pd, uint32_t* pt, int rel, int dl, uint32_t mt) {
  if (rel > 1) { edge16<0>(sd, st, pd, pt, dl, mt); edge16<0>(sd + 8, st + 8, pd + 4, pt + 4, dl, mt); }
  else if (rel == 1) { edge16<0>(sd, st, pd, pt, dl, mt); edge16<2>(sd + 8, st + 8, pd + 4, pt + 4, dl, mt); }
  else if (rel == 0) { edge16<2>(sd, st, pd, pt, dl, mt); edge16<1>(sd + 8, st + 8, pd + 4, pt + 4, dl, mt); }
  else { edge16<1>(sd, st, pd, pt, dl, mt); edge16<1>(sd + 8, st + 8, pd + 4, pt + 4, dl, mt); }
}
__device__ __forceinline__ void qk64(float* s, const uint32_t* qf, uint32_t kd) {
  wg_rs64_z<H64>(s, qf[0], qf[1], qf[2], qf[3], kd);
  wg_rs64<H64>(s, qf[4], qf[5], qf[6], qf[7], kd + 2, 1);
}
__device__ __forceinline__ void qk32x2(float* a, float* b, const uint32_t* qf, uint32_t ka, uint32_t kb) {
  wg_rs32_z<H64>(a, qf[0], qf[1], qf[2], qf[3], ka); wg_rs32_z<H64>(b, qf[0], qf[1], qf[2], qf[3], kb);
  wg_rs32<H64>(a, qf[4], qf[5], qf[6], qf[7], ka + 2, 1); wg_rs32<H64>(b, qf[4], qf[5], qf[6], qf[7], kb + 2, 1);
}
__device__ __forceinline__ void pv32(float* o, const uint32_t* p, uint32_t vd) {
  wg_rs40t<H64>(o, p[0], p[1], p[2], p[3], vd, 1);
  wg_rs40t<H64>(o, p[4], p[5], p[6], p[7], vd + VSTEP, 1);
}

__device__ __forceinline__ void fma8(float* d, uint4 w, float x) {
  d[0] += x * bf_lo(w.x); d[1] += x * bf_hi(w.x); d[2] += x * bf_lo(w.y); d[3] += x * bf_hi(w.y);
  d[4] += x * bf_lo(w.z); d[5] += x * bf_hi(w.z); d[6] += x * bf_lo(w.w); d[7] += x * bf_hi(w.w);
}

__device__ __forceinline__ int fresh_tid() { int r; asm volatile("mov.u32 %0, %%tid.x;" : "=r"(r)); return r; }
__device__ __forceinline__ int fresh_bid() { int r; asm volatile("mov.u32 %0, %%ctaid.x;" : "=r"(r)); return r; }
#define PHASE_IDS                                                                                                              \
  const uint32_t sbase = smem_u32(smem);                                                                                       \
  const int tid = fresh_tid(), bid = fresh_bid();                                                                              \
  const int warp = __shfl_sync(0xffffffffu, tid >> 5, 0), lane = tid & 31;                                                     \
  const int rank = bid & 1, cl = bid >> 1, rb = bid & 7, hp = bid >> 3;                  \
  const int mb = 2 * rb + (hp >> 3), nb = hp & 7;                                            \
  const int wg = warp >> 2, wi = warp & 3, g = lane >> 2, q = lane & 3;                                                        \
  const int mi = lane >> 3, srow = wi * 16 + (mi & 1) * 8 + (lane & 7);      \
  auto bar = [&](int i) { return sbase + OFF_BAR + 8 * i; };                                                                   \
  volatile uint32_t* s_misc = (volatile uint32_t*)(smem + OFF_MISC);                                                           \
  auto load_w = [&](int s, int kt) {                           \
    tma_load3_mc(sbase + s * QE + SL_W + rank * 6144, &P.mapW, hp * 64, kt * 32 + rank * 16, 0, bar(B_FULL + s));              \
  };                                                                                                                           \
  auto load_a = [&](int s, int kt, int layer) { mbar_expect_tx(bar(B_FULL + s), QE); tma_load2(sbase + s * QE, &P.mapA[layer], kt * 32, rb * 256, bar(B_FULL + s)); }; \
  auto load_wo = [&](int k) {                                                 \
    mbar_expect_tx(bar(B_WFULL + (k & 3)), 32768);                                                                             \
    tma_load3_mc(sbase + wo_off(k & 3) + 16384 + rank * 8192, &P.mapWo, nb * 128 + rank * 64, (k >> 3) * 32, (k & 7) * 2, bar(B_WFULL + (k & 3))); \
  };                                                                                                                           \
  auto load_o = [&](int k) {                                                            \
    bulk_load_h(sbase + wo_off(k & 3), g_o + (size_t)(mb * 16 + k) * 16384, 16384, bar(B_WFULL + (k & 3)), policy_evict_first());                    \
  };                                                                                                                           \
  auto load_res = [&](int half, int layer) {      \
    mbar_expect_tx(bar(B_RES), 16384);                                                                                         \
    tma_load2_h(sbase + qo_off(half, 0), &P.mapRes[layer], nb * 128 + half * 64, mb * 128, bar(B_RES), policy_evict_first());  \
    tma_load2_h(sbase + qo_off(half, 2), &P.mapRes[layer], nb * 128 + half * 64, mb * 128 + 64, bar(B_RES), policy_evict_first()); \
  };                                                                                                                           \
  auto store_tile = [&](int layer, int skip, bool wait) {                                           \
    _Pragma("unroll 1")                                                                                                        \
    for (int j = 0; j < 4; j++)                                                                                                \
      if ((j & 1) != skip) tma_store(&P.mapXst[layer], sbase + X_ST + (j & 1) * 16384 + (j >> 1) * 8192, nb * 128 + (j >> 1) * 64, mb * 128 + (j & 1) * 64); \
    bulk_commit();                                                                                                             \
    if (wait) bulk_wait_all();                                                                                                 \
  };                                                                                                                           \
  auto load_ws = [&](int pace) {                                    \
    mbar_expect_tx(bar(B_WS), 4 * SL_HD);                                                                                      \
    _Pragma("unroll 1")                                                                                                        \
    for (int j = 0; j < 4; j++) {                                                                                              \
      tma_load3(sbase + SL_F + j * SL_HD, &P.mapWs, hp * 64, rb * 128 + j * 32, 0, bar(B_WS));                                 \
      if (pace) spin_cycles(pace);                                                                                             \
    }                                                                                                                          \
  };                                                                                                                           \
  auto load_gu = [&](int half, int pace) {                             \
    mbar_expect_tx(bar(B_GU + half), 4 * FFN_PIECE);                                                                           \
    _Pragma("unroll 1")                                                                                                        \
    for (int j = 0; j < 4; j++) {                                                                                              \
      tma_load2_h(sbase + SL_F + j * FFN_PIECE, &P.mapG + (j >> 1), cl * 56, rank * 512 + half * 256 + (j & 1) * 128, bar(B_GU + half), policy_evict_first()); \
      if (j < 3) spin_cycles(pace);                                                                                            \
    }                                                                                                                          \
  };                                                                                                                           \
  auto fetch_gu = [&](uint32_t* a, int ks, int ct) {                 \
    ldsm_x4_t(sbase + SL_F + (mi & 1) * 2 * FFN_PIECE + (ks * 16 + (mi >> 1) * 8 + (lane & 7)) * 112 + ct * 16, a[0], a[1], a[2], a[3]); \
  };                                                                                                                           \
  auto send_gu = [&](float gate, float up, int ct, int part) {        \
    const int u = 8 * ct + g, own = u >= 28;                                                                                   \
    if (q == 0) st_async2(mapa(sbase + T_HP + ((rank * 5 + part) * 28 + u - 28 * own) * 8, own), gate, up, mapa(bar(B_HX), own)); \
  };                                                                                                                           \
  auto hidden = [&]() {                                     \
    const float2* hpart = (const float2*)(smem + T_HP) + min(lane, 27);                                                        \
    float gs[2] = {0.f, 0.f}, us[2] = {0.f, 0.f};                                                                              \
    _Pragma("unroll")                                                                                                          \
    for (int j = 0; j < 10; j++) { const float2 v = hpart[j * 28]; gs[j & 1] += v.x; us[j & 1] += v.y; }                       \
    const float gb = rbf(gs[0] + gs[1]), ub = rbf(us[0] + us[1]);                                                              \
    return lane < 28 ? rbf(__fdividef(gb, 1.f + __expf(-gb))) * ub : 0.f;                                                      \
  };                                                                                                                           \
  (void)load_wo; (void)load_o; (void)load_res; (void)store_tile; (void)fetch_gu; (void)load_ws; (void)load_gu; (void)send_gu; (void)hidden; (void)cl; (void)mb; (void)nb; (void)wg; (void)g; (void)q; (void)srow; (void)s_misc; (void)load_w; (void)load_a;

__global__ void __launch_bounds__(512, 1) mega_kernel(const __grid_constant__ Params P) {
  extern __shared__ __align__(1024) uint8_t smem[];
  {
    PHASE_IDS
    if (warp == 0) {
      if (lane == 0) {
        prefetch_tmap(&P.mapA[0]); prefetch_tmap(&P.mapW);
#pragma unroll
        for (int i = 0; i < 6; i++) mbar_init(bar(B_FULL + i), 1);
        asm volatile("fence.mbarrier_init.release.cluster;" ::: "memory");
      }
      __syncwarp();
#pragma unroll 1
      for (int i = 0; i < SOLO; i++) {
        load_a(i, i, 0);
        tma_load3(sbase + i * QE + SL_W, &P.mapW, hp * 64, i * 32, 0, bar(B_FULL + i));
        tma_load3(sbase + i * QE + SL_W + 6144, &P.mapW, hp * 64, i * 32 + 16, 0, bar(B_FULL + i));
      }
      load_a(SOLO, SOLO, 0);
    } else if (tid == 32) {
#pragma unroll
      for (int i = 6; i < B_COUNT; i++) mbar_init(bar(i), bar_count(i));
      asm volatile("fence.mbarrier_init.release.cluster;" ::: "memory");
    } else if (warp == 8) {
      ((uint4*)(smem + OFF_ONES))[lane] = make_uint4(0x3F803F80u, 0x3F803F80u, 0x3F803F80u, 0x3F803F80u);
      ((uint4*)(smem + OFF_ONES))[lane + 32] = make_uint4(0x3F803F80u, 0x3F803F80u, 0x3F803F80u, 0x3F803F80u);
    }
    __syncwarp();
    cluster_arrive(); cluster_wait();
    if (warp == 0) {
      PROFL(0, 1);
      load_w(SOLO, SOLO);
#pragma unroll 1
      for (int i = SOLO + 1; i < PRE_N; i++) { load_a(i, i, 0); load_w(i, i); }
    } else if (tid == 96) {
      if ((sbase & 0x3FFFF) != SOFF) __trap();
    }
    __syncwarp();
  }

  regs_dec<120>();
#pragma unroll 1
  for (unsigned pass_v = 0;;) {
    const unsigned pass = __shfl_sync(0xffffffffu, pass_v, 0);
    if (__shfl_sync(0xffffffffu, fresh_tid() >> 8, 0)) {
      if (pass > 0) {
        const unsigned layer = pass - 1;
        uint32_t xr[32];
        {
          PHASE_IDS
          float acc[64];
#pragma unroll
          for (int i = 0; i < 64; i++) acc[i] = 0.f;
          const uint32_t da0 = dlo(SOFF, 16) + (wg - 2) * 256;
          constexpr uint32_t db0 = dlo(SOFF + 16384, 8192);
#pragma unroll 1
          for (int k4 = 0; k4 < 4; k4++) {
#pragma unroll
            for (int st = 0; st < 4; st++) {
              mbar_wait(bar(B_WFULL + st), k4 & 1);
              wg_fence();
#pragma unroll
              for (int kk = 0; kk < 4; kk++)
                wg_ss128t<H64, H128>(acc, da0 + (wo_off(st) >> 4) + (kk >> 1) * 512 + (kk & 1) * 2, db0 + (wo_off(st) >> 4) + kk * 128, 1);
              wg_commit();
              if (st == 0 && k4 == 0 && warp == 9) PROF(10);
              if (warp == 9) STEPT(16 + k4 * 4 + st);
              wg_wait<1>();
              if (lane < 2 && (st == 0 ? k4 > 0 : (st < 3 || k4 < 3))) mbar_arrive_cluster(bar(B_WEMPTY + ((st + 3) & 3)), lane);
            }
          }
          mbar_wait(bar(B_RES), layer);
          mbar_wait(bar(B_RST), layer);
          const uint32_t zoff = qo_off(0, (wg - 2) * 2);
#pragma unroll
          for (int j = 0; j < 8; j++)
            ldsm_x4(sbase + zoff + srow * 128 + (j >> 2) * 8192 + ((((2 * j + (mi >> 1)) & 7) ^ (srow & 7)) << 4), xr[4 * j], xr[4 * j + 1], xr[4 * j + 2], xr[4 * j + 3]);
          wg_wait<0>();
          fence_regs<64>(acc);
          if (warp == 9) PROF(11);
          if (layer == 0 && lane < 2) mbar_arrive_cluster(bar(B_QFREE), lane);
#pragma unroll
          for (int j = 0; j < 32; j++) xr[j] = hadd_bf2(xr[j], pack_bf16(acc[2 * j], acc[2 * j + 1]));
        }
        PHASE_IDS
        const uint32_t tag = s_misc[M_TAG];
        const int grow = mb * 128 + (warp - 8) * 16 + g;
        {
          float d[6][4];
#pragma unroll
          for (int i = 0; i < 6; i++) d[i][0] = d[i][1] = d[i][2] = d[i][3] = 0.f;
          const uint4* tab = (const uint4*)(smem + OFF_PATCH + (g == 1 ? q * 64 : (g == 0 ? 256 : 320)));
#pragma unroll
          for (int j2 = 0; j2 < 4; j2++) {
            const uint4 w = tab[j2];
#pragma unroll
            for (int jj = 0; jj < 2; jj++) {
              const uint32_t* a = &xr[8 * j2 + 4 * jj];
              mma_16816(d[jj], a[0], a[1], a[2], a[3], jj ? w.z : w.x, jj ? w.w : w.y);
              mma_16816(d[2 + jj], a[0], a[1], a[2], a[3], a[0], a[2]);
              mma_16816(d[4 + jj], a[0], a[1], a[2], a[3], a[1], a[3]);
            }
          }
          const float sq0 = __shfl_sync(0xffffffffu, (g & 1) ? d[2][1] + d[3][1] : d[2][0] + d[3][0], g * 4 + (g >> 1));
          const float sq1 = __shfl_sync(0xffffffffu, (g & 1) ? d[4][3] + d[5][3] : d[4][2] + d[5][2], g * 4 + (g >> 1));
          uint4* dst = &g_part[layer][nb * SEQ + grow];
          if (q == 0) {
            st_relaxed4(dst, make_uint4(__float_as_uint(d[0][0] + d[1][0]), __float_as_uint(sq0), __float_as_uint(d[0][1] + d[1][1]), tag));
            st_relaxed4(dst + 8, make_uint4(__float_as_uint(d[0][2] + d[1][2]), __float_as_uint(sq1), __float_as_uint(d[0][3] + d[1][3]), tag));
          }
        }
        if (warp == 9) PROF(12);
        asm volatile("bar.arrive 6, 320;" ::: "memory");
        const int t_p = (int)clock();
        const uint32_t zrow = sbase + X_ST + (wg - 2) * 16384 + srow * 128;
        named_bar(5, 256);
#pragma unroll
        for (int j = 0; j < 8; j++)
          stsm_x4(zrow + (j >> 2) * 8192 + ((((2 * j + (mi >> 1)) & 7) ^ (srow & 7)) << 4), xr[4 * j], xr[4 * j + 1], xr[4 * j + 2], xr[4 * j + 3]);
        if (layer == 0) {
          fence_async_smem();
          asm volatile("bar.arrive 8, 288;" ::: "memory");
        }
#pragma unroll 1
        while ((int)clock() - t_p < DELAY_P) {}
        {
          const uint4* src = &g_part[layer][2 * q * SEQ + grow];
          uint4 pp[4];
          uint32_t spins = 0;
#pragma unroll 1
          do {
            pp[0] = ld_relaxed4(src); pp[1] = ld_relaxed4(src + SEQ); pp[2] = ld_relaxed4(src + 8); pp[3] = ld_relaxed4(src + SEQ + 8);
          } while (!__all_sync(0xffffffffu, pp[0].w == tag && pp[1].w == tag && pp[2].w == tag && pp[3].w == tag) && ++spins < SPIN_LIMIT);
          if (warp == 9) PROF(13);
          const int rr = q >> 1;
          float s3[3];
#pragma unroll
          for (int c = 0; c < 3; c++) {
            const float lo = __uint_as_float(c == 0 ? pp[0].x : c == 1 ? pp[0].y : pp[0].z) + __uint_as_float(c == 0 ? pp[1].x : c == 1 ? pp[1].y : pp[1].z);
            const float hi = __uint_as_float(c == 0 ? pp[2].x : c == 1 ? pp[2].y : pp[2].z) + __uint_as_float(c == 0 ? pp[3].x : c == 1 ? pp[3].y : pp[3].z);
            s3[c] = (rr ? hi : lo) + __shfl_xor_sync(0xffffffffu, rr ? lo : hi, 2);
            s3[c] += __shfl_xor_sync(0xffffffffu, s3[c], 1);
          }
          const float mu = s3[0] * (1.f / DM), var = fmaxf(fmaf(-mu, mu, s3[1] * (1.f / DM)), 0.f);
          const float mn = rbf(mu), iv = ln_inv(var);
          const uint32_t ky = router_key(rbf((s3[2] - mn * __uint_as_float(s_misc[M_WSUM])) * iv), grow + 8 * rr);
          const uint32_t wbest = __reduce_max_sync(0xffffffffu, ky);
          s_misc[M_KEYS + warp - 8] = wbest;
          named_bar(5, 256);
          if (__reduce_max_sync(0xffffffffu, s_misc[M_KEYS + (lane & 7)]) == wbest) {
            if (nb == 0 && ky == wbest && (q & 1) == 0) st_relaxed4(&g_slot[layer][mb * 8], make_uint4(ky, __float_as_uint(mn), __float_as_uint(iv), tag));
            const int r = ~wbest & 15;
            if ((r & 7) == g) {
#pragma unroll
              for (int j = 0; j < 4; j++) {
                const uint32_t* a = &xr[8 * j];
                st_relaxed4(&g_cand[layer][mb * 128 + nb * 16 + q * 4 + j],
                            r < 8 ? make_uint4(a[0], a[2], a[4], a[6]) : make_uint4(a[1], a[3], a[5], a[7]));
              }
            }
            __syncwarp();
          }
          if (warp == 9) PROF(14);
          if (layer == 0) {
            if ((q & 1) == 0) {
              g_rowln[nb][grow + 8 * rr] = make_float2(mn, iv);
              if (warp - 8 == nb) {
                const float mu2 = mu + (mu - mn) * iv, inv2 = ln_inv(var * (1.f + iv) * (1.f + iv));
                st_relaxed4(&g_rowab[1][grow + 8 * rr], make_uint4(__float_as_uint((1.f + iv) * inv2), __float_as_uint((mn * iv + rbf(mu2)) * inv2), tag, 0));
              }
            }
            __syncwarp();
          } else {
            const uint32_t m2 = pack_bf16(mn, mn);
            uint8_t* row = smem + X_ST + (wg - 2) * 16384 + (q & 1) * 8192 + (wi * 16 + g + 8 * rr) * 128;
#pragma unroll 2
            for (int j = 0; j < 8; j++) {
              uint4* c = (uint4*)(row + (((j + lane) & 7) << 4));
              const uint4 v = *c;
              *c = make_uint4(add_ln_pair(v.x, m2, iv), add_ln_pair(v.y, m2, iv), add_ln_pair(v.z, m2, iv), add_ln_pair(v.w, m2, iv));
            }
            fence_async_smem();
          }
          if (warp == 15) asm volatile("bar.arrive 7, 512;" ::: "memory");
        }
        if (warp < 15) {
          uint32_t gu[64];
          mbar_wait(bar(B_GU + 1), layer);
#pragma unroll
          for (int j = 0; j < 16; j++) fetch_gu(gu + 4 * j, j, warp - 8);
          fence_async_smem();
          float d[4][4] = {};
          named_bar(7, 512);
#pragma unroll
          for (int hf = 0; hf < 2; hf++) {
            uint4 xv[4] = {};
            if (g == 0) {
#pragma unroll
              for (int j = 0; j < 4; j++) xv[j] = ((const uint4*)(smem + T_XS))[32 + hf * 16 + j * 4 + q];
            }
            __syncwarp();
#pragma unroll
            for (int j = 0; j < 4; j++) {
              const uint32_t* a = gu + hf * 32 + j * 8;
              mma_16816(d[(j & 1) * 2], a[0], a[1], a[2], a[3], xv[j].x, xv[j].y);
              mma_16816(d[(j & 1) * 2 + 1], a[4], a[5], a[6], a[7], xv[j].z, xv[j].w);
            }
          }
          send_gu((d[0][0] + d[1][0]) + (d[2][0] + d[3][0]), (d[0][2] + d[1][2]) + (d[2][2] + d[3][2]), warp - 8, 4);
          __syncwarp();
        }
        if (layer == 0) asm volatile("bar.arrive 9, 512;" ::: "memory");
        else {
        uint32_t wd[64];
        mbar_wait(bar(B_DN), layer);
#pragma unroll
        for (int j = 0; j < 16; j++) {
          const uint32_t row = sbase + wo_off(0) + ((warp - 8) * 2 + (j >> 3)) * 3584 + min((j & 1) * 16 + (mi >> 1) * 8 + (lane & 7), 27) * 128;
          ldsm_x4_t(row + ((((j & 6) + (mi & 1)) ^ ((row >> 7) & 7)) << 4), wd[4 * j], wd[4 * j + 1], wd[4 * j + 2], wd[4 * j + 3]);
        }
        fence_regs_u<64>(wd);
        uint32_t hf[4];
        if (HID_H) {
          named_bar(10, 288);
          *(uint4*)hf = *(const uint4*)(smem + OFF_PATCH + 256 + q * 16);
        } else {
          mbar_wait_cluster(bar(B_HX), layer);
          const float hv = hidden();
          const uint32_t hp2 = pack_bf16(hv, __shfl_down_sync(0xffffffffu, hv, 1));
#pragma unroll
          for (int j = 0; j < 4; j++) hf[j] = __shfl_sync(0xffffffffu, hp2, 8 * j + 2 * q);
        }
        if (warp == 9) PROF(19);
        float y[4][4] = {};
#pragma unroll
        for (int j = 0; j < 16; j++)
          mma_16816(y[j & 3], wd[4 * j], wd[4 * j + 1], wd[4 * j + 2], wd[4 * j + 3], g == j >> 1 ? hf[(j & 1) * 2] : 0u, g == j >> 1 ? hf[(j & 1) * 2 + 1] : 0u);
        {
          float e[4];
#pragma unroll
          for (int c = 0; c < 4; c++) { const int i = (c & 1) * 2 + (c >> 1); e[c] = (y[0][i] + y[1][i]) + (y[2][i] + y[3][i]); }
          const bool b0 = g & 1, b1 = g & 2;
          float t0 = __shfl_xor_sync(0xffffffffu, b0 ? e[0] : e[1], 4), t1 = __shfl_xor_sync(0xffffffffu, b0 ? e[2] : e[3], 4);
          const float f0 = b0 ? t0 : e[0], f1 = b0 ? e[1] : t0, f2 = b0 ? t1 : e[2], f3 = b0 ? e[3] : t1;
          t0 = __shfl_xor_sync(0xffffffffu, b1 ? f0 : f2, 8); t1 = __shfl_xor_sync(0xffffffffu, b1 ? f1 : f3, 8);
          st_relaxed4(&g_ypart[layer][bid * 256 + (warp - 8) * 32 + (q * 4 + (g & 3)) * 2 + (g >> 2)],
                      b1 ? make_uint4(__float_as_uint(t0), __float_as_uint(t1), __float_as_uint(f2), __float_as_uint(f3)) : make_uint4(__float_as_uint(f0), __float_as_uint(f1), __float_as_uint(t0), __float_as_uint(t1)));
        }
        if (warp == 9) PROF(20);
        asm volatile("bar.arrive 9, 384;" ::: "memory");
        cluster_arrive(); cluster_wait();
        return;
        }
      }
      const unsigned layer = pass;
      named_bar(1 + (fresh_tid() >> 7), 128);
      regs_inc<224>();
      float acc[2][96];
      float pa[2][2], pb[2][2];
      {
        PHASE_IDS
        const uint32_t da0 = dlo(SOFF, 16) + (wg - 2) * 256;
        constexpr uint32_t db0 = dlo(SOFF + SL_W, 2048);
        if (warp == 9) PROF(19 - 2 * layer);
        mbar_wait(bar(B_FULL), 0);
        if (warp == 9) PROF(29);
        if (warp == 9) STEPT(0);
        wg_fence();
        wg_ss192t_z<H64, H128>(acc[0], da0, db0); wg_ss192t_z<H64, H128>(acc[1], da0 + 512, db0);
        wg_ss192t<H64, H128>(acc[0], da0 + 2, db0 + 384, 1); wg_ss192t<H64, H128>(acc[1], da0 + 514, db0 + 384, 1);
        wg_commit();
        int s = 1, u = 0;
#pragma unroll 1
        for (int i = 1; i < 28; i++) {
          const uint32_t da = da0 + s * (QE >> 4), db = db0 + s * (QE >> 4);
          mbar_wait(bar(B_FULL + s), (u + (s > 1 ? layer : 0)) & 1);
          if (warp == 9 && !(i & 1)) STEPT(i >> 1);
          wg_fence();
          wg_ss192t<H64, H128>(acc[0], da, db, 1); wg_ss192t<H64, H128>(acc[1], da + 512, db, 1);
          wg_ss192t<H64, H128>(acc[0], da + 2, db + 384, 1); wg_ss192t<H64, H128>(acc[1], da + 514, db + 384, 1);
          wg_commit();
          wg_wait<1>();
          if (lane < 2 && i < 27) mbar_arrive_cluster(bar(B_EMPTY + (s == 0 ? 5 : s - 1)), lane);
          if (++s == 6) { s = 0; u++; }
        }
      }
      PHASE_IDS
      auto last_tile = [&](int m, int j) {
        const int e = (4 + j) % 6;
        const uint32_t da = dlo(SOFF, 16) + (wg - 2) * 256 + e * (QE >> 4) + m * 512, db = dlo(SOFF + SL_W, 2048) + e * (QE >> 4);
        wg_fence();
        wg_ss192t<H64, H128>(acc[m], da, db, 1);
        wg_ss192t<H64, H128>(acc[m], da + 2, db + 384, 1);
      };
      {
        mbar_wait(bar(B_CS), layer);
        const uint32_t tag = s_misc[M_TAG];
        const uint4* src = &g_rowab[layer][rb * 256 + (wg - 2 + (lane >> 4) * 2) * 64 + wi * 16 + (lane & 15)];
        uint4 v;
#pragma unroll
        for (int j = 0; j < 4; j++) {
          if (j == AB_AT) v = ld_relaxed4(src);
          mbar_wait(bar(B_FULL + (4 + j) % 6), j < 2 ? layer : 1);
          last_tile(1, j);
          if (j == 0) { wg_commit(); wg_wait<1>(); mbar_arrive_e(bar(B_E23)); }
        }
        wg_commit();
        last_tile(0, 0);
        wg_commit();
        if (warp != 9) STEPT(4);
#pragma unroll 1
        for (uint32_t spins = 0; !__all_sync(0xffffffffu, v.z == tag) && spins < SPIN_LIMIT; spins++) v = ld_relaxed4(src);
#pragma unroll
        for (int j = 0; j < 4; j++) {
          pa[j >> 1][j & 1] = __uint_as_float(__shfl_sync(0xffffffffu, v.x, g + 8 * j));
          pb[j >> 1][j & 1] = __uint_as_float(__shfl_sync(0xffffffffu, v.y, g + 8 * j));
        }
        if (warp != 9) STEPT(5);
      }
      const int prow = (int)s_misc[M_SEL0] - rb * 256;
      const float4* cs = (const float4*)(smem + OFF_CS) + q;
      auto finish = [&](int m, int b, float2 c, uint32_t* dst) {
        dst[0] = pack_bf16(acc[m][4 * b] * pa[m][0] - c.x * pb[m][0], acc[m][4 * b + 1] * pa[m][0] - c.y * pb[m][0]);
        dst[1] = pack_bf16(acc[m][4 * b + 2] * pa[m][1] - c.x * pb[m][1], acc[m][4 * b + 3] * pa[m][1] - c.y * pb[m][1]);
      };
      auto grp = [](int n) { return n < 8 ? 4 + ((n >> 1) & 1) * 4 + (n >> 2) * 2 + (n & 1) : n - 8; };
      float4 cq[2] = {cs[grp(0) * 4], cs[grp(1) * 4]};
      auto next = [&](int m, int n, uint32_t* r) {
        if (m == 1 && (n == B_AT1 || n == B_AT2 || n == B_AT3)) { last_tile(0, n == B_AT1 ? 1 : n == B_AT2 ? 2 : 3); wg_commit(); }
        const float4 c = cq[n & 1];
        cq[n & 1] = cs[grp((n + 2) % 12) * 4];
        finish(m, 2 * grp(n), make_float2(c.x, c.y), r); finish(m, 2 * grp(n) + 1, make_float2(c.z, c.w), r + 2);
      };
#pragma unroll
      for (int m = 1; m >= 0; m--) {
        if (m == 1) {
          wg_wait<1>();
          fence_regs<96>(acc[1]);
          mbar_wait(bar(B_E23), layer);
          if (warp != 9) STEPT(0);
        } else {
          wg_wait<0>();
          fence_regs<96>(acc[0]);
          if (warp != 9) STEPT(1);
          if (lane < 2) mbar_arrive_cluster(bar(B_QDONE), lane);
          if (warp == 9) PROF(2);
        }
        const int qb = wg - 2 + 2 * m;
#pragma unroll
        for (int jj = 0; jj < 8; jj++) {
          const int h = jj >> 2;
          uint32_t r[4];
          next(m, jj, r);
          if (m == 0 && jj == 0) named_bar(5, 256);
          stsm_x4(sbase + kv_off(h, 4 + 2 * m) + (wg - 2) * 8192 + ((jj >> 1) & 1) * 4096 + srow * 64 + ((((jj & 1) * 2 + (mi >> 1)) ^ ((srow >> 1) & 3)) << 4),
                  r[0], r[1], r[2], r[3]);
        }
        const bool patch = prow >> 4 == qb * 4 + wi;
        if (patch) {
          __syncwarp();
          if (lane < 16)
            *(uint4*)(smem + kv_off(g >> 1, 4 + qb) + (g & 1) * 4096 + (prow & 63) * 64 + ((q ^ ((prow >> 1) & 3)) << 4)) =
                *(const uint4*)(smem + OFF_PATCH + 128 + (g & 1) * 128 + (g >> 1) * 64 + q * 16);
        }
        fence_async_smem();
        __syncwarp();
        mbar_arrive_e(bar(B_KVREADY + 1 - m));
        if (warp != 9) STEPT(3 - m);
        pa[m][0] *= SM_C; pa[m][1] *= SM_C; pb[m][0] *= SM_C; pb[m][1] *= SM_C;
#pragma unroll
        for (int jj = 0; jj < 4; jj++) {
          uint32_t r[4];
          next(m, 8 + jj, r);
          *(uint4*)(smem + qo_off(jj >> 1, 2 * m) + (warp - 8) * 1024 + (jj & 1) * 512 + lane * 16) = make_uint4(r[0], r[1], r[2], r[3]);
        }
        __syncwarp();
        if (patch) {
          *(uint32_t*)(smem + qo_off(lane >> 4, 2 * m) + (warp - 8) * 1024 + (mi & 1) * 512 + ((prow & 7) * 4 + q) * 16 + ((g & 1) * 2 + ((prow >> 3) & 1)) * 4) =
              *(const uint32_t*)(smem + OFF_PATCH + lane * 4);
          __syncwarp();
        }
      }
      if (warp == 9) PROF(3);
      mbar_arrive_e(bar(B_QREADY));
      regs_dec<120>();
    } else {
      if (pass > 0) {
        const unsigned layer = pass - 1;
        PHASE_IDS
        const uint32_t tag = s_misc[M_TAG];
        if (warp == 7) {
              uint32_t* tab = (uint32_t*)(smem + OFF_PATCH);
#pragma unroll
              for (int j = 0; j < 2; j++) { const int w = lane + 32 * j; tab[(w & 3) * 16 + (w >> 2)] = ((const uint32_t*)P.w_r)[nb * 64 + w]; }
              tab[64 + lane] = lane < 16 ? 0x3F803F80u : 0u;
              float tot = 0.f;
#pragma unroll 1
              for (int j = 0; j < 4; j++) {
                const uint4 u = ((const uint4*)P.w_r)[lane + 32 * j];
                tot += bf_lo(u.x) + bf_hi(u.x) + bf_lo(u.y) + bf_hi(u.y) + bf_lo(u.z) + bf_hi(u.z) + bf_lo(u.w) + bf_hi(u.w);
              }
              s_misc[M_WSUM] = __float_as_uint(warp_sum(tot));
        }
              if (layer == 1) {
                const float2 ln = g_rowln[nb][mb * 128 + tid - 128];
                const uint32_t m2 = pack_bf16(ln.x, ln.x);
                uint8_t* row = smem + qo_off(0, wi & 2) + (tid & 63) * 128;
                mbar_wait(bar(B_RES), 1);
#pragma unroll 1
                for (int j = 0; j < 8; j++) {
                  uint4* c = (uint4*)(row + (((j + lane) & 7) << 4));
                  const uint4 v = c[0], w = c[512];
                  c[0] = make_uint4(add_ln_pair(v.x, m2, ln.y), add_ln_pair(v.y, m2, ln.y), add_ln_pair(v.z, m2, ln.y), add_ln_pair(v.w, m2, ln.y));
                  c[512] = make_uint4(add_ln_pair(w.x, m2, ln.y), add_ln_pair(w.y, m2, ln.y), add_ln_pair(w.z, m2, ln.y), add_ln_pair(w.w, m2, ln.y));
                }
                const int prow = (int)s_misc[M_SEL0] - mb * 128;
                __syncwarp();
                if (prow >> 5 == wi && lane < 16)
                  *(uint4*)(smem + qo_off(0, wi & 2) + (lane >> 3) * 8192 + (prow & 63) * 128 + (((lane ^ prow) & 7) << 4)) = poll4(&g_x2row[(nb * 16 + lane) * 2]);
                PROF(30);
              }
              __syncwarp();
              mbar_arrive_e(bar(B_RST));
        if (warp == 4) {
            named_bar(6, 320);
            spin_cycles(DELAY_S);
            uint4 c, u0, u1;
            uint32_t u2, best = 0, spins = 0;
            int src;
#pragma unroll 1
            for (;;) {
              src = (~best & 0x7FFu) >> 7;
              const uint4* xsel = &g_cand[layer][src * 128];
              c = ld_relaxed4(&g_slot[layer][(lane & 15) * 8]);
              u0 = ld_relaxed4(xsel + rank * 64 + lane); u1 = ld_relaxed4(xsel + rank * 64 + 32 + lane);
              u2 = ld_relaxed((const uint32_t*)(xsel + (bid >> 4) * 16 + q * 4) + (bid & 15));
              const uint32_t prev = best;
              best = __reduce_max_sync(0xffffffffu, c.w == tag ? c.x : 0u);
              if ((__all_sync(0xffffffffu, c.w == tag && valid4(u0) && valid4(u1) && u2 != SENT) && best == prev) || ++spins > SPIN_LIMIT) break;
            }
            const float sel_m = __uint_as_float(__shfl_sync(0xffffffffu, c.y, src)), sel_inv = __uint_as_float(__shfl_sync(0xffffffffu, c.z, src));
            const uint32_t m2 = pack_bf16(sel_m, sel_m);
            uint4* xs = (uint4*)(smem + T_XS) + (lane & 16) + q * 4 + (g & 3);
            xs[0] = make_uint4(ln_pair(u0.x, m2, sel_inv), ln_pair(u0.y, m2, sel_inv), ln_pair(u0.z, m2, sel_inv), ln_pair(u0.w, m2, sel_inv));
            xs[32] = make_uint4(ln_pair(u1.x, m2, sel_inv), ln_pair(u1.y, m2, sel_inv), ln_pair(u1.z, m2, sel_inv), ln_pair(u1.w, m2, sel_inv));
            s_misc[M_KEY] = best; s_misc[M_MEAN] = __float_as_uint(sel_m); s_misc[M_INV] = __float_as_uint(sel_inv);
            s_misc[M_XQ + q] = u2;
            PROF(16);
        }
        if (layer == 1) {
          named_bar(7, 512);
          const int sel = SEQ - 1 - (int)(s_misc[M_KEY] & 0x7FFFu), skip = sel >> 7 == mb ? (sel >> 6) & 1 : -1;
          if (warp == 7) store_tile(1, skip, false);
          if (HID_H && warp == 4) {
            mbar_wait_cluster(bar(B_HX), 1);
            ((bf16*)(smem + OFF_PATCH + 256))[((lane >> 1) & 3) * 8 + (lane >> 3) * 2 + (lane & 1)] = __float2bfloat16_rn(hidden());
            asm volatile("bar.arrive 10, 288;" ::: "memory");
          }
#pragma unroll 1
          for (int c = tid - 128; c < 1024 && skip >= 0; c += 128) {
            const int r = c >> 4;
            if (r != (sel & 63))
              *(uint4*)(P.out + (size_t)(mb * 128 + skip * 64 + r) * DM + nb * 128 + (c & 15) * 8) =
                  *(const uint4*)(smem + X_ST + skip * 16384 + ((c >> 3) & 1) * 8192 + r * 128 + (((c ^ r) & 7) << 4));
          }
          __syncwarp();
        } else asm volatile("bar.arrive 7, 512;" ::: "memory");
        if (warp == 5 && layer == 0) {
              named_bar(8, 288);
              if (nb > 0) spin_cycles(X_STAGGER);
              store_tile(0, -1, true);
              set_flag(&g_xflag[mb][nb].v[0], tag);
              PROF(17);
              poll_flag(&g_xflag[2 * rb + (lane & 1)][0].v[0], tag);
              fence_async_global();
#pragma unroll 1
              for (int i = 0; i < 4; i++) load_a(i, i, 1);
              PROFL(1, 1);
        }
      }
      named_bar(1 + (fresh_tid() >> 7), 128);
      regs_dec<32>();
#pragma unroll 1
      for (;;) {
      const unsigned pass = __shfl_sync(0xffffffffu, pass_v, 0);
      if (pass > 0) {
        const unsigned layer = pass - 1;
        PHASE_IDS
        const uint32_t tag = s_misc[M_TAG], bkey = s_misc[M_KEY];
        const int sel = SEQ - 1 - (int)(bkey & 0x7FFFu);
        if (warp == 3) {
          if (layer == 1) {
#pragma unroll
            for (int j = 0; j < 3; j++) ((uint4*)g_vw)[bid * 96 + j * 32 + lane] = make_uint4(0, 0, 0, 0);
          } else s_misc[M_SEL0] = sel;
          if (bid == 0 && lane == 0) g_sel[layer] = sel;
        }
        __syncwarp();
        if (layer == 0) {
          auto load_down = [&](int j) {
            mbar_expect_tx(bar(B_DN + j), 2 * FFN_PIECE);
            bulk_load_h(sbase + SL_F + j * 2 * FFN_PIECE, P.w_d + (size_t)(bid * 28 + j * 14) * DM, 2 * FFN_PIECE, bar(B_DN + j), policy_evict_first());
          };
          if (warp == 5) {
            poll_flag(&g_xflag[2 * rb + (lane & 1)][(lane >> 1) & 7].v[0], tag);
            fence_async_global();
            load_a(4, 4, 1); load_a(5, 5, 1);
          }
          float hv = 0.f;
          if (wg == 1) { mbar_wait_cluster(bar(B_HX), 0); hv = rbf(hidden()); fence_regs<1>(&hv); }
          named_bar(9, 512);
          if (warp == 0) {
            fence_async_smem();
            if (lane < 16) mbar_arrive_cluster(bar(B_QFREE), lane & 1);
            mbar_wait(bar(B_QFREE), 1);
            load_w(4, 4); load_w(5, 5);
            load_down(0);
          } else if (wg == 1) {
            if (warp == 4) { mbar_wait(bar(B_DN), 0); load_down(1); }
            float d[8] = {0.f, 0.f, 0.f, 0.f, 0.f, 0.f, 0.f, 0.f};
#pragma unroll 1
            for (int j = 0; j < 28; j += 2) {
              if (j == 0 || j == 14) mbar_wait(bar(B_DN + (j > 0)), 0);
              const uint4 w0 = *(const uint4*)(smem + SL_F + j * 2048 + (tid - 128) * 16), w1 = *(const uint4*)(smem + SL_F + j * 2048 + 2048 + (tid - 128) * 16);
              fma8(d, w0, __shfl_sync(0xffffffffu, hv, j));
              fma8(d, w1, __shfl_sync(0xffffffffu, hv, j + 1));
            }
            uint4* dst = &g_ypart[0][bid * 256 + (tid - 128) * 2];
            st_relaxed4(dst, make_uint4(__float_as_uint(d[0]), __float_as_uint(d[1]), __float_as_uint(d[2]), __float_as_uint(d[3])));
            st_relaxed4(dst + 1, make_uint4(__float_as_uint(d[4]), __float_as_uint(d[5]), __float_as_uint(d[6]), __float_as_uint(d[7])));
            asm volatile("bar.arrive 11, 160;" ::: "memory");
            PROF(20);
          } else if (warp == 2) {
            named_bar(11, 160);
            fence_async_smem();
            load_ws(WS1_PACE);
          }
        } else {
          if (wg == 1) named_bar(9, 384);
          cluster_arrive();
        }
        if (wg == 1) {
          const int t_y = (int)clock();
          const uint32_t xw = s_misc[M_XQ + ((lane & 7) >> 1)];
          const float x = (lane & 1) ? bf_hi(xw) : bf_lo(xw);
          float xn = rbf(rbf(x - __uint_as_float(s_misc[M_MEAN])) * __uint_as_float(s_misc[M_INV]));
          uint32_t u = bkey & 0xFFFF0000u;
          u = (u & 0x80000000u) ? (u & 0x7FFFFFFFu) : (~u & 0xFFFF0000u);
          float sg = rbf(__fdividef(1.f, 1.f + __expf(-__uint_as_float(u))));
          uint32_t* dst = (layer == 0 ? (uint32_t*)&g_x2row[bid * 2] : (uint32_t*)(P.out + (size_t)sel * DM + bid * 8)) + (lane >> 1);
          asm volatile("" : "+f"(xn), "+f"(sg), "+l"(dst));
#pragma unroll 1
          while ((int)clock() - t_y < DELAY_Y) {}
          const uint4* src = &g_ypart[layer][((tid - 128) >> 1) * 256 + bid * 2 + (tid & 1)];
          uint4 v, w;
          uint32_t spins = 0;
#pragma unroll 1
          do { v = ld_relaxed4(src); w = ld_relaxed4(src + 64 * 256); } while (!__all_sync(0xffffffffu, valid4(v) && valid4(w)) && ++spins < SPIN_LIMIT);
          float a[4] = {__uint_as_float(v.x) + __uint_as_float(w.x), __uint_as_float(v.y) + __uint_as_float(w.y),
                        __uint_as_float(v.z) + __uint_as_float(w.z), __uint_as_float(v.w) + __uint_as_float(w.w)};
          const bool b1 = lane & 2, b2 = lane & 4;
          float c0 = (b1 ? a[1] : a[0]) + __shfl_xor_sync(0xffffffffu, b1 ? a[0] : a[1], 2);
          float c1 = (b1 ? a[3] : a[2]) + __shfl_xor_sync(0xffffffffu, b1 ? a[2] : a[3], 2);
          float y = (b2 ? c1 : c0) + __shfl_xor_sync(0xffffffffu, b2 ? c0 : c1, 4);
          y += __shfl_xor_sync(0xffffffffu, y, 8);
          y += __shfl_xor_sync(0xffffffffu, y, 16);
          float* red = (float*)(smem + OFF_PATCH);
          red[wi * 8 + (lane & 1) * 4 + ((lane >> 1) & 3)] = y;
          named_bar(2, 128);
          if (warp == 4) {
            PROF(21);
            y = (red[lane & 7] + red[8 + (lane & 7)]) + (red[16 + (lane & 7)] + red[24 + (lane & 7)]);
            const float res = x + rbf(xn + rbf(rbf(y) * sg));
            const uint32_t pr = pack_bf16(res, __shfl_down_sync(0xffffffffu, res, 1));
            if (lane < 8 && (lane & 1) == 0) st_relaxed(dst, pr);
            PROF(22);
          }
        }
        if (pass == 2) {
          if (bid == 0 && tid == 128) g_epoch = tag;
          bulk_wait_all();
          __syncwarp();
          cluster_wait();
          return;
        }
      }
      const unsigned layer = pass;
      if (__shfl_sync(0xffffffffu, fresh_tid() >> 5, 0) > 1 - (int)layer) {
        PHASE_IDS
        uint4* xrow = (uint4*)(smem + SL_F + 4 * SL_HD);
        if (wg == 1) {
          if (layer == 0) {
            xrow[tid - 128] = make_uint4(0x3F803F80u, 0x3F803F80u, 0x3F803F80u, 0x3F803F80u);
            if (warp == 5) {
              mbar_wait(bar(B_FULL + WS_AT), 0);
              if (lane == 0) {
#pragma unroll 1
                for (int i = 11; i > 0; i--) prefetch_tmap(&P.mapA[0] + i);
              }
              __syncwarp();
              load_ws(WS_PACE);
            }
          } else xrow[tid - 128] = poll4(&g_x2row[(tid - 128) * 2]);
          PROF(23);
        }
        named_bar(12, 192 + 32 * layer);
        if (warp == 1) {
          float mean = 0.f;
#pragma unroll 1
          for (int pass2 = 0; pass2 < 2; pass2++) {
            float acc = 0.f;
#pragma unroll 1
            for (int j = lane; j < 128; j += 32) {
              const uint4 v = xrow[j];
              const uint32_t w[4] = {v.x, v.y, v.z, v.w};
#pragma unroll
              for (int c = 0; c < 4; c++) {
                const float d0 = bf_lo(w[c]) - mean, d1 = bf_hi(w[c]) - mean;
                acc += pass2 ? d0 * d0 + d1 * d1 : d0 + d1;
              }
            }
            acc = warp_sum(acc) * (1.f / DM);
            if (pass2 == 0) mean = acc;
            else { s_misc[M_PMEAN] = __float_as_uint(rbf(mean)); s_misc[M_PINV] = __float_as_uint(ln_inv(acc)); }
          }
        } else {
          mbar_wait(bar(B_WS), layer);
          const uint8_t* wa = smem + SL_F + (g >> 1) * SL_HD + ((warp - 2) >> 1) * 4096 + (g & 1) * 2048;
          const uint32_t* xs = (const uint32_t*)xrow + rb * 64 + g * 8;
          const int ch = (warp & 1) * 4 + q;
          float d[8] = {0.f, 0.f, 0.f, 0.f, 0.f, 0.f, 0.f, 0.f};
#pragma unroll 1
          for (int j0 = 0; j0 < 16; j0 += 2) {
            const int j = j0 ^ ((g & 1) * 4);
            const uint4 w0 = *(const uint4*)(wa + j * 128 + (((ch ^ j) & 7) << 4)), w1 = *(const uint4*)(wa + j * 128 + 128 + (((ch ^ (j + 1)) & 7) << 4));
            const uint32_t xx = xs[j >> 1];
            fma8(d, w0, bf_lo(xx)); fma8(d, w1, bf_hi(xx));
          }
#pragma unroll
          for (int c = 0; c < 4; c++) d[c] = ((g & 4) ? d[c + 4] : d[c]) + __shfl_xor_sync(0xffffffffu, (g & 4) ? d[c] : d[c + 4], 16);
#pragma unroll
          for (int c = 0; c < 2; c++) d[c] = ((g & 2) ? d[c + 2] : d[c]) + __shfl_xor_sync(0xffffffffu, (g & 2) ? d[c] : d[c + 2], 8);
          d[0] = ((g & 1) ? d[1] : d[0]) + __shfl_xor_sync(0xffffffffu, (g & 1) ? d[0] : d[1], 4);
          st_relaxed(&g_vw[layer][rb][((warp - 2) >> 1) * DM + hp * 64 + ch * 8 + g], enc(d[0]));
        }
        named_bar(12, 192 + 32 * layer);
        PROF(24);
      }
      PHASE_IDS
      if (wg == 0) {
        if (warp == 0) {
          if (layer == 0) {
#pragma unroll 1
            for (int i = PRE_N; i < 6; i++) { load_a(i, i, 0); load_w(i, i); }
          }
          int s = 0, u = 0;
#pragma unroll 1
          for (int i = 6; i < 32; i++) {
            if (layer == 1) mbar_arrive_e(bar(B_EMPTY + s));
            mbar_wait(bar(B_EMPTY + s), (u + (s > 1 ? 0 : layer)) & 1);
            load_w(s, i);
            load_a(s, i, layer);
            if (++s == 6) { s = 0; u++; }
          }
        } else if (warp == 1) {
          if (layer == 0) {
            const uint32_t tag = ld_relaxed(&g_epoch) + 1;
            if (lane < 16) g_rowab[0][rb * 256 + hp * 16 + lane] = make_uint4(0, 0, 0, 0);
            float shift = 0.f, sum = 0.f, sq = 0.f;
            const int r = hp * 16 + (lane >> 1);
#pragma unroll 1
            for (int i = 0; i < 32; i++) {
              mbar_wait(bar(B_FULL + i % 6), (i / 6) & 1);
              const uint8_t* base = smem + (i % 6) * QE + r * 64 + (lane & 1) * 32;
              uint4 v[2];
#pragma unroll
              for (int j = 0; j < 2; j++) v[j] = *(const uint4*)(base + ((j ^ ((r >> 1) & 1)) << 4));
              if (i == 0) shift = __shfl_sync(0xffffffffu, bf_lo(v[0].x), lane & ~1);
#pragma unroll
              for (int j = 0; j < 2; j++) {
                const uint32_t w[4] = {v[j].x, v[j].y, v[j].z, v[j].w};
#pragma unroll
                for (int c = 0; c < 4; c++) {
                  const float d0 = bf_lo(w[c]) - shift, d1 = bf_hi(w[c]) - shift;
                  sum += d0 + d1; sq = fmaf(d0, d0, fmaf(d1, d1, sq));
                }
              }
              fence_async_smem();
              __syncwarp();
              if (i < 26) mbar_arrive_e(bar(B_EMPTY + i % 6));
            }
            sum += __shfl_xor_sync(0xffffffffu, sum, 1); sq += __shfl_xor_sync(0xffffffffu, sq, 1);
            const float dm = sum * (1.f / DM), var = fmaxf(sq * (1.f / DM) - dm * dm, 0.f), mean = shift + dm;
            const float inv = ln_inv(var);
            if ((lane & 1) == 0) st_relaxed4(&g_rowab[0][rb * 256 + r], make_uint4(__float_as_uint(inv), __float_as_uint(rbf(mean) * inv), tag, 0));
          }
          if (rb == 0) {
            mbar_wait(bar(B_QDONE), layer);
#pragma unroll 1
            for (int j = lane; j < 512; j += 32) ((uint4*)(smem + kv_off(1, 0)))[j] = make_uint4(0, 0, 0, 0);
            fence_async_smem();
            __syncwarp();
            if (lane < 3) mbar_arrive(bar(B_HALO + lane));
          }
        } else if (warp == 3) {
          fence_async_smem();
          load_gu(0, layer ? GU_PACE1 : GU_PACE);
          PROF(27);
        } else {
          const uint4 sent = make_uint4(SENT, SENT, SENT, SENT), zero = make_uint4(0, 0, 0, 0);
          if (layer == 0) {
            const int f = lane >> 1;
            Flag* fl = f < 2 ? &g_kvflag[rb >> 1][hp][f] : f < 4 ? &g_oflag[rb][f & 1][hp] : &g_xflag[mb][nb];
            if (f < 5 && (f >= 2 || (rank == 1 && rb < 7))) ((uint4*)fl)[lane & 1] = zero;
          }
#pragma unroll 1
          for (int t = lane; t < 128; t += 32) {
            g_ypart[layer][bid * 256 + t] = sent; g_ypart[layer][bid * 256 + 128 + t] = sent;
            g_part[layer][nb * SEQ + mb * 128 + t] = zero;
            if (t < 16) g_cand[layer][mb * 128 + nb * 16 + t] = sent;
            else if (t < 18) { if (nb == 0) g_slot[layer][mb * 8 + t - 16] = zero; }
            else if (t < 20) { if (layer == 0) g_x2row[bid * 2 + t - 18] = sent; }
          }
          __syncwarp();
          mbar_arrive_e(bar(B_CS));
        }
        __syncwarp();
        uint8_t* kvg = g_kv + (size_t)(((rb - 1 + rank) >> 1) * 16 + hp) * 65536;
        if (warp == 3) {
          if (rb > 0) { mbar_expect_tx(bar(B_HALO), 16384); mbar_expect_tx(bar(B_HALO + 1), 16384); mbar_expect_tx(bar(B_HALO + 2), 32768); }
        } else if (rank == 0) {
          if (warp == 0) {
            mbar_wait(bar(B_QDONE), layer);
#pragma unroll 1
            for (int j = 0; j < 4; j++) {
              mbar_wait(bar(B_KVREADY + (j >> 1)), layer);
              bulk_push(mapa(sbase + kv_off(j & 1, 2 - (j & 2)), 1), sbase + kv_off(j & 1, 6 - (j & 2)), 16384, mapa(bar(B_HALO + min(j, 2)), 1));
            }
          } else if (rb > 0) {
            const int p = warp - 1;
            mbar_wait(bar(B_QREADY), layer);
            if (p) spin_cycles(P1_DELAY);
            poll_flag(&g_kvflag[(rb - 1) >> 1][hp][p].v[layer], s_misc[M_TAG]);
            fence_async_global();
#pragma unroll 1
            for (int h = 0; h < 2; h++) bulk_load_h(sbase + kv_off(h, 2 - 2 * p), kvg + (p * 2 + h) * 16384, 16384, bar(B_HALO + (p ? 2 : h)), policy_evict_first());
            if (p == 0) PROF(5);
          }
        } else if (warp < 2 && rb < 7) {
          mbar_wait(bar(B_KVREADY + warp), layer);
          if (warp == 1) named_bar(13, 64);
#pragma unroll 1
          for (int h = 0; h < 2; h++) bulk_store(kvg + (warp * 2 + h) * 16384, sbase + kv_off(h, 6 - 2 * warp), 16384);
          bulk_commit();
          bulk_wait_all();
          if (warp == 0) asm volatile("bar.arrive 13, 64;" ::: "memory");
          set_flag(&g_kvflag[rb >> 1][hp][warp].v[layer], s_misc[M_TAG]);
          if (warp == 0) PROF(4);
        }
      } else {
        const int t = tid - 128, go = (t >> 5) * DM + hp * 64 + (t & 31) * 2;
        if (layer == 0 && t == 96) { s_misc[M_TAG] = ld_relaxed(&g_epoch) + 1; s_misc[M_SEL0] = 0xFFFFFFFFu; s_misc[M_PROG] = s_misc[M_PROG + 1] = 0; }
        if ((layer == 0 || (int)s_misc[M_SEL0] >> 8 == rb) && warp < 7) {
          spin_cycles(layer ? 300 : 1500);
          uint2 w[8];
          uint32_t spins = 0;
          bool ok;
#pragma unroll 1
          do {
            ok = true;
#pragma unroll
            for (int j = 0; j < 8; j++) w[j] = ld_relaxed2(&g_vw[layer][j][go]);
#pragma unroll
            for (int j = 0; j < 8; j++) ok = ok && w[j].x && w[j].y;
          } while (!__all_sync(0xffffffffu, ok) && ++spins < SPIN_LIMIT);
          float s0 = 0.f, s1 = 0.f;
#pragma unroll
          for (int j = 0; j < 8; j++) { s0 += dec(w[j].x); s1 += dec(w[j].y); }
          float2* csp = (float2*)(smem + OFF_CS) + (t & ~7) + (t & 3) * 2 + ((t >> 2) & 1);
          if (layer == 0) *csp = make_float2(s0, s1);
          else {
            const float2 c = *csp;
            const float a = __uint_as_float(s_misc[M_PINV]) * (warp == 4 ? SM_C : 1.f), b = __uint_as_float(s_misc[M_PMEAN]) * a;
            ((uint32_t*)(smem + OFF_PATCH))[t] = pack_bf16(s0 * a - c.x * b, s1 * a - c.y * b);
          }
          PROF(25);
        }
        __syncwarp();
        mbar_arrive_e(bar(B_CS));
      }
      __syncwarp();
      if (wi == 0) mbar_wait(bar(B_QREADY), layer);
      named_bar(1 + (fresh_tid() >> 7), 128);
      if (__shfl_sync(0xffffffffu, fresh_tid() >> 7, 0) == 0) {
        regs_inc<152>();
        uint32_t gu[112];
        {
          PHASE_IDS
          const uint32_t tag = s_misc[M_TAG];
          mbar_wait(bar(B_GU), layer);
#pragma unroll
          for (int j = 0; j < 28; j++) fetch_gu(gu + 4 * j, warp * 4 + (j & 3), j >> 2);
          fence_async_smem();
          named_bar(1, 128);
          if (warp == 0) {
            mbar_wait(bar(B_ADONE), layer);
#pragma unroll 1
            for (int k = 2; k < 16; k++) {
#pragma unroll 1
              for (uint32_t spins = 0; (int)s_misc[M_PROG + (k >> 3)] <= (k & 7) + 16 * (int)layer && spins < SPIN_LIMIT; spins++) {}
              if (k >= 4) mbar_wait(bar(B_WEMPTY + (k & 3)), ((k >> 2) - 1 + ((k & 2) ? layer : 0)) & 1);
              load_o(k); load_wo(k);
              STEPT(16 + k);
              if (k == RES_K) { mbar_wait(bar(B_OST + 1), layer); load_res(1, layer); }
            }
            if (layer == 1) {
              mbar_wait(bar(B_WEMPTY + 1), 1);
              mbar_expect_tx(bar(B_DN), 4 * FFN_PIECE);
              tma_load3_h(sbase + wo_off(0), &P.mapD, 0, bid * 28, 0, bar(B_DN), policy_evict_first());
            }
            named_bar(6, 320);
            if (layer == 0) {
              mbar_wait(bar(B_QFREE), 0);
#pragma unroll 1
              for (int i = 0; i < 4; i++) load_w(i, i);
            } else tma_load3_h(sbase + wo_off(0) + 2 * FFN_PIECE, &P.mapD, 0, bid * 28, 8, bar(B_DN), policy_evict_first());
          } else if (warp < 3) {
            const int h = warp - 1;
#pragma unroll 1
            for (int qb = 3; qb >= 0; qb--) {
              mbar_wait(bar(B_UNIT + h * 4 + 3 - qb), layer);
              bulk_store(g_o + (size_t)((((rb * 2 + (qb >> 1)) * 2 + h) * 16 + hp) * 2 + (qb & 1)) * 4096, sbase + qo_off(h, qb), 4096);
            }
            bulk_commit();
            if (h == 0 && lane < 2) mbar_arrive_cluster(bar(B_OST), lane);
            bulk_wait_all();
            if (h == 1) mbar_arrive_e(bar(B_OST + 1));
            set_flag(&g_oflag[rb][h][hp].v[layer], tag);
            PROF(28 + 3 * h);
            if (h == 0) { load_res(0, layer); mbar_wait(bar(B_OST), layer); load_wo(0); load_wo(1); }
            int n = 0, first = h;
#pragma unroll 1
            for (uint32_t spins = 0; n < 8 && spins < SPIN_LIMIT; spins++) {
              n = (__ffs(__ballot_sync(0xffffffffu, ld_relaxed(&g_oflag[rb][h][lane & 15].v[layer]) != tag || lane == 16)) - 1) >> 1;
              asm volatile("fence.acquire.gpu;" ::: "memory");
              fence_async_global();
              if (!first && n >= 2) {
                first = 1;
                load_o(0); load_o(1);
                PROF(15);
              }
              s_misc[M_PROG + h] = n + 16 * layer;
            }
            if (h) PROF(26);
          } else {
            mbar_expect_tx(bar(B_HX), 2240);
            mbar_wait(bar(B_HALO + 2), layer);
            if (rb == 0) spin_cycles(2000);
            PROF(6);
            load_gu(1, GUB_PACE);
          }
        }
        PHASE_IDS
        uint4 xa = {}, xb = {};
        named_bar(7, 512);
        if (g == 0) { xa = ((const uint4*)(smem + T_XS))[warp * 8 + q]; xb = ((const uint4*)(smem + T_XS))[warp * 8 + 4 + q]; }
        __syncwarp();
        float d[7][4] = {};
#pragma unroll
        for (int j = 0; j < 28; j++) {
          const int ks = j / 7, ct = j % 7;
          const uint32_t* a = gu + ct * 16 + ks * 4;
          mma_16816(d[ct], a[0], a[1], a[2], a[3], ks == 0 ? xa.x : ks == 1 ? xa.z : ks == 2 ? xb.x : xb.z, ks == 0 ? xa.y : ks == 1 ? xa.w : ks == 2 ? xb.y : xb.w);
        }
#pragma unroll
        for (int ct = 0; ct < 7; ct++) send_gu(d[ct][0], d[ct][2], ct, warp);
        __syncwarp();
        if (warp == 2) PROF(18);
        regs_dec<32>();
        pass_v = pass + 1;
        continue;
      }
      break;
      }
      regs_inc<120>();
    }
    const unsigned layer = pass;
    {
      PHASE_IDS
      mbar_wait(bar(B_QREADY), layer);
      if (warp != 9) STEPT(7);
      const int bmin = rb == 0 ? 4 : 0;
      auto kdesc = [&](int h, int b) { const uint32_t v = dlo(SOFF, 16) + (kv_off(h, b) >> 4); return b < bmin ? dlo(SOFF + kv_off(1, 0), 16) : v; };
      auto vdesc = [&](int h, int b) {
        const uint32_t v = dlo(SOFF + 4096, OFF_ONES - 4096) + (kv_off(h, b) >> 10) * VSTEP;
        return b < bmin ? dlo(SOFF + kv_off(1, 0), 4096) : v;
      };
      const int units = wg == 3 ? 0x8630 : (wg == 2 ? ULIST2 : ULIST1);
      auto need = [&](int h, int b) { if (b == 3 || b == 1) mbar_wait(bar(B_HALO + (b == 1 ? 2 : h)), layer); };
      auto load_q = [&](uint32_t* qf, int u) {
        *(uint4*)&qf[0] = *(const uint4*)(smem + qo_off(u >> 2, ~u & 3) + wi * 1024 + lane * 16);
        *(uint4*)&qf[4] = *(const uint4*)(smem + qo_off(u >> 2, ~u & 3) + wi * 1024 + 512 + lane * 16);
      };
      auto store_o = [&](const float* o, int u) {
        const float i0 = rcp(o[16]), i1 = rcp(o[18]);
        if (u >= 4 && lane < 2) mbar_arrive_cluster(bar(B_ADONE), lane);
#pragma unroll
        for (int j = 0; j < 2; j++)
          stsm_x4(sbase + qo_off(u >> 2, ~u & 3) + srow * 64 + (((2 * j + (mi >> 1)) ^ ((srow >> 1) & 3)) << 4),
                  pack_bf16(o[8 * j] * i0, o[8 * j + 1] * i0), pack_bf16(o[8 * j + 2] * i1, o[8 * j + 3] * i1),
                  pack_bf16(o[8 * j + 4] * i0, o[8 * j + 5] * i0), pack_bf16(o[8 * j + 6] * i1, o[8 * j + 7] * i1));
        fence_async_smem();
        __syncwarp();
        mbar_arrive_e(bar(B_UNIT + u));
      };
      int redo = 0;
      {
        const int dl = g - 2 * q;
        const uint32_t mt = shl_clamp(0xFFFFFFFFu, max(16 * dl + 16, 0));
        uint32_t qf[8];
        float s[32];
        load_q(qf, units & 7);
        wg_fence();
        qk64(s, qf, kdesc((units >> 2) & 1, 6 - (units & 3)));
        wg_commit();
        wg_wait<0>();
        fence_regs<32>(s);
#pragma unroll 1
        for (int ul = units; ul != 8; ul >>= 4) {
          const int u = ul & 7, h = u >> 2, qb = 3 - (u & 3);
          float o[20];
          uint32_t p1[16], p2[16], p3[16], p4[16], p5[16];
          if (warp != 9) STEPT(8 + nu * 8);
          exp_pack<8>(s, p1);
          fence_regs_u<16>(p1);
          need(h, qb + 2);
          {
            float s2[32];
            const uint32_t vd = vdesc(h, qb + 3);
            wg_fence();
            qk64(s2, qf, kdesc(h, qb + 2));
            wg_commit();
            wg_rs40t_z<H64>(o, p1[0], p1[1], p1[2], p1[3], vd);
            wg_rs40t<H64>(o, p1[4], p1[5], p1[6], p1[7], vd + VSTEP, 1);
            pv32(o, p1 + 8, vd + 2 * VSTEP);
            wg_commit();
            wg_wait<1>();
            fence_regs<32>(s2);
            if (warp != 9) STEPT(9 + nu * 8);
            exp_pack<8>(s2, p2);
            fence_regs_u<16>(p2);
            wg_wait<0>();
            fence_regs<20>(o);
          }
          need(h, qb + 1);
          {
            float s3[32];
            wg_fence();
            qk64(s3, qf, kdesc(h, qb + 1));
            wg_commit();
            pv32(o, p2, vdesc(h, qb + 2)); pv32(o, p2 + 8, vdesc(h, qb + 2) + 2 * VSTEP);
            wg_commit();
            wg_wait<1>();
            fence_regs<32>(s3);
            if (warp != 9) STEPT(10 + nu * 8);
            exp_pack<8>(s3, p3);
            fence_regs_u<16>(p3);
            wg_wait<0>();
            fence_regs<20>(o);
          }
          need(h, qb);
          const uint32_t kd = kdesc(h, qb + 4), kt = kdesc(h, qb), vd = vdesc(h, qb + 4), vt = vdesc(h, qb);
          {
            float sd[16], st[16];
            wg_fence();
            qk32x2(sd, st, qf, kd, kt);
            wg_commit();
            pv32(o, p3, vdesc(h, qb + 1)); pv32(o, p3 + 8, vdesc(h, qb + 1) + 2 * VSTEP);
            wg_commit();
            wg_wait<1>();
            fence_regs<16>(sd); fence_regs<16>(st);
            if (warp != 9) STEPT(11 + nu * 8);
            edge32(sd, st, p4, p4 + 8, wi, dl, mt);
            fence_regs_u<16>(p4);
            wg_wait<0>();
            fence_regs<20>(o);
          }
          const int un = (ul >> 4) == 8 ? 4 : (ul >> 4) & 7;
          {
            float sd[16], st[16];
            wg_fence();
            qk32x2(sd, st, qf, kd + 128, kt + 128);
            wg_commit();
            pv32(o, p4, vd); pv32(o, p4 + 8, vt);
            wg_commit();
            wg_wait<1>();
            fence_regs<16>(sd); fence_regs<16>(st);
            load_q(qf, un);
            edge32(sd, st, p5, p5 + 8, wi - 2, dl, mt);
            fence_regs_u<16>(p5);
          }
          need(un >> 2, 6 - (un & 3));
          wg_fence();
          pv32(o, p5, vd + 2 * VSTEP); pv32(o, p5 + 8, vt + 2 * VSTEP);
          wg_commit();
          qk64(s, qf, kdesc(un >> 2, 6 - (un & 3)));
          wg_commit();
          wg_wait<1>();
          fence_regs<20>(o);
          if (warp != 9) STEPT(12 + nu * 8);
          const bool unsafe = !(o[16] >= LSUM_MIN && o[16] <= LSUM_MAX && o[18] >= LSUM_MIN && o[18] <= LSUM_MAX);
          if (__any_sync(0xffffffffu, unsafe)) redo |= 1 << u;
          else store_o(o, u);
          wg_wait<0>();
          fence_regs<32>(s);
        }
      }
      if (warp != 9) STEPT(31);
      if (bar_red_or(1 + wg, 128, redo)) {
#pragma unroll 1
        for (int ul = units; ul != 8; ul >>= 4) {
          const int u = ul & 7;
          if (!bar_red_or(1 + wg, 128, redo >> u & 1)) continue;
          const int h = u >> 2, qb = 3 - (u & 3);
          uint32_t qf[8], p[16];
          float o[20], m0 = -INFINITY, m1 = -INFINITY;
          load_q(qf, u);
#pragma unroll
          for (int i = 0; i < 20; i++) o[i] = 0.f;
#pragma unroll 1
          for (int j = 0; j <= (rb == 0 ? qb : 4); j++) {
            const int b = qb + 4 - j;
            float s[32];
            wg_fence();
            qk64(s, qf, kdesc(h, b));
            wg_commit();
            wg_wait<0>();
            fence_regs<32>(s);
            float mx0 = m0, mx1 = m1;
#pragma unroll
            for (int c = 0; c < 8; c++) {
#pragma unroll
              for (int i = 0; i < 4; i++) {
                const int diff = j * 64 + (16 * wi + g + (i >> 1) * 8) - (8 * c + 2 * q + (i & 1));
                if (diff < 0 || diff > 255) s[4 * c + i] = -INFINITY;
              }
              mx0 = fmaxf(mx0, fmaxf(s[4 * c], s[4 * c + 1]));
              mx1 = fmaxf(mx1, fmaxf(s[4 * c + 2], s[4 * c + 3]));
            }
            mx0 = fmaxf(mx0, __shfl_xor_sync(0xffffffffu, mx0, 1)); mx1 = fmaxf(mx1, __shfl_xor_sync(0xffffffffu, mx1, 1));
            mx0 = fmaxf(mx0, __shfl_xor_sync(0xffffffffu, mx0, 2)); mx1 = fmaxf(mx1, __shfl_xor_sync(0xffffffffu, mx1, 2));
            const float r0 = j == 0 ? 0.f : ex2(m0 - mx0), r1 = j == 0 ? 0.f : ex2(m1 - mx1);
            m0 = mx0; m1 = mx1;
#pragma unroll
            for (int i = 0; i < 5; i++) { o[4 * i] *= r0; o[4 * i + 1] *= r0; o[4 * i + 2] *= r1; o[4 * i + 3] *= r1; }
#pragma unroll
            for (int c = 0; c < 8; c++) { s[4 * c] -= m0; s[4 * c + 1] -= m0; s[4 * c + 2] -= m1; s[4 * c + 3] -= m1; }
            exp_pack<8>(s, p);
            fence_regs<20>(o); fence_regs_u<16>(p);
            wg_fence();
            pv32(o, p, vdesc(h, b)); pv32(o, p + 8, vdesc(h, b) + 2 * VSTEP);
            wg_commit();
            wg_wait<0>();
            fence_regs<20>(o);
          }
          named_bar(1 + wg, 128);
          if (redo >> u & 1) store_o(o, u);
          __syncwarp();
        }
      }
      if (wi == 0) PROF(6 + wg);
    }
    pass_v = pass + 1;
  }
}

}

typedef CUresult (*EncodeFn)(CUtensorMap*, CUtensorMapDataType, cuuint32_t, void*, const cuuint64_t*, const cuuint64_t*,
                             const cuuint32_t*, const cuuint32_t*, CUtensorMapInterleave, CUtensorMapSwizzle,
                             CUtensorMapL2promotion, CUtensorMapFloatOOBfill);
static EncodeFn g_encode = nullptr;
struct Dim { uint64_t size, stride; uint32_t box; };
template <int N> static CUtensorMap make_map(const void* ptr, const Dim (&d)[N], int swizzle) {
  CUtensorMap m;
  cuuint64_t dims[N], strides[N];
  cuuint32_t box[N], es[N];
  for (int i = 0; i < N; i++) { dims[i] = d[i].size; strides[i] = d[i].stride; box[i] = d[i].box; es[i] = 1; }
  g_encode(&m, CU_TENSOR_MAP_DATA_TYPE_BFLOAT16, N, const_cast<void*>(ptr), dims, strides + 1, box, es, CU_TENSOR_MAP_INTERLEAVE_NONE,
           swizzle == 128 ? CU_TENSOR_MAP_SWIZZLE_128B : (swizzle == 64 ? CU_TENSOR_MAP_SWIZZLE_64B : CU_TENSOR_MAP_SWIZZLE_NONE),
           swizzle ? CU_TENSOR_MAP_L2_PROMOTION_L2_256B : CU_TENSOR_MAP_L2_PROMOTION_L2_128B, CU_TENSOR_MAP_FLOAT_OOB_FILL_NONE);
  return m;
}
static CUtensorMap map2(const void* ptr, uint64_t inner, uint64_t outer, uint32_t bi, uint32_t bo, int swizzle) {
  const Dim d[2] = {{inner, 0, bi}, {outer, inner * 2, bo}};
  return make_map(ptr, d, swizzle);
}
template <class T> static void* sym_addr(T& sym) { void* p = nullptr; cudaGetSymbolAddress(&p, sym); return p; }

static Params h_p;
static const void* h_key[9];

static cudaLaunchConfig_t launch_cfg(int grid, cudaLaunchAttribute* at) {
  cudaLaunchConfig_t cfg = {};
  cfg.gridDim = dim3(grid); cfg.blockDim = dim3(512); cfg.dynamicSmemBytes = SMEM_BYTES; cfg.stream = cudaStreamPerThread;
  at[0].id = cudaLaunchAttributeClusterDimension;
  at[0].val.clusterDim.x = 2; at[0].val.clusterDim.y = 1; at[0].val.clusterDim.z = 1;
  cfg.attrs = at; cfg.numAttrs = 1;
  return cfg;
}

extern "C" void kernel_launch(void* const* d_in, const int* in_sizes, int n_in, void* d_out, int out_size) {
  const bf16* x = (const bf16*)d_in[0];
  const bf16* wqkv = (const bf16*)d_in[1];
  const bf16* wo = (const bf16*)d_in[2];
  cudaLaunchAttribute at[1];
  bool fresh = g_encode != nullptr && h_key[8] == d_out;
  for (int i = 0; i < 8; i++) fresh = fresh && h_key[i] == d_in[i];
  if (!fresh) {
    if (!g_encode) {
      void* fn = nullptr;
      cudaDriverEntryPointQueryResult st;
      cudaGetDriverEntryPoint("cuTensorMapEncodeTiled", &fn, cudaEnableDefault, &st);
      g_encode = (EncodeFn)fn;
      cudaFuncSetAttribute(mega_kernel, cudaFuncAttributeMaxDynamicSharedMemorySize, SMEM_BYTES);
    }
    bf16* x1 = (bf16*)sym_addr(g_x1);
    Params& p = h_p;
    p.x = x; p.wqkv = wqkv; p.wo = wo; p.w_r = (const bf16*)d_in[4]; p.w_g = (const bf16*)d_in[5]; p.w_u = (const bf16*)d_in[6]; p.w_d = (const bf16*)d_in[7];
    p.out = (bf16*)d_out;
    p.mapA[0] = map2(x, DM, SEQ, 32, 256, 64);
    p.mapA[1] = map2(x1, DM, SEQ, 32, 256, 64);
    { const Dim d[3] = {{DM, 0, 64}, {DM, 3 * DM * 2, 16}, {3, DM * 2, 3}}; p.mapW = make_map(wqkv, d, 128); }
    { const Dim d[3] = {{DM, 0, 64}, {DM, 3 * DM * 2, 32}, {3, DM * 2, 3}}; p.mapWs = make_map(wqkv, d, 128); }
    { const Dim d[3] = {{DM, 0, 64}, {64, DM * 2, 32}, {16, 64 * DM * 2, 2}}; p.mapWo = make_map(wo, d, 128); }
    p.mapRes[0] = map2(x, DM, SEQ, 64, 64, 128);
    p.mapRes[1] = p.mapXst[0] = map2(x1, DM, SEQ, 64, 64, 128);
    p.mapXst[1] = map2(d_out, DM, SEQ, 64, 64, 128);
    p.mapG = map2(p.w_g, FF, DM, 56, 128, 0);
    p.mapU = map2(p.w_u, FF, DM, 56, 128, 0);
    { const Dim d[3] = {{64, 0, 64}, {FF, DM * 2, 28}, {DM / 64, 128, 8}}; p.mapD = make_map(p.w_d, d, 128); }
    for (int i = 0; i < 8; i++) h_key[i] = d_in[i];
    h_key[8] = d_out;
  }
  void* a0[] = {&h_p};
  cudaLaunchConfig_t cfg = launch_cfg(128, at);
  cudaLaunchKernelExC(&cfg, (const void*)mega_kernel, a0);
}
```

```cpp
#include <cuda_runtime.h>
#include <cuda_bf16.h>
#include <cuda.h>
#include <stdint.h>
#pragma nv_diag_suppress 550

namespace {

constexpr int SEQ = 2048, DM = 1024, FF = 3584;
constexpr float LN_EPS = 1e-5f;
typedef __nv_bfloat16 bf16;

__device__ __align__(1024) uint8_t g_kv[3 * 16 * 65536];
__device__ __align__(1024) uint8_t g_o[SEQ * DM * 2];
__device__ __align__(1024) bf16 g_x1[SEQ * DM];
__device__ unsigned g_epoch;
struct __align__(128) Flag { unsigned v[32]; };
__device__ Flag g_kvflag[3][16][2], g_oflag[8][2][16], g_xflag[16][8];
__device__ uint4 g_rowab[2][SEQ];
__device__ __align__(16) uint32_t g_vw[2][8][3 * DM];
constexpr uint32_t SENT = 0xFFFFFFFFu;
__device__ uint4 g_part[2][8 * SEQ];
__device__ uint4 g_slot[2][16 * 8];
__device__ uint4 g_cand[2][16 * 128];
__device__ uint4 g_ypart[2][128 * DM / 4];
__device__ uint4 g_x2row[128 * 2];
__device__ float2 g_rowln[8][SEQ];
__device__ int g_sel[2];

#define PROFL(l, e)
#define PROF(e) PROFL(layer, e)
#define STEPT(i)
#define SPIN_LIMIT 4000000u
__device__ __forceinline__ uint32_t smem_u32(const void* p) { return (uint32_t)__cvta_generic_to_shared(p); }
__device__ __forceinline__ void mbar_init(uint32_t bar, uint32_t cnt) {
  asm volatile("mbarrier.init.shared::cta.b64 [%0], %1;" ::"r"(bar), "r"(cnt) : "memory");
}
#define ELECT "{\n.reg .pred e;\nelect.sync _|e, 0xffffffff;\n@e "
__device__ __forceinline__ void mbar_expect_tx(uint32_t bar, uint32_t bytes) {
  asm volatile(ELECT "mbarrier.arrive.expect_tx.shared::cta.b64 _, [%0], %1;\n}" ::"r"(bar), "r"(bytes) : "memory");
}
__device__ __forceinline__ void mbar_arrive(uint32_t bar) {
  asm volatile("mbarrier.arrive.shared::cta.b64 _, [%0];" ::"r"(bar) : "memory");
}
__device__ __forceinline__ void mbar_arrive_e(uint32_t bar) {
  asm volatile(ELECT "mbarrier.arrive.shared::cta.b64 _, [%0];\n}" ::"r"(bar) : "memory");
}
__device__ __forceinline__ uint32_t mapa(uint32_t addr, uint32_t cta) {
  uint32_t r; asm("mapa.shared::cluster.u32 %0, %1, %2;" : "=r"(r) : "r"(addr), "r"(cta)); return r;
}
__device__ __forceinline__ void mbar_arrive_cluster(uint32_t bar, uint32_t cta) {
  asm volatile("mbarrier.arrive.shared::cluster.b64 _, [%0];" ::"r"(mapa(bar, cta)) : "memory");
}
#define MBAR_WAIT_ASM(QUAL)                                                                                                \
  asm volatile("{\n.reg .pred p;\nWAIT_LOOP:\n.pragma \"nounroll\";\nmbarrier.try_wait.parity" QUAL ".shared::cta.b64 p, [%0], %1;\n" \
               "@!p bra WAIT_LOOP;\n}" ::"r"(bar), "r"(parity) : "memory")
__device__ __forceinline__ void mbar_wait(uint32_t bar, uint32_t parity) { MBAR_WAIT_ASM(""); }
__device__ __forceinline__ void mbar_wait_cluster(uint32_t bar, uint32_t parity) { MBAR_WAIT_ASM(".acquire.cluster"); }
__device__ __forceinline__ void st_async2(uint32_t addr, float a, float b, uint32_t bar) {
  asm volatile("st.async.weak.shared::cluster.mbarrier::complete_tx::bytes.v2.f32 [%0], {%1, %2}, [%3];"
               ::"r"(addr), "f"(a), "f"(b), "r"(bar) : "memory");
}
__device__ __forceinline__ uint64_t policy_evict_first() {
  uint64_t p; asm volatile("createpolicy.fractional.L2::evict_first.b64 %0, 1.0;" : "=l"(p)); return p;
}
__device__ __forceinline__ void tma_load2(uint32_t dst, const CUtensorMap* m, int c0, int c1, uint32_t bar) {
  asm volatile(ELECT "cp.async.bulk.tensor.2d.shared::cluster.global.mbarrier::complete_tx::bytes [%0], [%1, {%3, %4}], [%2];\n}"
               ::"r"(dst), "l"(m), "r"(bar), "r"(c0), "r"(c1) : "memory");
}
__device__ __forceinline__ void tma_load2_h(uint32_t dst, const CUtensorMap* m, int c0, int c1, uint32_t bar, uint64_t pol) {
  asm volatile(ELECT "cp.async.bulk.tensor.2d.shared::cluster.global.mbarrier::complete_tx::bytes.L2::cache_hint [%0], [%1, {%3, %4}], [%2], %5;\n}"
               ::"r"(dst), "l"(m), "r"(bar), "r"(c0), "r"(c1), "l"(pol) : "memory");
}
__device__ __forceinline__ void tma_load3(uint32_t dst, const CUtensorMap* m, int c0, int c1, int c2, uint32_t bar) {
  asm volatile(ELECT "cp.async.bulk.tensor.3d.shared::cluster.global.mbarrier::complete_tx::bytes [%0], [%1, {%3, %4, %5}], [%2];\n}"
               ::"r"(dst), "l"(m), "r"(bar), "r"(c0), "r"(c1), "r"(c2) : "memory");
}
__device__ __forceinline__ void tma_load3_h(uint32_t dst, const CUtensorMap* m, int c0, int c1, int c2, uint32_t bar, uint64_t pol) {
  asm volatile(ELECT "cp.async.bulk.tensor.3d.shared::cluster.global.mbarrier::complete_tx::bytes.L2::cache_hint [%0], [%1, {%3, %4, %5}], [%2], %6;\n}"
               ::"r"(dst), "l"(m), "r"(bar), "r"(c0), "r"(c1), "r"(c2), "l"(pol) : "memory");
}
__device__ __forceinline__ void tma_load3_mc(uint32_t dst, const CUtensorMap* m, int c0, int c1, int c2, uint32_t bar) {
  asm volatile(ELECT "cp.async.bulk.tensor.3d.shared::cluster.global.mbarrier::complete_tx::bytes.multicast::cluster [%0], [%1, {%3, %4, %5}], [%2], %6;\n}"
               ::"r"(dst), "l"(m), "r"(bar), "r"(c0), "r"(c1), "r"(c2), "h"((uint16_t)3) : "memory");
}
__device__ __forceinline__ void bulk_push(uint32_t dst, uint32_t src, uint32_t bytes, uint32_t bar) {
  asm volatile(ELECT "cp.async.bulk.shared::cluster.shared::cta.mbarrier::complete_tx::bytes [%0], [%1], %2, [%3];\n}"
               ::"r"(dst), "r"(src), "r"(bytes), "r"(bar) : "memory");
}
template <int N> __device__ __forceinline__ void regs_inc() { asm volatile("setmaxnreg.inc.sync.aligned.u32 %0;" ::"n"(N)); }
template <int N> __device__ __forceinline__ void regs_dec() { asm volatile("setmaxnreg.dec.sync.aligned.u32 %0;" ::"n"(N)); }
__device__ __forceinline__ void tma_store(const CUtensorMap* m, uint32_t src, int c0, int c1) {
  asm volatile(ELECT "cp.async.bulk.tensor.2d.global.shared::cta.bulk_group [%0, {%2, %3}], [%1];\n}"
               ::"l"(m), "r"(src), "r"(c0), "r"(c1) : "memory");
}
__device__ __forceinline__ void bulk_load_h(uint32_t dst, const void* src, uint32_t bytes, uint32_t bar, uint64_t pol) {
  asm volatile(ELECT "cp.async.bulk.shared::cluster.global.mbarrier::complete_tx::bytes.L2::cache_hint [%0], [%1], %2, [%3], %4;\n}"
               ::"r"(dst), "l"(src), "r"(bytes), "r"(bar), "l"(pol) : "memory");
}
__device__ __forceinline__ void bulk_store(void* dst, uint32_t src, uint32_t bytes) {
  asm volatile(ELECT "cp.async.bulk.global.shared::cta.bulk_group [%0], [%1], %2;\n}" ::"l"(dst), "r"(src), "r"(bytes) : "memory");
}
__device__ __forceinline__ void bulk_commit() { asm volatile("cp.async.bulk.commit_group;" ::: "memory"); }
__device__ __forceinline__ void bulk_wait_all() { asm volatile("cp.async.bulk.wait_group 0;" ::: "memory"); }
__device__ __forceinline__ void fence_async_smem() { asm volatile("fence.proxy.async.shared::cta;" ::: "memory"); }
__device__ __forceinline__ void fence_async_global() { asm volatile("fence.proxy.async.global;" ::: "memory"); }
__device__ __forceinline__ void prefetch_tmap(const CUtensorMap* m) { asm volatile("prefetch.tensormap [%0];" ::"l"(m) : "memory"); }
__device__ __forceinline__ void named_bar(int id, int n) { asm volatile("bar.sync %0, %1;" ::"r"(id), "r"(n) : "memory"); }
__device__ __forceinline__ bool bar_red_or(int id, int n, bool v) {
  uint32_t r;
  asm volatile("{\n.reg .pred p, q;\nsetp.ne.u32 q, %3, 0;\nbarrier.cta.red.or.pred p, %1, %2, q;\nselp.u32 %0, 1, 0, p;\n}"
               : "=r"(r) : "r"(id), "r"(n), "r"((uint32_t)v) : "memory");
  return r != 0;
}
__device__ __forceinline__ void cluster_arrive() { asm volatile("barrier.cluster.arrive.relaxed.aligned;" ::: "memory"); }
__device__ __forceinline__ void cluster_wait() { asm volatile("barrier.cluster.wait.aligned;" ::: "memory"); }
__device__ __forceinline__ unsigned ld_relaxed(const unsigned* p) {
  unsigned v; asm volatile("ld.relaxed.gpu.global.u32 %0, [%1];" : "=r"(v) : "l"(p) : "memory"); return v;
}
__device__ __forceinline__ uint4 ld_relaxed4(const uint4* p) {
  uint4 v; asm volatile("ld.relaxed.gpu.global.v4.u32 {%0, %1, %2, %3}, [%4];" : "=r"(v.x), "=r"(v.y), "=r"(v.z), "=r"(v.w) : "l"(p) : "memory"); return v;
}
__device__ __forceinline__ void st_relaxed(unsigned* p, unsigned v) {
  asm volatile("st.relaxed.gpu.global.u32 [%0], %1;" ::"l"(p), "r"(v) : "memory");
}
__device__ __forceinline__ uint2 ld_relaxed2(const void* p) {
  uint2 v; asm volatile("ld.relaxed.gpu.global.v2.u32 {%0, %1}, [%2];" : "=r"(v.x), "=r"(v.y) : "l"(p) : "memory"); return v;
}
__device__ __forceinline__ void st_relaxed4(uint4* p, uint4 v) {
  asm volatile("st.relaxed.gpu.global.v4.u32 [%0], {%1, %2, %3, %4};" ::"l"(p), "r"(v.x), "r"(v.y), "r"(v.z), "r"(v.w) : "memory");
}
__device__ __forceinline__ bool valid4(uint4 v) { return v.x != SENT && v.y != SENT && v.z != SENT && v.w != SENT; }
__device__ __forceinline__ uint4 poll4(const uint4* p) {
  uint4 v;
  uint32_t spins = 0;
#pragma unroll 1
  do { v = ld_relaxed4(p); } while (!valid4(v) && ++spins < SPIN_LIMIT);
  return v;
}
__device__ __forceinline__ void set_flag(unsigned* p, unsigned tag) {
  asm volatile(ELECT "st.release.gpu.global.u32 [%0], %1;\n}" ::"l"(p), "r"(tag) : "memory");
}
__device__ __forceinline__ void poll_flag(const unsigned* p, unsigned tag) {
#pragma unroll 1
  for (uint32_t spins = 0; !__all_sync(0xffffffffu, ld_relaxed(p) == tag) && spins < SPIN_LIMIT; spins++) {}
  asm volatile("fence.acquire.gpu;" ::: "memory");
}
__device__ __forceinline__ uint32_t enc(float x) { return __float_as_uint(x + 0.0f) ^ 0x80000000u; }
__device__ __forceinline__ float dec(uint32_t u) { return __uint_as_float(u ^ 0x80000000u); }
__device__ __forceinline__ uint32_t hadd_bf2(uint32_t a, uint32_t b) {
  uint32_t r; asm("add.rn.bf16x2 %0, %1, %2;" : "=r"(r) : "r"(a), "r"(b)); return r;
}
__device__ __forceinline__ uint32_t hsub_bf2(uint32_t a, uint32_t b) {
  uint32_t r; asm("sub.rn.bf16x2 %0, %1, %2;" : "=r"(r) : "r"(a), "r"(b)); return r;
}
__device__ __forceinline__ void wg_fence() { asm volatile("wgmma.fence.sync.aligned;" ::: "memory"); }
__device__ __forceinline__ void wg_commit() { asm volatile("wgmma.commit_group.sync.aligned;" ::: "memory"); }
template <int N> __device__ __forceinline__ void wg_wait() { asm volatile("wgmma.wait_group.sync.aligned %0;" ::"n"(N) : "memory"); }
template <int R> __device__ __forceinline__ void fence_regs(float* d) {
#pragma unroll
  for (int i = 0; i < R; i++) asm volatile("" : "+f"(d[i])::"memory");
}
template <int R> __device__ __forceinline__ void fence_regs_u(uint32_t* d) {
#pragma unroll
  for (int i = 0; i < R; i++) asm volatile("" : "+r"(d[i])::"memory");
}
__host__ __device__ constexpr uint32_t dlo(uint32_t addr, uint32_t lbo) { return ((addr & 0x3FFFF) >> 4) | ((lbo >> 4) << 16); }
constexpr uint32_t H128 = 0x40000040u, H64 = 0x80000020u;
__device__ __forceinline__ void stsm_x4(uint32_t addr, uint32_t r0, uint32_t r1, uint32_t r2, uint32_t r3) {
  asm volatile("stmatrix.sync.aligned.m8n8.x4.shared.b16 [%0], {%1, %2, %3, %4};"
               ::"r"(addr), "r"(r0), "r"(r1), "r"(r2), "r"(r3) : "memory");
}
__device__ __forceinline__ void ldsm_x4(uint32_t addr, uint32_t& r0, uint32_t& r1, uint32_t& r2, uint32_t& r3) {
  asm volatile("ldmatrix.sync.aligned.m8n8.x4.shared.b16 {%0, %1, %2, %3}, [%4];"
               : "=r"(r0), "=r"(r1), "=r"(r2), "=r"(r3) : "r"(addr) : "memory");
}
__device__ __forceinline__ void ldsm_x4_t(uint32_t addr, uint32_t& r0, uint32_t& r1, uint32_t& r2, uint32_t& r3) {
  asm volatile("ldmatrix.sync.aligned.m8n8.x4.trans.shared.b16 {%0, %1, %2, %3}, [%4];"
               : "=r"(r0), "=r"(r1), "=r"(r2), "=r"(r3) : "r"(addr) : "memory");
}
__device__ __forceinline__ void mma_16816(float* d, uint32_t a0, uint32_t a1, uint32_t a2, uint32_t a3, uint32_t b0, uint32_t b1) {
  asm volatile("mma.sync.aligned.m16n8k16.row.col.f32.bf16.bf16.f32 {%0, %1, %2, %3}, {%4, %5, %6, %7}, {%8, %9}, {%0, %1, %2, %3};"
               : "+f"(d[0]), "+f"(d[1]), "+f"(d[2]), "+f"(d[3]) : "r"(a0), "r"(a1), "r"(a2), "r"(a3), "r"(b0), "r"(b1));
}
__device__ __forceinline__ void spin_cycles(int n) {
  const int t0 = (int)clock();
#pragma unroll 1
  while ((int)clock() - t0 < n) {}
}
__device__ __forceinline__ uint32_t pack_bf16(float lo, float hi) {
  uint32_t r; asm("cvt.rn.bf16x2.f32 %0, %1, %2;" : "=r"(r) : "f"(hi), "f"(lo)); return r;
}
__device__ __forceinline__ float bf_lo(uint32_t v) { return __uint_as_float(v << 16); }
__device__ __forceinline__ float bf_hi(uint32_t v) { return __uint_as_float(v & 0xffff0000u); }
__device__ __forceinline__ float rbf(float x) { return __bfloat162float(__float2bfloat16_rn(x)); }
__device__ __forceinline__ float ex2(float x) { float y; asm("ex2.approx.ftz.f32 %0, %1;" : "=f"(y) : "f"(x)); return y; }
__device__ __forceinline__ float rcp(float x) { float y; asm("rcp.approx.ftz.f32 %0, %1;" : "=f"(y) : "f"(x)); return y; }
__device__ __forceinline__ uint32_t shl_clamp(uint32_t v, uint32_t n) {
  uint32_t r; asm("shl.b32 %0, %1, %2;" : "=r"(r) : "r"(v), "r"(n)); return r;
}
__device__ __forceinline__ float warp_sum(float v) {
#pragma unroll
  for (int o = 16; o > 0; o >>= 1) v += __shfl_xor_sync(0xffffffffu, v, o);
  return v;
}
__device__ __forceinline__ float ln_inv(float var) {
  float r;
  asm("sqrt.approx.ftz.f32 %0, %1;" : "=f"(r) : "f"(rbf(rbf(var) + LN_EPS)));
  asm("rcp.approx.ftz.f32 %0, %1;" : "=f"(r) : "f"(rbf(r)));
  return r;
}
__device__ __forceinline__ uint32_t ln_pair(uint32_t x, uint32_t mean2, float inv) {
  const uint32_t d = hsub_bf2(x, mean2);
  return pack_bf16(bf_lo(d) * inv, bf_hi(d) * inv);
}
__device__ __forceinline__ uint32_t add_ln_pair(uint32_t x, uint32_t mean2, float inv) { return hadd_bf2(x, ln_pair(x, mean2, inv)); }
__device__ __forceinline__ uint32_t router_key(float r_bf, int row) {
  uint32_t u = __float_as_uint(r_bf);
  u = (u & 0x80000000u) ? ~u : (u | 0x80000000u);
  return (u & 0xFFFF0000u) | 0x8000u | (uint32_t)(SEQ - 1 - row);
}

template <uint32_t HA = 0x40000040u, uint32_t HB = 0x40000040u>
__device__ __forceinline__ void wg_ss192t(float* d, uint32_t da, uint32_t db, int scale_d) {
  asm volatile("{\n.reg .pred p;\n.reg .b64 dA, dB;\nmov.b64 dA, {%96, %99};\nmov.b64 dB, {%97, %100};\nsetp.ne.b32 p, %98, 0;\n"
    "wgmma.mma_async.sync.aligned.m64n192k16.f32.bf16.bf16 "
    "{%0, %1, %2, %3, %4, %5, %6, %7, %8, %9, %10, %11, %12, %13, %14, %15, "
    "%16, %17, %18, %19, %20, %21, %22, %23, %24, %25, %26, %27, %28, %29, %30, %31, "
    "%32, %33, %34, %35, %36, %37, %38, %39, %40, %41, %42, %43, %44, %45, %46, %47, "
    "%48, %49, %50, %51, %52, %53, %54, %55, %56, %57, %58, %59, %60, %61, %62, %63, "
    "%64, %65, %66, %67, %68, %69, %70, %71, %72, %73, %74, %75, %76, %77, %78, %79, "
    "%80, %81, %82, %83, %84, %85, %86, %87, %88, %89, %90, %91, %92, %93, %94, %95}, "
    "dA, dB, p, 1, 1, 0, 1;\n}\n"
    : "+f"(d[0]), "+f"(d[1]), "+f"(d[2]), "+f"(d[3]), "+f"(d[4]), "+f"(d[5]), "+f"(d[6]), "+f"(d[7]),
      "+f"(d[8]), "+f"(d[9]), "+f"(d[10]), "+f"(d[11]), "+f"(d[12]), "+f"(d[13]), "+f"(d[14]), "+f"(d[15]),
      "+f"(d[16]), "+f"(d[17]), "+f"(d[18]), "+f"(d[19]), "+f"(d[20]), "+f"(d[21]), "+f"(d[22]), "+f"(d[23]),
      "+f"(d[24]), "+f"(d[25]), "+f"(d[26]), "+f"(d[27]), "+f"(d[28]), "+f"(d[29]), "+f"(d[30]), "+f"(d[31]),
      "+f"(d[32]), "+f"(d[33]), "+f"(d[34]), "+f"(d[35]), "+f"(d[36]), "+f"(d[37]), "+f"(d[38]), "+f"(d[39]),
      "+f"(d[40]), "+f"(d[41]), "+f"(d[42]), "+f"(d[43]), "+f"(d[44]), "+f"(d[45]), "+f"(d[46]), "+f"(d[47]),
      "+f"(d[48]), "+f"(d[49]), "+f"(d[50]), "+f"(d[51]), "+f"(d[52]), "+f"(d[53]), "+f"(d[54]), "+f"(d[55]),
      "+f"(d[56]), "+f"(d[57]), "+f"(d[58]), "+f"(d[59]), "+f"(d[60]), "+f"(d[61]), "+f"(d[62]), "+f"(d[63]),
      "+f"(d[64]), "+f"(d[65]), "+f"(d[66]), "+f"(d[67]), "+f"(d[68]), "+f"(d[69]), "+f"(d[70]), "+f"(d[71]),
      "+f"(d[72]), "+f"(d[73]), "+f"(d[74]), "+f"(d[75]), "+f"(d[76]), "+f"(d[77]), "+f"(d[78]), "+f"(d[79]),
      "+f"(d[80]), "+f"(d[81]), "+f"(d[82]), "+f"(d[83]), "+f"(d[84]), "+f"(d[85]), "+f"(d[86]), "+f"(d[87]),
      "+f"(d[88]), "+f"(d[89]), "+f"(d[90]), "+f"(d[91]), "+f"(d[92]), "+f"(d[93]), "+f"(d[94]), "+f"(d[95])
    : "r"(da), "r"(db), "r"(scale_d), "n"(HA), "n"(HB));
}
template <uint32_t HA = 0x40000040u, uint32_t HB = 0x40000040u>
__device__ __forceinline__ void wg_ss192t_z(float* d, uint32_t da, uint32_t db) {
  asm volatile("{\n.reg .pred p;\n.reg .b64 dA, dB;\nmov.b64 dA, {%96, %98};\nmov.b64 dB, {%97, %99};\nsetp.ne.b32 p, 0, 0;\n"
    "wgmma.mma_async.sync.aligned.m64n192k16.f32.bf16.bf16 "
    "{%0, %1, %2, %3, %4, %5, %6, %7, %8, %9, %10, %11, %12, %13, %14, %15, "
    "%16, %17, %18, %19, %20, %21, %22, %23, %24, %25, %26, %27, %28, %29, %30, %31, "
    "%32, %33, %34, %35, %36, %37, %38, %39, %40, %41, %42, %43, %44, %45, %46, %47, "
    "%48, %49, %50, %51, %52, %53, %54, %55, %56, %57, %58, %59, %60, %61, %62, %63, "
    "%64, %65, %66, %67, %68, %69, %70, %71, %72, %73, %74, %75, %76, %77, %78, %79, "
    "%80, %81, %82, %83, %84, %85, %86, %87, %88, %89, %90, %91, %92, %93, %94, %95}, "
    "dA, dB, p, 1, 1, 0, 1;\n}\n"
    : "=f"(d[0]), "=f"(d[1]), "=f"(d[2]), "=f"(d[3]), "=f"(d[4]), "=f"(d[5]), "=f"(d[6]), "=f"(d[7]),
      "=f"(d[8]), "=f"(d[9]), "=f"(d[10]), "=f"(d[11]), "=f"(d[12]), "=f"(d[13]), "=f"(d[14]), "=f"(d[15]),
      "=f"(d[16]), "=f"(d[17]), "=f"(d[18]), "=f"(d[19]), "=f"(d[20]), "=f"(d[21]), "=f"(d[22]), "=f"(d[23]),
      "=f"(d[24]), "=f"(d[25]), "=f"(d[26]), "=f"(d[27]), "=f"(d[28]), "=f"(d[29]), "=f"(d[30]), "=f"(d[31]),
      "=f"(d[32]), "=f"(d[33]), "=f"(d[34]), "=f"(d[35]), "=f"(d[36]), "=f"(d[37]), "=f"(d[38]), "=f"(d[39]),
      "=f"(d[40]), "=f"(d[41]), "=f"(d[42]), "=f"(d[43]), "=f"(d[44]), "=f"(d[45]), "=f"(d[46]), "=f"(d[47]),
      "=f"(d[48]), "=f"(d[49]), "=f"(d[50]), "=f"(d[51]), "=f"(d[52]), "=f"(d[53]), "=f"(d[54]), "=f"(d[55]),
      "=f"(d[56]), "=f"(d[57]), "=f"(d[58]), "=f"(d[59]), "=f"(d[60]), "=f"(d[61]), "=f"(d[62]), "=f"(d[63]),
      "=f"(d[64]), "=f"(d[65]), "=f"(d[66]), "=f"(d[67]), "=f"(d[68]), "=f"(d[69]), "=f"(d[70]), "=f"(d[71]),
      "=f"(d[72]), "=f"(d[73]), "=f"(d[74]), "=f"(d[75]), "=f"(d[76]), "=f"(d[77]), "=f"(d[78]), "=f"(d[79]),
      "=f"(d[80]), "=f"(d[81]), "=f"(d[82]), "=f"(d[83]), "=f"(d[84]), "=f"(d[85]), "=f"(d[86]), "=f"(d[87]),
      "=f"(d[88]), "=f"(d[89]), "=f"(d[90]), "=f"(d[91]), "=f"(d[92]), "=f"(d[93]), "=f"(d[94]), "=f"(d[95])
    : "r"(da), "r"(db), "n"(HA), "n"(HB));
}
template <uint32_t HA = 0x40000040u, uint32_t HB = 0x40000040u>
__device__ __forceinline__ void wg_ss128t(float* d, uint32_t da, uint32_t db, int scale_d) {
  asm volatile("{\n.reg .pred p;\n.reg .b64 dA, dB;\nmov.b64 dA, {%64, %67};\nmov.b64 dB, {%65, %68};\nsetp.ne.b32 p, %66, 0;\n"
    "wgmma.mma_async.sync.aligned.m64n128k16.f32.bf16.bf16 "
    "{%0, %1, %2, %3, %4, %5, %6, %7, %8, %9, %10, %11, %12, %13, %14, %15, "
    "%16, %17, %18, %19, %20, %21, %22, %23, %24, %25, %26, %27, %28, %29, %30, %31, "
    "%32, %33, %34, %35, %36, %37, %38, %39, %40, %41, %42, %43, %44, %45, %46, %47, "
    "%48, %49, %50, %51, %52, %53, %54, %55, %56, %57, %58, %59, %60, %61, %62, %63}, "
    "dA, dB, p, 1, 1, 0, 1;\n}\n"
    : "+f"(d[0]), "+f"(d[1]), "+f"(d[2]), "+f"(d[3]), "+f"(d[4]), "+f"(d[5]), "+f"(d[6]), "+f"(d[7]),
      "+f"(d[8]), "+f"(d[9]), "+f"(d[10]), "+f"(d[11]), "+f"(d[12]), "+f"(d[13]), "+f"(d[14]), "+f"(d[15]),
      "+f"(d[16]), "+f"(d[17]), "+f"(d[18]), "+f"(d[19]), "+f"(d[20]), "+f"(d[21]), "+f"(d[22]), "+f"(d[23]),
      "+f"(d[24]), "+f"(d[25]), "+f"(d[26]), "+f"(d[27]), "+f"(d[28]), "+f"(d[29]), "+f"(d[30]), "+f"(d[31]),
      "+f"(d[32]), "+f"(d[33]), "+f"(d[34]), "+f"(d[35]), "+f"(d[36]), "+f"(d[37]), "+f"(d[38]), "+f"(d[39]),
      "+f"(d[40]), "+f"(d[41]), "+f"(d[42]), "+f"(d[43]), "+f"(d[44]), "+f"(d[45]), "+f"(d[46]), "+f"(d[47]),
      "+f"(d[48]), "+f"(d[49]), "+f"(d[50]), "+f"(d[51]), "+f"(d[52]), "+f"(d[53]), "+f"(d[54]), "+f"(d[55]),
      "+f"(d[56]), "+f"(d[57]), "+f"(d[58]), "+f"(d[59]), "+f"(d[60]), "+f"(d[61]), "+f"(d[62]), "+f"(d[63])
    : "r"(da), "r"(db), "r"(scale_d), "n"(HA), "n"(HB));
}
template <uint32_t HB = 0x40000040u>
__device__ __forceinline__ void wg_rs64(float* d, uint32_t a0, uint32_t a1, uint32_t a2, uint32_t a3, uint32_t db, int scale_d) {
  asm volatile("{\n.reg .pred p;\n.reg .b64 dB;\nmov.b64 dB, {%36, %38};\nsetp.ne.b32 p, %37, 0;\n"
    "wgmma.mma_async.sync.aligned.m64n64k16.f32.bf16.bf16 "
    "{%0, %1, %2, %3, %4, %5, %6, %7, %8, %9, %10, %11, %12, %13, %14, %15, "
    "%16, %17, %18, %19, %20, %21, %22, %23, %24, %25, %26, %27, %28, %29, %30, %31}, "
    "{%32, %33, %34, %35}, dB, p, 1, 1, 0;\n}\n"
    : "+f"(d[0]), "+f"(d[1]), "+f"(d[2]), "+f"(d[3]), "+f"(d[4]), "+f"(d[5]), "+f"(d[6]), "+f"(d[7]),
      "+f"(d[8]), "+f"(d[9]), "+f"(d[10]), "+f"(d[11]), "+f"(d[12]), "+f"(d[13]), "+f"(d[14]), "+f"(d[15]),
      "+f"(d[16]), "+f"(d[17]), "+f"(d[18]), "+f"(d[19]), "+f"(d[20]), "+f"(d[21]), "+f"(d[22]), "+f"(d[23]),
      "+f"(d[24]), "+f"(d[25]), "+f"(d[26]), "+f"(d[27]), "+f"(d[28]), "+f"(d[29]), "+f"(d[30]), "+f"(d[31])
    : "r"(a0), "r"(a1), "r"(a2), "r"(a3), "r"(db), "r"(scale_d), "n"(HB));
}
template <uint32_t HB = 0x40000040u>
__device__ __forceinline__ void wg_rs64_z(float* d, uint32_t a0, uint32_t a1, uint32_t a2, uint32_t a3, uint32_t db) {
  asm volatile("{\n.reg .pred p;\n.reg .b64 dB;\nmov.b64 dB, {%36, %37};\nsetp.ne.b32 p, 0, 0;\n"
    "wgmma.mma_async.sync.aligned.m64n64k16.f32.bf16.bf16 "
    "{%0, %1, %2, %3, %4, %5, %6, %7, %8, %9, %10, %11, %12, %13, %14, %15, "
    "%16, %17, %18, %19, %20, %21, %22, %23, %24, %25, %26, %27, %28, %29, %30, %31}, "
    "{%32, %33, %34, %35}, dB, p, 1, 1, 0;\n}\n"
    : "=f"(d[0]), "=f"(d[1]), "=f"(d[2]), "=f"(d[3]), "=f"(d[4]), "=f"(d[5]), "=f"(d[6]), "=f"(d[7]),
      "=f"(d[8]), "=f"(d[9]), "=f"(d[10]), "=f"(d[11]), "=f"(d[12]), "=f"(d[13]), "=f"(d[14]), "=f"(d[15]),
      "=f"(d[16]), "=f"(d[17]), "=f"(d[18]), "=f"(d[19]), "=f"(d[20]), "=f"(d[21]), "=f"(d[22]), "=f"(d[23]),
      "=f"(d[24]), "=f"(d[25]), "=f"(d[26]), "=f"(d[27]), "=f"(d[28]), "=f"(d[29]), "=f"(d[30]), "=f"(d[31])
    : "r"(a0), "r"(a1), "r"(a2), "r"(a3), "r"(db), "n"(HB));
}
template <uint32_t HB = 0x40000040u>
__device__ __forceinline__ void wg_rs32(float* d, uint32_t a0, uint32_t a1, uint32_t a2, uint32_t a3, uint32_t db, int scale_d) {
  asm volatile("{\n.reg .pred p;\n.reg .b64 dB;\nmov.b64 dB, {%20, %22};\nsetp.ne.b32 p, %21, 0;\n"
    "wgmma.mma_async.sync.aligned.m64n32k16.f32.bf16.bf16 "
    "{%0, %1, %2, %3, %4, %5, %6, %7, %8, %9, %10, %11, %12, %13, %14, %15}, "
    "{%16, %17, %18, %19}, dB, p, 1, 1, 0;\n}\n"
    : "+f"(d[0]), "+f"(d[1]), "+f"(d[2]), "+f"(d[3]), "+f"(d[4]), "+f"(d[5]), "+f"(d[6]), "+f"(d[7]),
      "+f"(d[8]), "+f"(d[9]), "+f"(d[10]), "+f"(d[11]), "+f"(d[12]), "+f"(d[13]), "+f"(d[14]), "+f"(d[15])
    : "r"(a0), "r"(a1), "r"(a2), "r"(a3), "r"(db), "r"(scale_d), "n"(HB));
}
template <uint32_t HB = 0x40000040u>
__device__ __forceinline__ void wg_rs32_z(float* d, uint32_t a0, uint32_t a1, uint32_t a2, uint32_t a3, uint32_t db) {
  asm volatile("{\n.reg .pred p;\n.reg .b64 dB;\nmov.b64 dB, {%20, %21};\nsetp.ne.b32 p, 0, 0;\n"
    "wgmma.mma_async.sync.aligned.m64n32k16.f32.bf16.bf16 "
    "{%0, %1, %2, %3, %4, %5, %6, %7, %8, %9, %10, %11, %12, %13, %14, %15}, "
    "{%16, %17, %18, %19}, dB, p, 1, 1, 0;\n}\n"
    : "=f"(d[0]), "=f"(d[1]), "=f"(d[2]), "=f"(d[3]), "=f"(d[4]), "=f"(d[5]), "=f"(d[6]), "=f"(d[7]),
      "=f"(d[8]), "=f"(d[9]), "=f"(d[10]), "=f"(d[11]), "=f"(d[12]), "=f"(d[13]), "=f"(d[14]), "=f"(d[15])
    : "r"(a0), "r"(a1), "r"(a2), "r"(a3), "r"(db), "n"(HB));
}
template <uint32_t HB = 0x40000040u>
__device__ __forceinline__ void wg_rs40t(float* d, uint32_t a0, uint32_t a1, uint32_t a2, uint32_t a3, uint32_t db, int scale_d) {
  asm volatile("{\n.reg .pred p;\n.reg .b64 dB;\nmov.b64 dB, {%24, %26};\nsetp.ne.b32 p, %25, 0;\n"
    "wgmma.mma_async.sync.aligned.m64n40k16.f32.bf16.bf16 "
    "{%0, %1, %2, %3, %4, %5, %6, %7, %8, %9, %10, %11, %12, %13, %14, %15, "
    "%16, %17, %18, %19}, "
    "{%20, %21, %22, %23}, dB, p, 1, 1, 1;\n}\n"
    : "+f"(d[0]), "+f"(d[1]), "+f"(d[2]), "+f"(d[3]), "+f"(d[4]), "+f"(d[5]), "+f"(d[6]), "+f"(d[7]),
      "+f"(d[8]), "+f"(d[9]), "+f"(d[10]), "+f"(d[11]), "+f"(d[12]), "+f"(d[13]), "+f"(d[14]), "+f"(d[15]),
      "+f"(d[16]), "+f"(d[17]), "+f"(d[18]), "+f"(d[19])
    : "r"(a0), "r"(a1), "r"(a2), "r"(a3), "r"(db), "r"(scale_d), "n"(HB));
}
template <uint32_t HB = 0x40000040u>
__device__ __forceinline__ void wg_rs40t_z(float* d, uint32_t a0, uint32_t a1, uint32_t a2, uint32_t a3, uint32_t db) {
  asm volatile("{\n.reg .pred p;\n.reg .b64 dB;\nmov.b64 dB, {%24, %25};\nsetp.ne.b32 p, 0, 0;\n"
    "wgmma.mma_async.sync.aligned.m64n40k16.f32.bf16.bf16 "
    "{%0, %1, %2, %3, %4, %5, %6, %7, %8, %9, %10, %11, %12, %13, %14, %15, "
    "%16, %17, %18, %19}, "
    "{%20, %21, %22, %23}, dB, p, 1, 1, 1;\n}\n"
    : "=f"(d[0]), "=f"(d[1]), "=f"(d[2]), "=f"(d[3]), "=f"(d[4]), "=f"(d[5]), "=f"(d[6]), "=f"(d[7]),
      "=f"(d[8]), "=f"(d[9]), "=f"(d[10]), "=f"(d[11]), "=f"(d[12]), "=f"(d[13]), "=f"(d[14]), "=f"(d[15]),
      "=f"(d[16]), "=f"(d[17]), "=f"(d[18]), "=f"(d[19])
    : "r"(a0), "r"(a1), "r"(a2), "r"(a3), "r"(db), "n"(HB));
}

constexpr uint32_t SOFF = 1024;
constexpr int STG = 57344, QE = 28672, SL_W = 16384, SL_HD = 12288, SL_F = 3 * STG, X_ST = 131072;
__host__ __device__ constexpr int kv_off(int h, int b) { return 16384 + h * 81920 + (b ^ (6 * h)) * 8192; }
__host__ __device__ constexpr int qo_off(int h, int qb) { return (qb >> 1) * 81920 + h * 8192 + (qb & 1) * 4096; }
__host__ __device__ constexpr int wo_off(int st) { return 16384 + st * 32768 + (st >> 1) * 16384; }
constexpr int OFF_ONES = 4 * STG;
constexpr int OFF_PATCH = OFF_ONES + 1024;
constexpr int OFF_CS = OFF_PATCH + 768;
constexpr int OFF_BAR = OFF_CS + 768;
constexpr int OFF_MISC = OFF_BAR + 416;
constexpr int SMEM_BYTES = OFF_MISC + 96;
enum { B_FULL = 0, B_EMPTY = 6, B_HALO = 12, B_CS = 15, B_KVREADY, B_QDONE = B_KVREADY + 2, B_QREADY, B_OST, B_ADONE = B_OST + 2,
       B_QFREE, B_WS, B_WFULL, B_WEMPTY = B_WFULL + 4, B_GU = B_WEMPTY + 4, B_RES = B_GU + 2, B_DN,
       B_HX = B_DN + 2, B_RST, B_E23, B_UNIT, B_COUNT = B_UNIT + 8 };
static_assert(B_COUNT <= 52, "barrier area");
__host__ __device__ constexpr int bar_count(int i) {
  return i >= B_EMPTY && i < B_HALO ? 17 : i == B_CS ? 5 : i == B_QFREE ? 16
       : i == B_KVREADY || i == B_KVREADY + 1 || i == B_QREADY ? 8 : i == B_E23 ? 9 : i == B_ADONE ? 32 : i == B_OST ? 2 : i >= B_UNIT ? 4
       : i == B_QDONE || (i >= B_WEMPTY && i < B_GU) ? 16 : i == B_RST ? 4 : i == B_RES ? 2 : 1;
}
enum { M_KEY = 0, M_MEAN, M_INV, M_WSUM, M_TAG, M_SEL0, M_PMEAN, M_PINV, M_XQ = 8, M_KEYS = 12, M_PROG = 20 };
constexpr int FFN_PIECE = 14336;
constexpr int T_XS = 163840, T_HP = T_XS + 1024;
constexpr float LSUM_MIN = 5.421010862427522e-20f, LSUM_MAX = 1.8446744073709552e19f;
constexpr float SM_C = 0.17677669529663687f * 1.4426950408889634f;
constexpr uint32_t VSTEP = 64u - (64u << 16);
constexpr int DELAY_P = 600, DELAY_S = 2400, DELAY_Y = 400, P1_DELAY = 800, X_STAGGER = 500;
constexpr int GU_PACE = 2500, GU_PACE1 = 1200, GUB_PACE = 900, WS_PACE = 1000;
constexpr int RES_K = 6;

struct Params {
  CUtensorMap mapA[2], mapW, mapWo, mapRes[2], mapXst[2], mapG, mapU, mapD, mapWs;
  const bf16 *w_r, *w_d;
  bf16* out;
};

template <int N> __device__ __forceinline__ void exp_pack(const float* s, uint32_t* p) {
#pragma unroll
  for (int b = 0; b < N; b++) {
    p[2 * b] = pack_bf16(ex2(s[4 * b]), ex2(s[4 * b + 1]));
    p[2 * b + 1] = pack_bf16(ex2(s[4 * b + 2]), ex2(s[4 * b + 3]));
  }
}
template <int KIND> __device__ __forceinline__ void edge16(const float* sd, const float* st, uint32_t* pd, uint32_t* pt, int dl, uint32_t mt) {
  if (KIND == 0) { exp_pack<2>(sd, pd); pt[0] = pt[1] = pt[2] = pt[3] = 0; }
  else if (KIND == 1) { exp_pack<2>(st, pt); pd[0] = pd[1] = pd[2] = pd[3] = 0; }
  else {
    const uint32_t a = pack_bf16(ex2(dl >= 0 ? sd[0] : st[0]), ex2(dl >= 1 ? sd[1] : st[1]));
    const uint32_t c = pack_bf16(ex2(dl >= 0 ? sd[6] : st[6]), ex2(dl >= 1 ? sd[7] : st[7]));
    pd[0] = a & ~mt; pt[0] = a & mt; pd[3] = c & ~mt; pt[3] = c & mt;
    pd[1] = pack_bf16(ex2(sd[2]), ex2(sd[3])); pt[1] = 0;
    pt[2] = pack_bf16(ex2(st[4]), ex2(st[5])); pd[2] = 0;
  }
}
__device__ __forceinline__ void edge32(const float* sd, const float* st, uint32_t* pd, uint32_t* pt, int rel, int dl, uint32_t mt) {
  if (rel > 1) { edge16<0>(sd, st, pd, pt, dl, mt); edge16<0>(sd + 8, st + 8, pd + 4, pt + 4, dl, mt); }
  else if (rel == 1) { edge16<0>(sd, st, pd, pt, dl, mt); edge16<2>(sd + 8, st + 8, pd + 4, pt + 4, dl, mt); }
  else if (rel == 0) { edge16<2>(sd, st, pd, pt, dl, mt); edge16<1>(sd + 8, st + 8, pd + 4, pt + 4, dl, mt); }
  else { edge16<1>(sd, st, pd, pt, dl, mt); edge16<1>(sd + 8, st + 8, pd + 4, pt + 4, dl, mt); }
}
__device__ __forceinline__ void qk64(float* s, const uint32_t* qf, uint32_t kd) {
  wg_rs64_z<H64>(s, qf[0], qf[1], qf[2], qf[3], kd);
  wg_rs64<H64>(s, qf[4], qf[5], qf[6], qf[7], kd + 2, 1);
}
__device__ __forceinline__ void qk32x2(float* a, float* b, const uint32_t* qf, uint32_t ka, uint32_t kb) {
  wg_rs32_z<H64>(a, qf[0], qf[1], qf[2], qf[3], ka); wg_rs32_z<H64>(b, qf[0], qf[1], qf[2], qf[3], kb);
  wg_rs32<H64>(a, qf[4], qf[5], qf[6], qf[7], ka + 2, 1); wg_rs32<H64>(b, qf[4], qf[5], qf[6], qf[7], kb + 2, 1);
}
__device__ __forceinline__ void pv32(float* o, const uint32_t* p, uint32_t vd) {
  wg_rs40t<H64>(o, p[0], p[1], p[2], p[3], vd, 1);
  wg_rs40t<H64>(o, p[4], p[5], p[6], p[7], vd + VSTEP, 1);
}

__device__ __forceinline__ void fma8(float* d, uint4 w, float x) {
  d[0] += x * bf_lo(w.x); d[1] += x * bf_hi(w.x); d[2] += x * bf_lo(w.y); d[3] += x * bf_hi(w.y);
  d[4] += x * bf_lo(w.z); d[5] += x * bf_hi(w.z); d[6] += x * bf_lo(w.w); d[7] += x * bf_hi(w.w);
}

__device__ __forceinline__ int fresh_tid() { int r; asm volatile("mov.u32 %0, %%tid.x;" : "=r"(r)); return r; }
__device__ __forceinline__ int fresh_bid() { int r; asm volatile("mov.u32 %0, %%ctaid.x;" : "=r"(r)); return r; }
#define PHASE_IDS                                                                                                              \
  const uint32_t sbase = smem_u32(smem);                                                                                       \
  const int tid = fresh_tid(), bid = fresh_bid();                                                                              \
  const int warp = __shfl_sync(0xffffffffu, tid >> 5, 0), lane = tid & 31;                                                     \
  const int rank = bid & 1, cl = bid >> 1, rb = bid & 7, hp = bid >> 3;                  \
  const int mb = 2 * rb + (hp >> 3), nb = hp & 7;                                            \
  const int wg = warp >> 2, wi = warp & 3, g = lane >> 2, q = lane & 3;                                                        \
  const int mi = lane >> 3, srow = wi * 16 + (mi & 1) * 8 + (lane & 7);      \
  auto bar = [&](int i) { return sbase + OFF_BAR + 8 * i; };                                                                   \
  volatile uint32_t* s_misc = (volatile uint32_t*)(smem + OFF_MISC);                                                           \
  auto load_w = [&](int s, int kt) {                           \
    tma_load3_mc(sbase + s * QE + SL_W + rank * 6144, &P.mapW, hp * 64, kt * 32 + rank * 16, 0, bar(B_FULL + s));              \
  };                                                                                                                           \
  auto load_a = [&](int s, int kt, int layer) { mbar_expect_tx(bar(B_FULL + s), QE); tma_load2(sbase + s * QE, &P.mapA[layer], kt * 32, rb * 256, bar(B_FULL + s)); }; \
  auto load_wo = [&](int k) {                                                 \
    mbar_expect_tx(bar(B_WFULL + (k & 3)), 32768);                                                                             \
    tma_load3_mc(sbase + wo_off(k & 3) + 16384 + rank * 8192, &P.mapWo, nb * 128 + rank * 64, (k >> 3) * 32, (k & 7) * 2, bar(B_WFULL + (k & 3))); \
  };                                                                                                                           \
  auto load_o = [&](int k) {                                                            \
    bulk_load_h(sbase + wo_off(k & 3), g_o + (size_t)(mb * 16 + k) * 16384, 16384, bar(B_WFULL + (k & 3)), policy_evict_first());                    \
  };                                                                                                                           \
  auto load_res = [&](int half, int layer) {      \
    mbar_expect_tx(bar(B_RES), 16384);                                                                                         \
    tma_load2_h(sbase + qo_off(half, 0), &P.mapRes[layer], nb * 128 + half * 64, mb * 128, bar(B_RES), policy_evict_first());  \
    tma_load2_h(sbase + qo_off(half, 2), &P.mapRes[layer], nb * 128 + half * 64, mb * 128 + 64, bar(B_RES), policy_evict_first()); \
  };                                                                                                                           \
  auto store_tile = [&](int layer, int skip, bool wait) {                                           \
    _Pragma("unroll 1")                                                                                                        \
    for (int j = 0; j < 4; j++)                                                                                                \
      if ((j & 1) != skip) tma_store(&P.mapXst[layer], sbase + X_ST + (j & 1) * 16384 + (j >> 1) * 8192, nb * 128 + (j >> 1) * 64, mb * 128 + (j & 1) * 64); \
    bulk_commit();                                                                                                             \
    if (wait) bulk_wait_all();                                                                                                 \
  };                                                                                                                           \
  auto load_ws = [&](int pace) {                                    \
    mbar_expect_tx(bar(B_WS), 4 * SL_HD);                                                                                      \
    _Pragma("unroll 1")                                                                                                        \
    for (int j = 0; j < 4; j++) {                                                                                              \
      tma_load3(sbase + SL_F + j * SL_HD, &P.mapWs, hp * 64, rb * 128 + j * 32, 0, bar(B_WS));                                 \
      if (pace) spin_cycles(pace);                                                                                             \
    }                                                                                                                          \
  };                                                                                                                           \
  auto load_gu = [&](int half, int pace) {                             \
    mbar_expect_tx(bar(B_GU + half), 4 * FFN_PIECE);                                                                           \
    _Pragma("unroll 1")                                                                                                        \
    for (int j = 0; j < 4; j++) {                                                                                              \
      tma_load2_h(sbase + SL_F + j * FFN_PIECE, &P.mapG + (j >> 1), cl * 56, rank * 512 + half * 256 + (j & 1) * 128, bar(B_GU + half), policy_evict_first()); \
      if (j < 3) spin_cycles(pace);                                                                                            \
    }                                                                                                                          \
  };                                                                                                                           \
  auto fetch_gu = [&](uint32_t* a, int ks, int ct) {                 \
    ldsm_x4_t(sbase + SL_F + (mi & 1) * 2 * FFN_PIECE + (ks * 16 + (mi >> 1) * 8 + (lane & 7)) * 112 + ct * 16, a[0], a[1], a[2], a[3]); \
  };                                                                                                                           \
  auto send_gu = [&](float gate, float up, int ct, int part) {        \
    const int u = 8 * ct + g, own = u >= 28;                                                                                   \
    if (q == 0) st_async2(mapa(sbase + T_HP + ((rank * 5 + part) * 28 + u - 28 * own) * 8, own), gate, up, mapa(bar(B_HX), own)); \
  };                                                                                                                           \
  auto hidden = [&]() {                                     \
    const float2* hpart = (const float2*)(smem + T_HP) + min(lane, 27);                                                        \
    float gs[2] = {0.f, 0.f}, us[2] = {0.f, 0.f};                                                                              \
    _Pragma("unroll")                                                                                                          \
    for (int j = 0; j < 10; j++) { const float2 v = hpart[j * 28]; gs[j & 1] += v.x; us[j & 1] += v.y; }                       \
    const float gb = rbf(gs[0] + gs[1]), ub = rbf(us[0] + us[1]);                                                              \
    return lane < 28 ? rbf(__fdividef(gb, 1.f + __expf(-gb))) * ub : 0.f;                                                      \
  };                                                                                                                           \
  (void)load_wo; (void)load_o; (void)load_res; (void)store_tile; (void)fetch_gu; (void)load_ws; (void)load_gu; (void)send_gu; (void)hidden; (void)cl; (void)mb; (void)nb; (void)wg; (void)g; (void)q; (void)srow; (void)s_misc; (void)load_w; (void)load_a;

__global__ void __launch_bounds__(512, 1) mega_kernel(const __grid_constant__ Params P) {
  extern __shared__ __align__(1024) uint8_t smem[];
  {
    PHASE_IDS
    if (warp == 0) {
      if (lane == 0) {
        prefetch_tmap(&P.mapA[0]); prefetch_tmap(&P.mapW);
#pragma unroll
        for (int i = 0; i < 6; i++) mbar_init(bar(B_FULL + i), 1);
        asm volatile("fence.mbarrier_init.release.cluster;" ::: "memory");
      }
      __syncwarp();
      load_a(0, 0, 0);
      tma_load3(sbase + SL_W, &P.mapW, hp * 64, 0, 0, bar(B_FULL));
      tma_load3(sbase + SL_W + 6144, &P.mapW, hp * 64, 16, 0, bar(B_FULL));
      load_a(1, 1, 0);
    } else if (tid == 32) {
#pragma unroll
      for (int i = 6; i < B_COUNT; i++) mbar_init(bar(i), bar_count(i));
      asm volatile("fence.mbarrier_init.release.cluster;" ::: "memory");
    } else if (warp == 8) {
      ((uint4*)(smem + OFF_ONES))[lane] = make_uint4(0x3F803F80u, 0x3F803F80u, 0x3F803F80u, 0x3F803F80u);
      ((uint4*)(smem + OFF_ONES))[lane + 32] = make_uint4(0x3F803F80u, 0x3F803F80u, 0x3F803F80u, 0x3F803F80u);
    }
    __syncwarp();
    cluster_arrive(); cluster_wait();
    if (warp == 0) {
      PROFL(0, 1);
      load_w(1, 1);
    } else if (tid == 96) {
      if ((sbase & 0x3FFFF) != SOFF) __trap();
    }
    __syncwarp();
  }

  regs_dec<120>();
#pragma unroll 1
  for (unsigned pass_v = 0;;) {
    const unsigned pass = __shfl_sync(0xffffffffu, pass_v, 0);
    if (__shfl_sync(0xffffffffu, fresh_tid() >> 8, 0)) {
      if (pass > 0) {
        const unsigned layer = pass - 1;
        uint32_t xr[32];
        {
          PHASE_IDS
          float acc[64];
#pragma unroll
          for (int i = 0; i < 64; i++) acc[i] = 0.f;
          const uint32_t da0 = dlo(SOFF, 16) + (wg - 2) * 256;
          constexpr uint32_t db0 = dlo(SOFF + 16384, 8192);
#pragma unroll 1
          for (int k4 = 0; k4 < 4; k4++) {
#pragma unroll
            for (int st = 0; st < 4; st++) {
              mbar_wait(bar(B_WFULL + st), k4 & 1);
              wg_fence();
#pragma unroll
              for (int kk = 0; kk < 4; kk++)
                wg_ss128t<H64, H128>(acc, da0 + (wo_off(st) >> 4) + (kk >> 1) * 512 + (kk & 1) * 2, db0 + (wo_off(st) >> 4) + kk * 128, 1);
              wg_commit();
              if (st == 0 && k4 == 0 && warp == 9) PROF(10);
              if (warp == 9) STEPT(16 + k4 * 4 + st);
              wg_wait<1>();
              if (lane < 2 && (st == 0 ? k4 > 0 : (st < 3 || k4 < 3))) mbar_arrive_cluster(bar(B_WEMPTY + ((st + 3) & 3)), lane);
            }
          }
          mbar_wait(bar(B_RES), layer);
          mbar_wait(bar(B_RST), layer);
          const uint32_t zoff = qo_off(0, (wg - 2) * 2);
#pragma unroll
          for (int j = 0; j < 8; j++)
            ldsm_x4(sbase + zoff + srow * 128 + (j >> 2) * 8192 + ((((2 * j + (mi >> 1)) & 7) ^ (srow & 7)) << 4), xr[4 * j], xr[4 * j + 1], xr[4 * j + 2], xr[4 * j + 3]);
          wg_wait<0>();
          fence_regs<64>(acc);
          if (warp == 9) PROF(11);
#pragma unroll
          for (int j = 0; j < 32; j++) xr[j] = hadd_bf2(xr[j], pack_bf16(acc[2 * j], acc[2 * j + 1]));
        }
        PHASE_IDS
        const uint32_t tag = s_misc[M_TAG];
        const int grow = mb * 128 + (warp - 8) * 16 + g;
        {
          float d[6][4];
#pragma unroll
          for (int i = 0; i < 6; i++) d[i][0] = d[i][1] = d[i][2] = d[i][3] = 0.f;
          const uint4* tab = (const uint4*)(smem + OFF_PATCH + (g == 1 ? q * 64 : (g == 0 ? 256 : 320)));
#pragma unroll
          for (int j2 = 0; j2 < 4; j2++) {
            const uint4 w = tab[j2];
#pragma unroll
            for (int jj = 0; jj < 2; jj++) {
              const uint32_t* a = &xr[8 * j2 + 4 * jj];
              mma_16816(d[jj], a[0], a[1], a[2], a[3], jj ? w.z : w.x, jj ? w.w : w.y);
              mma_16816(d[2 + jj], a[0], a[1], a[2], a[3], a[0], a[2]);
              mma_16816(d[4 + jj], a[0], a[1], a[2], a[3], a[1], a[3]);
            }
          }
          const float sq0 = __shfl_sync(0xffffffffu, (g & 1) ? d[2][1] + d[3][1] : d[2][0] + d[3][0], g * 4 + (g >> 1));
          const float sq1 = __shfl_sync(0xffffffffu, (g & 1) ? d[4][3] + d[5][3] : d[4][2] + d[5][2], g * 4 + (g >> 1));
          uint4* dst = &g_part[layer][nb * SEQ + grow];
          if (q == 0) {
            st_relaxed4(dst, make_uint4(__float_as_uint(d[0][0] + d[1][0]), __float_as_uint(sq0), __float_as_uint(d[0][1] + d[1][1]), tag));
            st_relaxed4(dst + 8, make_uint4(__float_as_uint(d[0][2] + d[1][2]), __float_as_uint(sq1), __float_as_uint(d[0][3] + d[1][3]), tag));
          }
        }
        if (warp == 9) PROF(12);
        if (layer == 0 && lane < 2) mbar_arrive_cluster(bar(B_QFREE), lane);
        asm volatile("bar.arrive 6, 320;" ::: "memory");
        const int t_p = (int)clock();
        const uint32_t zrow = sbase + X_ST + (wg - 2) * 16384 + srow * 128;
        named_bar(5, 256);
#pragma unroll
        for (int j = 0; j < 8; j++)
          stsm_x4(zrow + (j >> 2) * 8192 + ((((2 * j + (mi >> 1)) & 7) ^ (srow & 7)) << 4), xr[4 * j], xr[4 * j + 1], xr[4 * j + 2], xr[4 * j + 3]);
        if (layer == 0) {
          fence_async_smem();
          asm volatile("bar.arrive 8, 288;" ::: "memory");
        }
#pragma unroll 1
        while ((int)clock() - t_p < DELAY_P) {}
        {
          const uint4* src = &g_part[layer][2 * q * SEQ + grow];
          uint4 pp[4];
          uint32_t spins = 0;
#pragma unroll 1
          do {
            pp[0] = ld_relaxed4(src); pp[1] = ld_relaxed4(src + SEQ); pp[2] = ld_relaxed4(src + 8); pp[3] = ld_relaxed4(src + SEQ + 8);
          } while (!__all_sync(0xffffffffu, pp[0].w == tag && pp[1].w == tag && pp[2].w == tag && pp[3].w == tag) && ++spins < SPIN_LIMIT);
          if (warp == 9) PROF(13);
          const int rr = q >> 1;
          float s3[3];
#pragma unroll
          for (int c = 0; c < 3; c++) {
            const float lo = __uint_as_float(c == 0 ? pp[0].x : c == 1 ? pp[0].y : pp[0].z) + __uint_as_float(c == 0 ? pp[1].x : c == 1 ? pp[1].y : pp[1].z);
            const float hi = __uint_as_float(c == 0 ? pp[2].x : c == 1 ? pp[2].y : pp[2].z) + __uint_as_float(c == 0 ? pp[3].x : c == 1 ? pp[3].y : pp[3].z);
            s3[c] = (rr ? hi : lo) + __shfl_xor_sync(0xffffffffu, rr ? lo : hi, 2);
            s3[c] += __shfl_xor_sync(0xffffffffu, s3[c], 1);
          }
          const float mu = s3[0] * (1.f / DM), var = fmaxf(fmaf(-mu, mu, s3[1] * (1.f / DM)), 0.f);
          const float mn = rbf(mu), iv = ln_inv(var);
          const uint32_t ky = router_key(rbf((s3[2] - mn * __uint_as_float(s_misc[M_WSUM])) * iv), grow + 8 * rr);
          const uint32_t wbest = __reduce_max_sync(0xffffffffu, ky);
          s_misc[M_KEYS + warp - 8] = wbest;
          named_bar(5, 256);
          if (__reduce_max_sync(0xffffffffu, s_misc[M_KEYS + (lane & 7)]) == wbest) {
            if (nb == 0 && ky == wbest && (q & 1) == 0) st_relaxed4(&g_slot[layer][mb * 8], make_uint4(ky, __float_as_uint(mn), __float_as_uint(iv), tag));
            const int r = ~wbest & 15;
            if ((r & 7) == g) {
#pragma unroll
              for (int j = 0; j < 4; j++) {
                const uint32_t* a = &xr[8 * j];
                st_relaxed4(&g_cand[layer][mb * 128 + nb * 16 + q * 4 + j],
                            r < 8 ? make_uint4(a[0], a[2], a[4], a[6]) : make_uint4(a[1], a[3], a[5], a[7]));
              }
            }
            __syncwarp();
          }
          if (warp == 9) PROF(14);
          if (layer == 0) {
            if ((q & 1) == 0) {
              g_rowln[nb][grow + 8 * rr] = make_float2(mn, iv);
              if (warp - 8 == nb) {
                const float mu2 = mu + (mu - mn) * iv, inv2 = ln_inv(var * (1.f + iv) * (1.f + iv));
                st_relaxed4(&g_rowab[1][grow + 8 * rr], make_uint4(__float_as_uint((1.f + iv) * inv2), __float_as_uint((mn * iv + rbf(mu2)) * inv2), tag, 0));
              }
            }
            __syncwarp();
          } else {
            const uint32_t m2 = pack_bf16(mn, mn);
            uint8_t* row = smem + X_ST + (wg - 2) * 16384 + (q & 1) * 8192 + (wi * 16 + g + 8 * rr) * 128;
#pragma unroll 2
            for (int j = 0; j < 8; j++) {
              uint4* c = (uint4*)(row + (((j + lane) & 7) << 4));
              const uint4 v = *c;
              *c = make_uint4(add_ln_pair(v.x, m2, iv), add_ln_pair(v.y, m2, iv), add_ln_pair(v.z, m2, iv), add_ln_pair(v.w, m2, iv));
            }
            fence_async_smem();
          }
          if (warp == 15) asm volatile("bar.arrive 7, 512;" ::: "memory");
        }
        if (warp < 15) {
          uint32_t gu[64];
          mbar_wait(bar(B_GU + 1), layer);
#pragma unroll
          for (int j = 0; j < 16; j++) fetch_gu(gu + 4 * j, j, warp - 8);
          fence_async_smem();
          float d[4][4] = {};
          named_bar(7, 512);
#pragma unroll
          for (int hf = 0; hf < 2; hf++) {
            uint4 xv[4] = {};
            if (g == 0) {
#pragma unroll
              for (int j = 0; j < 4; j++) xv[j] = ((const uint4*)(smem + T_XS))[32 + hf * 16 + j * 4 + q];
            }
            __syncwarp();
#pragma unroll
            for (int j = 0; j < 4; j++) {
              const uint32_t* a = gu + hf * 32 + j * 8;
              mma_16816(d[(j & 1) * 2], a[0], a[1], a[2], a[3], xv[j].x, xv[j].y);
              mma_16816(d[(j & 1) * 2 + 1], a[4], a[5], a[6], a[7], xv[j].z, xv[j].w);
            }
          }
          send_gu((d[0][0] + d[1][0]) + (d[2][0] + d[3][0]), (d[0][2] + d[1][2]) + (d[2][2] + d[3][2]), warp - 8, 4);
          __syncwarp();
        }
        if (layer == 0) asm volatile("bar.arrive 9, 512;" ::: "memory");
        else {
        uint32_t wd[64];
        mbar_wait(bar(B_DN), layer);
#pragma unroll
        for (int j = 0; j < 16; j++) {
          const uint32_t row = sbase + wo_off(0) + ((warp - 8) * 2 + (j >> 3)) * 3584 + min((j & 1) * 16 + (mi >> 1) * 8 + (lane & 7), 27) * 128;
          ldsm_x4_t(row + ((((j & 6) + (mi & 1)) ^ ((row >> 7) & 7)) << 4), wd[4 * j], wd[4 * j + 1], wd[4 * j + 2], wd[4 * j + 3]);
        }
        fence_regs_u<64>(wd);
        uint32_t hf[4];
        named_bar(10, 288);
        *(uint4*)hf = *(const uint4*)(smem + OFF_PATCH + 256 + q * 16);
        if (warp == 9) PROF(19);
        float y[4][4] = {};
#pragma unroll
        for (int j = 0; j < 16; j++)
          mma_16816(y[j & 3], wd[4 * j], wd[4 * j + 1], wd[4 * j + 2], wd[4 * j + 3], g == j >> 1 ? hf[(j & 1) * 2] : 0u, g == j >> 1 ? hf[(j & 1) * 2 + 1] : 0u);
        {
          float e[4];
#pragma unroll
          for (int c = 0; c < 4; c++) { const int i = (c & 1) * 2 + (c >> 1); e[c] = (y[0][i] + y[1][i]) + (y[2][i] + y[3][i]); }
          const bool b0 = g & 1, b1 = g & 2;
          float t0 = __shfl_xor_sync(0xffffffffu, b0 ? e[0] : e[1], 4), t1 = __shfl_xor_sync(0xffffffffu, b0 ? e[2] : e[3], 4);
          const float f0 = b0 ? t0 : e[0], f1 = b0 ? e[1] : t0, f2 = b0 ? t1 : e[2], f3 = b0 ? e[3] : t1;
          t0 = __shfl_xor_sync(0xffffffffu, b1 ? f0 : f2, 8); t1 = __shfl_xor_sync(0xffffffffu, b1 ? f1 : f3, 8);
          st_relaxed4(&g_ypart[layer][bid * 256 + (warp - 8) * 32 + (q * 4 + (g & 3)) * 2 + (g >> 2)],
                      b1 ? make_uint4(__float_as_uint(t0), __float_as_uint(t1), __float_as_uint(f2), __float_as_uint(f3)) : make_uint4(__float_as_uint(f0), __float_as_uint(f1), __float_as_uint(t0), __float_as_uint(t1)));
        }
        if (warp == 9) PROF(20);
        asm volatile("bar.arrive 9, 384;" ::: "memory");
        cluster_arrive(); cluster_wait();
        return;
        }
      }
      const unsigned layer = pass;
      named_bar(1 + (fresh_tid() >> 7), 128);
      regs_inc<224>();
      float acc[2][96];
      float pa[2][2], pb[2][2];
      {
        PHASE_IDS
        const uint32_t da0 = dlo(SOFF, 16) + (wg - 2) * 256;
        constexpr uint32_t db0 = dlo(SOFF + SL_W, 2048);
        if (warp == 9) PROF(19 - 2 * layer);
        mbar_wait(bar(B_FULL), 0);
        if (warp == 9) PROF(29);
        if (warp == 9) STEPT(0);
        wg_fence();
        wg_ss192t_z<H64, H128>(acc[0], da0, db0); wg_ss192t_z<H64, H128>(acc[1], da0 + 512, db0);
        wg_ss192t<H64, H128>(acc[0], da0 + 2, db0 + 384, 1); wg_ss192t<H64, H128>(acc[1], da0 + 514, db0 + 384, 1);
        wg_commit();
        int s = 1, u = 0;
#pragma unroll 1
        for (int i = 1; i < 28; i++) {
          const uint32_t da = da0 + s * (QE >> 4), db = db0 + s * (QE >> 4);
          mbar_wait(bar(B_FULL + s), (u + (s > 1 ? layer : 0)) & 1);
          if (warp == 9 && !(i & 1)) STEPT(i >> 1);
          wg_fence();
          wg_ss192t<H64, H128>(acc[0], da, db, 1); wg_ss192t<H64, H128>(acc[1], da + 512, db, 1);
          wg_ss192t<H64, H128>(acc[0], da + 2, db + 384, 1); wg_ss192t<H64, H128>(acc[1], da + 514, db + 384, 1);
          wg_commit();
          wg_wait<1>();
          if (lane < 2 && i < 27) mbar_arrive_cluster(bar(B_EMPTY + (s == 0 ? 5 : s - 1)), lane);
          if (++s == 6) { s = 0; u++; }
        }
      }
      PHASE_IDS
      auto last_tile = [&](int m, int j) {
        const int e = (4 + j) % 6;
        const uint32_t da = dlo(SOFF, 16) + (wg - 2) * 256 + e * (QE >> 4) + m * 512, db = dlo(SOFF + SL_W, 2048) + e * (QE >> 4);
        wg_fence();
        wg_ss192t<H64, H128>(acc[m], da, db, 1);
        wg_ss192t<H64, H128>(acc[m], da + 2, db + 384, 1);
      };
      {
        if (layer == 0) mbar_wait(bar(B_CS), 0);
        const uint32_t tag = s_misc[M_TAG];
        const uint4* src = &g_rowab[layer][rb * 256 + (wg - 2 + (lane >> 4) * 2) * 64 + wi * 16 + (lane & 15)];
        uint4 v;
#pragma unroll
        for (int j = 0; j < 4; j++) {
          if (j == 2) v = ld_relaxed4(src);
          mbar_wait(bar(B_FULL + (4 + j) % 6), j < 2 ? layer : 1);
          last_tile(1, j);
          if (j == 0) { wg_commit(); wg_wait<1>(); mbar_arrive_e(bar(B_E23)); }
        }
        wg_commit();
        last_tile(0, 0);
        wg_commit();
        if (warp != 9) STEPT(4);
#pragma unroll 1
        for (uint32_t spins = 0; !__all_sync(0xffffffffu, v.z == tag) && spins < SPIN_LIMIT; spins++) v = ld_relaxed4(src);
#pragma unroll
        for (int j = 0; j < 4; j++) {
          pa[j >> 1][j & 1] = __uint_as_float(__shfl_sync(0xffffffffu, v.x, g + 8 * j));
          pb[j >> 1][j & 1] = __uint_as_float(__shfl_sync(0xffffffffu, v.y, g + 8 * j));
        }
        if (warp != 9) STEPT(5);
      }
      const int prow = (int)s_misc[M_SEL0] - rb * 256;
      const float4* cs = (const float4*)(smem + OFF_CS) + q;
      auto finish = [&](int m, int b, float2 c, uint32_t* dst) {
        dst[0] = pack_bf16(acc[m][4 * b] * pa[m][0] - c.x * pb[m][0], acc[m][4 * b + 1] * pa[m][0] - c.y * pb[m][0]);
        dst[1] = pack_bf16(acc[m][4 * b + 2] * pa[m][1] - c.x * pb[m][1], acc[m][4 * b + 3] * pa[m][1] - c.y * pb[m][1]);
      };
      auto grp = [](int n) { return n < 8 ? 4 + ((n >> 1) & 1) * 4 + (n >> 2) * 2 + (n & 1) : n - 8; };
      float4 cq[2] = {cs[grp(0) * 4], cs[grp(1) * 4]};
      auto next = [&](int m, int n, uint32_t* r) {
        if (m == 1 && n % 4 == 0) { last_tile(0, 1 + n / 4); wg_commit(); }
        const float4 c = cq[n & 1];
        cq[n & 1] = cs[grp((n + 2) % 12) * 4];
        finish(m, 2 * grp(n), make_float2(c.x, c.y), r); finish(m, 2 * grp(n) + 1, make_float2(c.z, c.w), r + 2);
      };
#pragma unroll
      for (int m = 1; m >= 0; m--) {
        if (m == 1) {
          wg_wait<1>();
          fence_regs<96>(acc[1]);
          mbar_wait(bar(B_E23), layer);
          if (warp != 9) STEPT(0);
        } else {
          wg_wait<0>();
          fence_regs<96>(acc[0]);
          if (warp != 9) STEPT(1);
          if (lane < 2) mbar_arrive_cluster(bar(B_QDONE), lane);
          if (warp == 9) PROF(2);
        }
        const int qb = wg - 2 + 2 * m;
        const bool patch = prow >> 4 == qb * 4 + wi;
#pragma unroll
        for (int jj = 0; jj < 8; jj++) {
          const int h = jj >> 2;
          uint32_t r[4];
          next(m, jj, r);
          if (m == 0 && jj == 0) named_bar(5, 256);
          stsm_x4(sbase + kv_off(h, 4 + 2 * m) + (wg - 2) * 8192 + ((jj >> 1) & 1) * 4096 + srow * 64 + ((((jj & 1) * 2 + (mi >> 1)) ^ ((srow >> 1) & 3)) << 4),
                  r[0], r[1], r[2], r[3]);
        }
        if (patch) {
          mbar_wait(bar(B_CS), 1);
          __syncwarp();
          if (lane < 16)
            *(uint4*)(smem + kv_off(g >> 1, 4 + qb) + (g & 1) * 4096 + (prow & 63) * 64 + ((q ^ ((prow >> 1) & 3)) << 4)) =
                *(const uint4*)(smem + OFF_PATCH + 128 + (g & 1) * 128 + (g >> 1) * 64 + q * 16);
        }
        fence_async_smem();
        __syncwarp();
        mbar_arrive_e(bar(B_KVREADY + 1 - m));
        if (warp != 9) STEPT(3 - m);
        pa[m][0] *= SM_C; pa[m][1] *= SM_C; pb[m][0] *= SM_C; pb[m][1] *= SM_C;
#pragma unroll
        for (int jj = 0; jj < 4; jj++) {
          uint32_t r[4];
          next(m, 8 + jj, r);
          *(uint4*)(smem + qo_off(jj >> 1, 2 * m) + (warp - 8) * 1024 + (jj & 1) * 512 + lane * 16) = make_uint4(r[0], r[1], r[2], r[3]);
        }
        __syncwarp();
        if (patch) {
          *(uint32_t*)(smem + qo_off(lane >> 4, 2 * m) + (warp - 8) * 1024 + (mi & 1) * 512 + ((prow & 7) * 4 + q) * 16 + ((g & 1) * 2 + ((prow >> 3) & 1)) * 4) =
              *(const uint32_t*)(smem + OFF_PATCH + lane * 4);
          __syncwarp();
        }
      }
      if (warp == 9) PROF(3);
      mbar_arrive_e(bar(B_QREADY));
      regs_dec<120>();
    } else {
      if (pass > 0) {
        const unsigned layer = pass - 1;
        PHASE_IDS
        const uint32_t tag = s_misc[M_TAG];
        if (warp == 7) {
              uint32_t* tab = (uint32_t*)(smem + OFF_PATCH);
#pragma unroll
              for (int j = 0; j < 2; j++) { const int w = lane + 32 * j; tab[(w & 3) * 16 + (w >> 2)] = ((const uint32_t*)P.w_r)[nb * 64 + w]; }
              tab[64 + lane] = lane < 16 ? 0x3F803F80u : 0u;
              float tot = 0.f;
#pragma unroll 1
              for (int j = 0; j < 4; j++) {
                const uint4 u = ((const uint4*)P.w_r)[lane + 32 * j];
                tot += bf_lo(u.x) + bf_hi(u.x) + bf_lo(u.y) + bf_hi(u.y) + bf_lo(u.z) + bf_hi(u.z) + bf_lo(u.w) + bf_hi(u.w);
              }
              s_misc[M_WSUM] = __float_as_uint(warp_sum(tot));
        }
              if (layer == 1) {
                const float2 ln = g_rowln[nb][mb * 128 + tid - 128];
                const uint32_t m2 = pack_bf16(ln.x, ln.x);
                uint8_t* row = smem + qo_off(0, wi & 2) + (tid & 63) * 128;
                mbar_wait(bar(B_RES), 1);
#pragma unroll 1
                for (int j = 0; j < 8; j++) {
                  uint4* c = (uint4*)(row + (((j + lane) & 7) << 4));
                  const uint4 v = c[0], w = c[512];
                  c[0] = make_uint4(add_ln_pair(v.x, m2, ln.y), add_ln_pair(v.y, m2, ln.y), add_ln_pair(v.z, m2, ln.y), add_ln_pair(v.w, m2, ln.y));
                  c[512] = make_uint4(add_ln_pair(w.x, m2, ln.y), add_ln_pair(w.y, m2, ln.y), add_ln_pair(w.z, m2, ln.y), add_ln_pair(w.w, m2, ln.y));
                }
                const int prow = (int)s_misc[M_SEL0] - mb * 128;
                __syncwarp();
                if (prow >> 5 == wi && lane < 16)
                  *(uint4*)(smem + qo_off(0, wi & 2) + (lane >> 3) * 8192 + (prow & 63) * 128 + (((lane ^ prow) & 7) << 4)) = poll4(&g_x2row[(nb * 16 + lane) * 2]);
                PROF(30);
              }
              __syncwarp();
              mbar_arrive_e(bar(B_RST));
        if (warp == 4) {
            named_bar(6, 320);
            spin_cycles(DELAY_S);
            uint4 c, u0, u1;
            uint32_t u2, best = 0, spins = 0;
            int src;
#pragma unroll 1
            for (;;) {
              src = (~best & 0x7FFu) >> 7;
              const uint4* xsel = &g_cand[layer][src * 128];
              c = ld_relaxed4(&g_slot[layer][(lane & 15) * 8]);
              u0 = ld_relaxed4(xsel + rank * 64 + lane); u1 = ld_relaxed4(xsel + rank * 64 + 32 + lane);
              u2 = ld_relaxed((const uint32_t*)(xsel + (bid >> 4) * 16 + q * 4) + (bid & 15));
              const uint32_t prev = best;
              best = __reduce_max_sync(0xffffffffu, c.w == tag ? c.x : 0u);
              if ((__all_sync(0xffffffffu, c.w == tag && valid4(u0) && valid4(u1) && u2 != SENT) && best == prev) || ++spins > SPIN_LIMIT) break;
            }
            const float sel_m = __uint_as_float(__shfl_sync(0xffffffffu, c.y, src)), sel_inv = __uint_as_float(__shfl_sync(0xffffffffu, c.z, src));
            const uint32_t m2 = pack_bf16(sel_m, sel_m);
            uint4* xs = (uint4*)(smem + T_XS) + (lane & 16) + q * 4 + (g & 3);
            xs[0] = make_uint4(ln_pair(u0.x, m2, sel_inv), ln_pair(u0.y, m2, sel_inv), ln_pair(u0.z, m2, sel_inv), ln_pair(u0.w, m2, sel_inv));
            xs[32] = make_uint4(ln_pair(u1.x, m2, sel_inv), ln_pair(u1.y, m2, sel_inv), ln_pair(u1.z, m2, sel_inv), ln_pair(u1.w, m2, sel_inv));
            s_misc[M_KEY] = best; s_misc[M_MEAN] = __float_as_uint(sel_m); s_misc[M_INV] = __float_as_uint(sel_inv);
            s_misc[M_XQ + q] = u2;
            if (layer == 0) s_misc[M_SEL0] = ~best & 0x7FFu;
            PROF(16);
        }
        if (layer == 1) {
          named_bar(7, 512);
          const int sel = SEQ - 1 - (int)(s_misc[M_KEY] & 0x7FFFu), skip = sel >> 7 == mb ? (sel >> 6) & 1 : -1;
          if (warp == 7) store_tile(1, skip, false);
          if (warp == 4) {
            mbar_wait_cluster(bar(B_HX), 1);
            ((bf16*)(smem + OFF_PATCH + 256))[((lane >> 1) & 3) * 8 + (lane >> 3) * 2 + (lane & 1)] = __float2bfloat16_rn(hidden());
            asm volatile("bar.arrive 10, 288;" ::: "memory");
          }
#pragma unroll 1
          for (int c = tid - 128; c < 1024 && skip >= 0; c += 128) {
            const int r = c >> 4;
            if (r != (sel & 63))
              *(uint4*)(P.out + (size_t)(mb * 128 + skip * 64 + r) * DM + nb * 128 + (c & 15) * 8) =
                  *(const uint4*)(smem + X_ST + skip * 16384 + ((c >> 3) & 1) * 8192 + r * 128 + (((c ^ r) & 7) << 4));
          }
          __syncwarp();
        } else asm volatile("bar.arrive 7, 512;" ::: "memory");
        if (warp == 5 && layer == 0) {
              named_bar(8, 288);
              if (nb > 0) spin_cycles(X_STAGGER);
              store_tile(0, -1, true);
              set_flag(&g_xflag[mb][nb].v[0], tag);
              PROF(17);
              poll_flag(&g_xflag[2 * rb + (lane & 1)][0].v[0], tag);
              fence_async_global();
#pragma unroll 1
              for (int i = 0; i < 4; i++) load_a(i, i, 1);
              PROFL(1, 1);
        }
      }
      named_bar(1 + (fresh_tid() >> 7), 128);
      regs_dec<32>();
#pragma unroll 1
      for (;;) {
      const unsigned pass = __shfl_sync(0xffffffffu, pass_v, 0);
      if (pass > 0) {
        const unsigned layer = pass - 1;
        PHASE_IDS
        const uint32_t tag = s_misc[M_TAG], bkey = s_misc[M_KEY];
        const int sel = SEQ - 1 - (int)(bkey & 0x7FFFu);
        if (warp == 3) {
          if (layer == 1) {
#pragma unroll
            for (int j = 0; j < 3; j++) ((uint4*)g_vw)[bid * 96 + j * 32 + lane] = make_uint4(0, 0, 0, 0);
          }
          if (bid == 0 && lane == 0) g_sel[layer] = sel;
        }
        __syncwarp();
        if (layer == 0) {
          auto load_down = [&](int j) {
            mbar_expect_tx(bar(B_DN + j), 2 * FFN_PIECE);
            bulk_load_h(sbase + SL_F + j * 2 * FFN_PIECE, P.w_d + (size_t)(bid * 28 + j * 14) * DM, 2 * FFN_PIECE, bar(B_DN + j), policy_evict_first());
          };
          if (warp == 5) {
            poll_flag(&g_xflag[2 * rb + (lane & 1)][(lane >> 1) & 7].v[0], tag);
            fence_async_global();
            load_a(4, 4, 1); load_a(5, 5, 1);
          }
          float hv = 0.f;
          if (wg == 1) { mbar_wait_cluster(bar(B_HX), 0); hv = rbf(hidden()); fence_regs<1>(&hv); }
          named_bar(9, 512);
          if (warp == 0) {
            fence_async_smem();
            if (lane < 16) mbar_arrive_cluster(bar(B_QFREE), lane & 1);
            mbar_wait(bar(B_QFREE), 1);
            load_w(4, 4); load_w(5, 5);
            load_down(0);
          } else if (wg == 1) {
            if (warp == 4) { mbar_wait(bar(B_DN), 0); load_down(1); }
            float d[8] = {0.f, 0.f, 0.f, 0.f, 0.f, 0.f, 0.f, 0.f};
            const uint4* wrow = (const uint4*)(smem + SL_F) + tid - 128;
            mbar_wait(bar(B_DN), 0);
            uint4 w0 = wrow[0];
#pragma unroll 1
            for (int j = 0; j < 28; j += 2) {
              const uint4 w1 = wrow[j * 128 + 128];
              fma8(d, w0, __shfl_sync(0xffffffffu, hv, j));
              if (j == 12) mbar_wait(bar(B_DN + 1), 0);
              w0 = wrow[min(j + 2, 27) * 128];
              fma8(d, w1, __shfl_sync(0xffffffffu, hv, j + 1));
            }
            uint4* dst = &g_ypart[0][bid * 256 + (tid - 128) * 2];
            st_relaxed4(dst, make_uint4(__float_as_uint(d[0]), __float_as_uint(d[1]), __float_as_uint(d[2]), __float_as_uint(d[3])));
            st_relaxed4(dst + 1, make_uint4(__float_as_uint(d[4]), __float_as_uint(d[5]), __float_as_uint(d[6]), __float_as_uint(d[7])));
            asm volatile("bar.arrive 11, 160;" ::: "memory");
            PROF(20);
          } else if (warp == 2) {
            named_bar(11, 160);
            fence_async_smem();
            load_ws(WS_PACE);
          }
        } else {
          if (wg == 1) named_bar(9, 384);
          cluster_arrive();
        }
        if (wg == 1) {
          const int t_y = (int)clock();
          const uint32_t xw = s_misc[M_XQ + ((lane & 7) >> 1)];
          const float x = (lane & 1) ? bf_hi(xw) : bf_lo(xw);
          float xn = rbf(rbf(x - __uint_as_float(s_misc[M_MEAN])) * __uint_as_float(s_misc[M_INV]));
          uint32_t u = bkey & 0xFFFF0000u;
          u = (u & 0x80000000u) ? (u & 0x7FFFFFFFu) : (~u & 0xFFFF0000u);
          float sg = rbf(__fdividef(1.f, 1.f + __expf(-__uint_as_float(u))));
          uint32_t* dst = (layer == 0 ? (uint32_t*)&g_x2row[bid * 2] : (uint32_t*)(P.out + (size_t)sel * DM + bid * 8)) + (lane >> 1);
          asm volatile("" : "+f"(xn), "+f"(sg), "+l"(dst));
#pragma unroll 1
          while ((int)clock() - t_y < DELAY_Y) {}
          const uint4* src = &g_ypart[layer][((tid - 128) >> 1) * 256 + bid * 2 + (tid & 1)];
          uint4 v, w;
          uint32_t spins = 0;
#pragma unroll 1
          do { v = ld_relaxed4(src); w = ld_relaxed4(src + 64 * 256); } while (!__all_sync(0xffffffffu, valid4(v) && valid4(w)) && ++spins < SPIN_LIMIT);
          float a[4] = {__uint_as_float(v.x) + __uint_as_float(w.x), __uint_as_float(v.y) + __uint_as_float(w.y),
                        __uint_as_float(v.z) + __uint_as_float(w.z), __uint_as_float(v.w) + __uint_as_float(w.w)};
          const bool b1 = lane & 2, b2 = lane & 4;
          float c0 = (b1 ? a[1] : a[0]) + __shfl_xor_sync(0xffffffffu, b1 ? a[0] : a[1], 2);
          float c1 = (b1 ? a[3] : a[2]) + __shfl_xor_sync(0xffffffffu, b1 ? a[2] : a[3], 2);
          float y = (b2 ? c1 : c0) + __shfl_xor_sync(0xffffffffu, b2 ? c0 : c1, 4);
          y += __shfl_xor_sync(0xffffffffu, y, 8);
          y += __shfl_xor_sync(0xffffffffu, y, 16);
          float* red = (float*)(smem + OFF_PATCH);
          red[wi * 8 + (lane & 1) * 4 + ((lane >> 1) & 3)] = y;
          named_bar(2, 128);
          if (warp == 4) {
            PROF(21);
            y = (red[lane & 7] + red[8 + (lane & 7)]) + (red[16 + (lane & 7)] + red[24 + (lane & 7)]);
            const float res = x + rbf(xn + rbf(rbf(y) * sg));
            const uint32_t pr = pack_bf16(res, __shfl_down_sync(0xffffffffu, res, 1));
            if (lane < 8 && (lane & 1) == 0) st_relaxed(dst, pr);
            PROF(22);
          }
        }
        if (pass == 2) {
          if (bid == 0 && tid == 128) g_epoch = tag;
          bulk_wait_all();
          __syncwarp();
          cluster_wait();
          return;
        }
      }
      const unsigned layer = pass;
      if (__shfl_sync(0xffffffffu, fresh_tid() >> 5, 0) > 1 - (int)layer) {
        PHASE_IDS
        uint4* xrow = (uint4*)(smem + SL_F + 4 * SL_HD);
        if (wg == 1) {
          if (layer == 0) {
            xrow[tid - 128] = make_uint4(0x3F803F80u, 0x3F803F80u, 0x3F803F80u, 0x3F803F80u);
            if (warp == 5) {
              mbar_wait(bar(B_FULL + 5), 0);
              if (lane == 0) {
#pragma unroll 1
                for (int i = 11; i > 0; i--) prefetch_tmap(&P.mapA[0] + i);
              }
              __syncwarp();
              load_ws(WS_PACE);
            }
          } else xrow[tid - 128] = poll4(&g_x2row[(tid - 128) * 2]);
          PROF(23);
        }
        named_bar(12, 192 + 32 * layer);
        if (warp == 1) {
          float mean = 0.f;
#pragma unroll 1
          for (int pass2 = 0; pass2 < 2; pass2++) {
            float acc = 0.f;
#pragma unroll 1
            for (int j = lane; j < 128; j += 32) {
              const uint4 v = xrow[j];
              const uint32_t w[4] = {v.x, v.y, v.z, v.w};
#pragma unroll
              for (int c = 0; c < 4; c++) {
                const float d0 = bf_lo(w[c]) - mean, d1 = bf_hi(w[c]) - mean;
                acc += pass2 ? d0 * d0 + d1 * d1 : d0 + d1;
              }
            }
            acc = warp_sum(acc) * (1.f / DM);
            if (pass2 == 0) mean = acc;
            else { s_misc[M_PMEAN] = __float_as_uint(rbf(mean)); s_misc[M_PINV] = __float_as_uint(ln_inv(acc)); }
          }
        } else {
          mbar_wait(bar(B_WS), layer);
          const uint8_t* wa = smem + SL_F + (g >> 1) * SL_HD + ((warp - 2) >> 1) * 4096 + (g & 1) * 2048;
          const uint32_t* xs = (const uint32_t*)xrow + rb * 64 + g * 8;
          const int ch = (warp & 1) * 4 + q;
          float d[8] = {0.f, 0.f, 0.f, 0.f, 0.f, 0.f, 0.f, 0.f};
          auto wrow = [&](int j) { j = (j ^ ((g & 1) * 4)) & 15; return *(const uint4*)(wa + j * 128 + (((ch ^ j) & 7) << 4)); };
          uint4 w0 = wrow(0);
#pragma unroll 1
          for (int j = 0; j < 16; j += 2) {
            const uint32_t xx = xs[(j >> 1) ^ ((g & 1) * 2)];
            const uint4 w1 = wrow(j + 1);
            fma8(d, w0, bf_lo(xx));
            w0 = wrow(j + 2);
            fma8(d, w1, bf_hi(xx));
          }
#pragma unroll
          for (int c = 0; c < 4; c++) d[c] = ((g & 4) ? d[c + 4] : d[c]) + __shfl_xor_sync(0xffffffffu, (g & 4) ? d[c] : d[c + 4], 16);
#pragma unroll
          for (int c = 0; c < 2; c++) d[c] = ((g & 2) ? d[c + 2] : d[c]) + __shfl_xor_sync(0xffffffffu, (g & 2) ? d[c] : d[c + 2], 8);
          d[0] = ((g & 1) ? d[1] : d[0]) + __shfl_xor_sync(0xffffffffu, (g & 1) ? d[0] : d[1], 4);
          st_relaxed(&g_vw[layer][rb][((warp - 2) >> 1) * DM + hp * 64 + ch * 8 + g], enc(d[0]));
        }
        named_bar(12, 192 + 32 * layer);
        PROF(24);
      }
      PHASE_IDS
      if (wg == 0) {
        if (warp == 0) {
          if (layer == 0) {
#pragma unroll 1
            for (int i = 2; i < 6; i++) { load_a(i, i, 0); load_w(i, i); }
          }
          int s = 0, u = 0;
#pragma unroll 1
          for (int i = 6; i < 32; i++) {
            if (layer == 1) mbar_arrive_e(bar(B_EMPTY + s));
            mbar_wait(bar(B_EMPTY + s), (u + (s > 1 ? 0 : layer)) & 1);
            load_w(s, i);
            load_a(s, i, layer);
            if (++s == 6) { s = 0; u++; }
          }
        } else if (warp == 1) {
          if (layer == 0) {
            const uint32_t tag = ld_relaxed(&g_epoch) + 1;
            if (lane < 16) g_rowab[0][rb * 256 + hp * 16 + lane] = make_uint4(0, 0, 0, 0);
            float shift = 0.f, sum = 0.f, sq = 0.f;
            const int r = hp * 16 + (lane >> 1);
#pragma unroll 1
            for (int i = 0; i < 32; i++) {
              mbar_wait(bar(B_FULL + i % 6), (i / 6) & 1);
              const uint8_t* base = smem + (i % 6) * QE + r * 64 + (lane & 1) * 32;
              uint4 v[2];
#pragma unroll
              for (int j = 0; j < 2; j++) v[j] = *(const uint4*)(base + ((j ^ ((r >> 1) & 1)) << 4));
              if (i == 0) shift = __shfl_sync(0xffffffffu, bf_lo(v[0].x), lane & ~1);
#pragma unroll
              for (int j = 0; j < 2; j++) {
                const uint32_t w[4] = {v[j].x, v[j].y, v[j].z, v[j].w};
#pragma unroll
                for (int c = 0; c < 4; c++) {
                  const float d0 = bf_lo(w[c]) - shift, d1 = bf_hi(w[c]) - shift;
                  sum += d0 + d1; sq = fmaf(d0, d0, fmaf(d1, d1, sq));
                }
              }
              fence_async_smem();
              __syncwarp();
              if (i < 26) mbar_arrive_e(bar(B_EMPTY + i % 6));
            }
            sum += __shfl_xor_sync(0xffffffffu, sum, 1); sq += __shfl_xor_sync(0xffffffffu, sq, 1);
            const float dm = sum * (1.f / DM), var = fmaxf(sq * (1.f / DM) - dm * dm, 0.f), mean = shift + dm;
            const float inv = ln_inv(var);
            if ((lane & 1) == 0) st_relaxed4(&g_rowab[0][rb * 256 + r], make_uint4(__float_as_uint(inv), __float_as_uint(rbf(mean) * inv), tag, 0));
          }
          __syncwarp();
          mbar_arrive_e(bar(B_E23));
          if (rb == 0) {
            mbar_wait(bar(B_QDONE), layer);
#pragma unroll 1
            for (int j = lane; j < 512; j += 32) ((uint4*)(smem + kv_off(1, 0)))[j] = make_uint4(0, 0, 0, 0);
            fence_async_smem();
            __syncwarp();
            if (lane < 3) mbar_arrive(bar(B_HALO + lane));
          }
        } else if (warp == 3) {
          if (rb > 0) { mbar_expect_tx(bar(B_HALO), 16384); mbar_expect_tx(bar(B_HALO + 1), 16384); mbar_expect_tx(bar(B_HALO + 2), 32768); }
          fence_async_smem();
          load_gu(0, layer ? GU_PACE1 : GU_PACE);
          PROF(27);
        } else {
          const uint4 sent = make_uint4(SENT, SENT, SENT, SENT), zero = make_uint4(0, 0, 0, 0);
          if (layer == 0) {
            const int f = lane >> 1;
            Flag* fl = f < 2 ? &g_kvflag[rb >> 1][hp][f] : f < 4 ? &g_oflag[rb][f & 1][hp] : &g_xflag[mb][nb];
            if (f < 5 && (f >= 2 || (rank == 1 && rb < 7))) ((uint4*)fl)[lane & 1] = zero;
          }
#pragma unroll 1
          for (int t = lane; t < 128; t += 32) {
            g_ypart[layer][bid * 256 + t] = sent; g_ypart[layer][bid * 256 + 128 + t] = sent;
            g_part[layer][nb * SEQ + mb * 128 + t] = zero;
            if (t < 16) g_cand[layer][mb * 128 + nb * 16 + t] = sent;
            else if (t < 18) { if (nb == 0) g_slot[layer][mb * 8 + t - 16] = zero; }
            else if (t < 20) { if (layer == 0) g_x2row[bid * 2 + t - 18] = sent; }
          }
          __syncwarp();
          mbar_arrive_e(bar(B_CS));
        }
        __syncwarp();
        uint8_t* kvg = g_kv + (size_t)(((rb - 1 + rank) >> 1) * 16 + hp) * 65536;
        if (rank == 0) {
          if (warp == 0) {
            mbar_wait(bar(B_QDONE), layer);
#pragma unroll 1
            for (int j = 0; j < 4; j++) {
              mbar_wait(bar(B_KVREADY + (j >> 1)), layer);
              bulk_push(mapa(sbase + kv_off(j & 1, 2 - (j & 2)), 1), sbase + kv_off(j & 1, 6 - (j & 2)), 16384, mapa(bar(B_HALO + min(j, 2)), 1));
            }
          } else if (warp < 3 && rb > 0) {
            const int p = warp - 1;
            mbar_wait(bar(B_QREADY), layer);
            if (p) spin_cycles(P1_DELAY);
            poll_flag(&g_kvflag[(rb - 1) >> 1][hp][p].v[layer], s_misc[M_TAG]);
            fence_async_global();
#pragma unroll 1
            for (int j = 2 * p; j < 2 * p + 2; j++) bulk_load_h(sbase + kv_off(j & 1, 2 - (j & 2)), kvg + j * 16384, 16384, bar(B_HALO + min(j, 2)), policy_evict_first());
            if (p == 0) PROF(5);
          }
        } else if (warp < 2 && rb < 7) {
          mbar_wait(bar(B_KVREADY + warp), layer);
          if (warp == 1) named_bar(13, 64);
#pragma unroll 1
          for (int j = 2 * warp; j < 2 * warp + 2; j++) bulk_store(kvg + j * 16384, sbase + kv_off(j & 1, 6 - (j & 2)), 16384);
          bulk_commit();
          bulk_wait_all();
          if (warp == 0) asm volatile("bar.arrive 13, 64;" ::: "memory");
          set_flag(&g_kvflag[rb >> 1][hp][warp].v[layer], s_misc[M_TAG]);
          if (warp == 0) PROF(4);
        }
      } else {
        const int t = tid - 128, go = (t >> 5) * DM + hp * 64 + (t & 31) * 2;
        if (layer == 0 && t == 96) { s_misc[M_TAG] = ld_relaxed(&g_epoch) + 1; s_misc[M_SEL0] = 0xFFFFFFFFu; s_misc[M_PROG] = s_misc[M_PROG + 1] = 0; }
        if ((layer == 0 || (int)s_misc[M_SEL0] >> 8 == rb) && warp < 7) {
          spin_cycles(layer ? 300 : 1500);
          uint2 w[8];
          uint32_t spins = 0;
          bool ok;
#pragma unroll 1
          do {
            ok = true;
#pragma unroll
            for (int j = 0; j < 8; j++) w[j] = ld_relaxed2(&g_vw[layer][j][go]);
#pragma unroll
            for (int j = 0; j < 8; j++) ok = ok && w[j].x && w[j].y;
          } while (!__all_sync(0xffffffffu, ok) && ++spins < SPIN_LIMIT);
          float s0 = 0.f, s1 = 0.f;
#pragma unroll
          for (int j = 0; j < 8; j++) { s0 += dec(w[j].x); s1 += dec(w[j].y); }
          float2* csp = (float2*)(smem + OFF_CS) + (t & ~7) + (t & 3) * 2 + ((t >> 2) & 1);
          if (layer == 0) *csp = make_float2(s0, s1);
          else {
            const float2 c = *csp;
            const float a = __uint_as_float(s_misc[M_PINV]) * (warp == 4 ? SM_C : 1.f), b = __uint_as_float(s_misc[M_PMEAN]) * a;
            ((uint32_t*)(smem + OFF_PATCH))[t] = pack_bf16(s0 * a - c.x * b, s1 * a - c.y * b);
          }
          PROF(25);
        }
        __syncwarp();
        mbar_arrive_e(bar(B_CS));
      }
      __syncwarp();
      if (wi == 0) mbar_wait(bar(B_QREADY), layer);
      named_bar(1 + (fresh_tid() >> 7), 128);
      if (__shfl_sync(0xffffffffu, fresh_tid() >> 7, 0) == 0) {
        regs_inc<152>();
        uint32_t gu[112];
        {
          PHASE_IDS
          const uint32_t tag = s_misc[M_TAG];
          mbar_wait(bar(B_GU), layer);
#pragma unroll
          for (int j = 0; j < 28; j++) fetch_gu(gu + 4 * j, warp * 4 + (j & 3), j >> 2);
          fence_async_smem();
          named_bar(1, 128);
          if (warp == 0) {
            mbar_wait(bar(B_ADONE), layer);
#pragma unroll 1
            for (int k = 2; k < 16; k++) {
#pragma unroll 1
              for (uint32_t spins = 0; (int)s_misc[M_PROG + (k >> 3)] <= (k & 7) + 16 * (int)layer && spins < SPIN_LIMIT; spins++) {}
              if (k >= 4) mbar_wait(bar(B_WEMPTY + (k & 3)), ((k >> 2) - 1 + ((k & 2) ? layer : 0)) & 1);
              load_o(k); load_wo(k);
              STEPT(16 + k);
              if (k == RES_K) { mbar_wait(bar(B_OST + 1), layer); load_res(1, layer); }
            }
            if (layer == 1) {
              mbar_wait(bar(B_WEMPTY + 1), 1);
              mbar_expect_tx(bar(B_DN), 4 * FFN_PIECE);
              tma_load3_h(sbase + wo_off(0), &P.mapD, 0, bid * 28, 0, bar(B_DN), policy_evict_first());
            }
            named_bar(6, 320);
            if (layer == 0) {
              mbar_wait(bar(B_QFREE), 0);
#pragma unroll 1
              for (int i = 0; i < 4; i++) load_w(i, i);
            } else tma_load3_h(sbase + wo_off(0) + 2 * FFN_PIECE, &P.mapD, 0, bid * 28, 8, bar(B_DN), policy_evict_first());
          } else if (warp < 3) {
            const int h = warp - 1;
#pragma unroll 1
            for (int qb = 3; qb >= 0; qb--) {
              mbar_wait(bar(B_UNIT + h * 4 + 3 - qb), layer);
              bulk_store(g_o + (size_t)((((rb * 2 + (qb >> 1)) * 2 + h) * 16 + hp) * 2 + (qb & 1)) * 4096, sbase + qo_off(h, qb), 4096);
            }
            bulk_commit();
            if (h == 0 && lane < 2) mbar_arrive_cluster(bar(B_OST), lane);
            bulk_wait_all();
            if (h == 1) mbar_arrive_e(bar(B_OST + 1));
            set_flag(&g_oflag[rb][h][hp].v[layer], tag);
            PROF(28 + 3 * h);
            if (h == 0) { load_res(0, layer); mbar_wait(bar(B_OST), layer); load_wo(0); load_wo(1); }
            int n = 0, first = h;
#pragma unroll 1
            for (uint32_t spins = 0; n < 8 && spins < SPIN_LIMIT; spins++) {
              n = (__ffs(__ballot_sync(0xffffffffu, ld_relaxed(&g_oflag[rb][h][lane & 15].v[layer]) != tag || lane == 16)) - 1) >> 1;
              asm volatile("fence.acquire.gpu;" ::: "memory");
              fence_async_global();
              if (!first && n >= 2) {
                first = 1;
                load_o(0); load_o(1);
                PROF(15);
              }
              s_misc[M_PROG + h] = n + 16 * layer;
            }
            if (h) PROF(26);
          } else {
            mbar_expect_tx(bar(B_HX), 2240);
            mbar_wait(bar(B_HALO + 2), layer);
            if (rb == 0) spin_cycles(2000);
            PROF(6);
            load_gu(1, GUB_PACE);
          }
        }
        PHASE_IDS
        uint4 xa = {}, xb = {};
        named_bar(7, 512);
        if (g == 0) { xa = ((const uint4*)(smem + T_XS))[warp * 8 + q]; xb = ((const uint4*)(smem + T_XS))[warp * 8 + 4 + q]; }
        __syncwarp();
        float d[7][4] = {};
#pragma unroll
        for (int j = 0; j < 28; j++) {
          const int ks = j / 7, ct = j % 7;
          const uint32_t* a = gu + ct * 16 + ks * 4;
          mma_16816(d[ct], a[0], a[1], a[2], a[3], ks == 0 ? xa.x : ks == 1 ? xa.z : ks == 2 ? xb.x : xb.z, ks == 0 ? xa.y : ks == 1 ? xa.w : ks == 2 ? xb.y : xb.w);
        }
#pragma unroll
        for (int ct = 0; ct < 7; ct++) send_gu(d[ct][0], d[ct][2], ct, warp);
        __syncwarp();
        if (warp == 2) PROF(18);
        regs_dec<32>();
        pass_v = pass + 1;
        continue;
      }
      break;
      }
      regs_inc<120>();
    }
    const unsigned layer = pass;
    {
      PHASE_IDS
      mbar_wait(bar(B_QREADY), layer);
      if (warp != 9) STEPT(7);
      const int bmin = rb == 0 ? 4 : 0;
      auto kdesc = [&](int h, int b) { const uint32_t v = dlo(SOFF, 16) + (kv_off(h, b) >> 4); return b < bmin ? dlo(SOFF + kv_off(1, 0), 16) : v; };
      auto vdesc = [&](int h, int b) {
        const uint32_t v = dlo(SOFF + 4096, OFF_ONES - 4096) + (kv_off(h, b) >> 10) * VSTEP;
        return b < bmin ? dlo(SOFF + kv_off(1, 0), 4096) : v;
      };
      const int units = wg == 3 ? 0x8630 : (wg == 2 ? 0x8721 : 0x854);
      auto need = [&](int h, int b) { if (b == 3 || b == 1) mbar_wait(bar(B_HALO + (b == 1 ? 2 : h)), layer); };
      auto load_q = [&](uint32_t* qf, int u) {
        *(uint4*)&qf[0] = *(const uint4*)(smem + qo_off(u >> 2, ~u & 3) + wi * 1024 + lane * 16);
        *(uint4*)&qf[4] = *(const uint4*)(smem + qo_off(u >> 2, ~u & 3) + wi * 1024 + 512 + lane * 16);
      };
      auto store_o = [&](const float* o, int u) {
        const float i0 = rcp(o[16]), i1 = rcp(o[18]);
        if (u >= 4 && lane < 2) mbar_arrive_cluster(bar(B_ADONE), lane);
#pragma unroll
        for (int j = 0; j < 2; j++)
          stsm_x4(sbase + qo_off(u >> 2, ~u & 3) + srow * 64 + (((2 * j + (mi >> 1)) ^ ((srow >> 1) & 3)) << 4),
                  pack_bf16(o[8 * j] * i0, o[8 * j + 1] * i0), pack_bf16(o[8 * j + 2] * i1, o[8 * j + 3] * i1),
                  pack_bf16(o[8 * j + 4] * i0, o[8 * j + 5] * i0), pack_bf16(o[8 * j + 6] * i1, o[8 * j + 7] * i1));
        fence_async_smem();
        __syncwarp();
        mbar_arrive_e(bar(B_UNIT + u));
      };
      int redo = 0;
      {
        const int dl = g - 2 * q;
        const uint32_t mt = shl_clamp(0xFFFFFFFFu, max(16 * dl + 16, 0));
        uint32_t qf[8];
        float s[32];
        load_q(qf, units & 7);
        wg_fence();
        qk64(s, qf, kdesc((units >> 2) & 1, 6 - (units & 3)));
        wg_commit();
        wg_wait<0>();
        fence_regs<32>(s);
#pragma unroll 1
        for (int ul = units; ul != 8; ul >>= 4) {
          const int u = ul & 7, h = u >> 2, qb = 3 - (u & 3);
          float o[20];
          uint32_t p1[16], p2[16], p3[16], p4[16], p5[16];
          if (warp != 9) STEPT(8 + nu * 8);
          exp_pack<8>(s, p1);
          fence_regs_u<16>(p1);
          need(h, qb + 2);
          {
            float s2[32];
            const uint32_t vd = vdesc(h, qb + 3);
            wg_fence();
            qk64(s2, qf, kdesc(h, qb + 2));
            wg_commit();
            wg_rs40t_z<H64>(o, p1[0], p1[1], p1[2], p1[3], vd);
            wg_rs40t<H64>(o, p1[4], p1[5], p1[6], p1[7], vd + VSTEP, 1);
            pv32(o, p1 + 8, vd + 2 * VSTEP);
            wg_commit();
            wg_wait<1>();
            fence_regs<32>(s2);
            if (warp != 9) STEPT(9 + nu * 8);
            exp_pack<8>(s2, p2);
            fence_regs_u<16>(p2);
            wg_wait<0>();
            fence_regs<20>(o);
          }
          need(h, qb + 1);
          {
            float s3[32];
            wg_fence();
            qk64(s3, qf, kdesc(h, qb + 1));
            wg_commit();
            pv32(o, p2, vdesc(h, qb + 2)); pv32(o, p2 + 8, vdesc(h, qb + 2) + 2 * VSTEP);
            wg_commit();
            wg_wait<1>();
            fence_regs<32>(s3);
            if (warp != 9) STEPT(10 + nu * 8);
            exp_pack<8>(s3, p3);
            fence_regs_u<16>(p3);
            wg_wait<0>();
            fence_regs<20>(o);
          }
          need(h, qb);
          const uint32_t kd = kdesc(h, qb + 4), kt = kdesc(h, qb), vd = vdesc(h, qb + 4), vt = vdesc(h, qb);
          {
            float sd[16], st[16];
            wg_fence();
            qk32x2(sd, st, qf, kd, kt);
            wg_commit();
            pv32(o, p3, vdesc(h, qb + 1)); pv32(o, p3 + 8, vdesc(h, qb + 1) + 2 * VSTEP);
            wg_commit();
            wg_wait<1>();
            fence_regs<16>(sd); fence_regs<16>(st);
            if (warp != 9) STEPT(11 + nu * 8);
            edge32(sd, st, p4, p4 + 8, wi, dl, mt);
            fence_regs_u<16>(p4);
            wg_wait<0>();
            fence_regs<20>(o);
          }
          const int un = (ul >> 4) == 8 ? 4 : (ul >> 4) & 7;
          {
            float sd[16], st[16];
            wg_fence();
            qk32x2(sd, st, qf, kd + 128, kt + 128);
            wg_commit();
            pv32(o, p4, vd); pv32(o, p4 + 8, vt);
            wg_commit();
            wg_wait<1>();
            fence_regs<16>(sd); fence_regs<16>(st);
            load_q(qf, un);
            edge32(sd, st, p5, p5 + 8, wi - 2, dl, mt);
            fence_regs_u<16>(p5);
          }
          need(un >> 2, 6 - (un & 3));
          wg_fence();
          pv32(o, p5, vd + 2 * VSTEP); pv32(o, p5 + 8, vt + 2 * VSTEP);
          wg_commit();
          qk64(s, qf, kdesc(un >> 2, 6 - (un & 3)));
          wg_commit();
          wg_wait<1>();
          fence_regs<20>(o);
          if (warp != 9) STEPT(12 + nu * 8);
          const bool unsafe = !(o[16] >= LSUM_MIN && o[16] <= LSUM_MAX && o[18] >= LSUM_MIN && o[18] <= LSUM_MAX);
          if (__any_sync(0xffffffffu, unsafe)) redo |= 1 << u;
          else store_o(o, u);
          wg_wait<0>();
          fence_regs<32>(s);
        }
      }
      if (warp != 9) STEPT(31);
      if (bar_red_or(1 + wg, 128, redo)) {
#pragma unroll 1
        for (int ul = units; ul != 8; ul >>= 4) {
          const int u = ul & 7;
          if (!bar_red_or(1 + wg, 128, redo >> u & 1)) continue;
          const int h = u >> 2, qb = 3 - (u & 3);
          uint32_t qf[8], p[16];
          float o[20], m0 = -INFINITY, m1 = -INFINITY;
          load_q(qf, u);
#pragma unroll
          for (int i = 0; i < 20; i++) o[i] = 0.f;
#pragma unroll 1
          for (int j = 0; j <= (rb == 0 ? qb : 4); j++) {
            const int b = qb + 4 - j;
            float s[32];
            wg_fence();
            qk64(s, qf, kdesc(h, b));
            wg_commit();
            wg_wait<0>();
            fence_regs<32>(s);
            float mx0 = m0, mx1 = m1;
#pragma unroll
            for (int c = 0; c < 8; c++) {
#pragma unroll
              for (int i = 0; i < 4; i++) {
                const int diff = j * 64 + (16 * wi + g + (i >> 1) * 8) - (8 * c + 2 * q + (i & 1));
                if (diff < 0 || diff > 255) s[4 * c + i] = -INFINITY;
              }
              mx0 = fmaxf(mx0, fmaxf(s[4 * c], s[4 * c + 1]));
              mx1 = fmaxf(mx1, fmaxf(s[4 * c + 2], s[4 * c + 3]));
            }
            mx0 = fmaxf(mx0, __shfl_xor_sync(0xffffffffu, mx0, 1)); mx1 = fmaxf(mx1, __shfl_xor_sync(0xffffffffu, mx1, 1));
            mx0 = fmaxf(mx0, __shfl_xor_sync(0xffffffffu, mx0, 2)); mx1 = fmaxf(mx1, __shfl_xor_sync(0xffffffffu, mx1, 2));
            const float r0 = j == 0 ? 0.f : ex2(m0 - mx0), r1 = j == 0 ? 0.f : ex2(m1 - mx1);
            m0 = mx0; m1 = mx1;
#pragma unroll
            for (int i = 0; i < 5; i++) { o[4 * i] *= r0; o[4 * i + 1] *= r0; o[4 * i + 2] *= r1; o[4 * i + 3] *= r1; }
#pragma unroll
            for (int c = 0; c < 8; c++) { s[4 * c] -= m0; s[4 * c + 1] -= m0; s[4 * c + 2] -= m1; s[4 * c + 3] -= m1; }
            exp_pack<8>(s, p);
            fence_regs<20>(o); fence_regs_u<16>(p);
            wg_fence();
            pv32(o, p, vdesc(h, b)); pv32(o, p + 8, vdesc(h, b) + 2 * VSTEP);
            wg_commit();
            wg_wait<0>();
            fence_regs<20>(o);
          }
          named_bar(1 + wg, 128);
          if (redo >> u & 1) store_o(o, u);
          __syncwarp();
        }
      }
      if (wi == 0) PROF(6 + wg);
    }
    pass_v = pass + 1;
  }
}

}

typedef CUresult (*EncodeFn)(CUtensorMap*, CUtensorMapDataType, cuuint32_t, void*, const cuuint64_t*, const cuuint64_t*,
                             const cuuint32_t*, const cuuint32_t*, CUtensorMapInterleave, CUtensorMapSwizzle,
                             CUtensorMapL2promotion, CUtensorMapFloatOOBfill);
static EncodeFn g_encode = nullptr;
struct Dim { uint64_t size, stride; uint32_t box; };
template <int N> static CUtensorMap make_map(const void* ptr, const Dim (&d)[N], int swizzle) {
  CUtensorMap m;
  cuuint64_t dims[N], strides[N];
  cuuint32_t box[N], es[N];
  for (int i = 0; i < N; i++) { dims[i] = d[i].size; strides[i] = d[i].stride; box[i] = d[i].box; es[i] = 1; }
  g_encode(&m, CU_TENSOR_MAP_DATA_TYPE_BFLOAT16, N, const_cast<void*>(ptr), dims, strides + 1, box, es, CU_TENSOR_MAP_INTERLEAVE_NONE,
           swizzle == 128 ? CU_TENSOR_MAP_SWIZZLE_128B : (swizzle == 64 ? CU_TENSOR_MAP_SWIZZLE_64B : CU_TENSOR_MAP_SWIZZLE_NONE),
           swizzle ? CU_TENSOR_MAP_L2_PROMOTION_L2_256B : CU_TENSOR_MAP_L2_PROMOTION_L2_128B, CU_TENSOR_MAP_FLOAT_OOB_FILL_NONE);
  return m;
}
static CUtensorMap map2(const void* ptr, uint64_t inner, uint64_t outer, uint32_t bi, uint32_t bo, int swizzle) {
  const Dim d[2] = {{inner, 0, bi}, {outer, inner * 2, bo}};
  return make_map(ptr, d, swizzle);
}
template <class T> static void* sym_addr(T& sym) { void* p = nullptr; cudaGetSymbolAddress(&p, sym); return p; }

static Params h_p;
static const void* h_key[9];

static cudaLaunchConfig_t launch_cfg(int grid, cudaLaunchAttribute* at) {
  cudaLaunchConfig_t cfg = {};
  cfg.gridDim = dim3(grid); cfg.blockDim = dim3(512); cfg.dynamicSmemBytes = SMEM_BYTES; cfg.stream = cudaStreamPerThread;
  at[0].id = cudaLaunchAttributeClusterDimension;
  at[0].val.clusterDim.x = 2; at[0].val.clusterDim.y = 1; at[0].val.clusterDim.z = 1;
  cfg.attrs = at; cfg.numAttrs = 1;
  return cfg;
}

extern "C" void kernel_launch(void* const* d_in, const int* in_sizes, int n_in, void* d_out, int out_size) {
  const bf16* x = (const bf16*)d_in[0];
  const bf16* wqkv = (const bf16*)d_in[1];
  const bf16* wo = (const bf16*)d_in[2];
  cudaLaunchAttribute at[1];
  bool fresh = g_encode != nullptr && h_key[8] == d_out;
  for (int i = 0; i < 8; i++) fresh = fresh && h_key[i] == d_in[i];
  if (!fresh) {
    if (!g_encode) {
      void* fn = nullptr;
      cudaDriverEntryPointQueryResult st;
      cudaGetDriverEntryPoint("cuTensorMapEncodeTiled", &fn, cudaEnableDefault, &st);
      g_encode = (EncodeFn)fn;
      cudaFuncSetAttribute(mega_kernel, cudaFuncAttributeMaxDynamicSharedMemorySize, SMEM_BYTES);
    }
    bf16* x1 = (bf16*)sym_addr(g_x1);
    Params& p = h_p;
    p.w_r = (const bf16*)d_in[4]; p.w_d = (const bf16*)d_in[7];
    p.out = (bf16*)d_out;
    p.mapA[0] = map2(x, DM, SEQ, 32, 256, 64);
    p.mapA[1] = map2(x1, DM, SEQ, 32, 256, 64);
    { const Dim d[3] = {{DM, 0, 64}, {DM, 3 * DM * 2, 16}, {3, DM * 2, 3}}; p.mapW = make_map(wqkv, d, 128); }
    { const Dim d[3] = {{DM, 0, 64}, {DM, 3 * DM * 2, 32}, {3, DM * 2, 3}}; p.mapWs = make_map(wqkv, d, 128); }
    { const Dim d[3] = {{DM, 0, 64}, {64, DM * 2, 32}, {16, 64 * DM * 2, 2}}; p.mapWo = make_map(wo, d, 128); }
    p.mapRes[0] = map2(x, DM, SEQ, 64, 64, 128);
    p.mapRes[1] = p.mapXst[0] = map2(x1, DM, SEQ, 64, 64, 128);
    p.mapXst[1] = map2(d_out, DM, SEQ, 64, 64, 128);
    p.mapG = map2(d_in[5], FF, DM, 56, 128, 0);
    p.mapU = map2(d_in[6], FF, DM, 56, 128, 0);
    { const Dim d[3] = {{64, 0, 64}, {FF, DM * 2, 28}, {DM / 64, 128, 8}}; p.mapD = make_map(p.w_d, d, 128); }
    for (int i = 0; i < 8; i++) h_key[i] = d_in[i];
    h_key[8] = d_out;
  }
  void* a0[] = {&h_p};
  cudaLaunchConfig_t cfg = launch_cfg(128, at);
  cudaLaunchKernelExC(&cfg, (const void*)mega_kernel, a0);
}
```

```cpp
#include <cuda_runtime.h>
#include <cuda_bf16.h>
#include <cuda.h>
#include <stdint.h>
#pragma nv_diag_suppress 550

namespace {

constexpr int SEQ = 2048, DM = 1024, FF = 3584;
constexpr float LN_EPS = 1e-5f;
typedef __nv_bfloat16 bf16;

__device__ __align__(1024) uint8_t g_kv[3 * 16 * 65536];
__device__ __align__(1024) uint8_t g_o[SEQ * DM * 2];
__device__ __align__(1024) bf16 g_x1[SEQ * DM];
__device__ unsigned g_epoch;
struct __align__(128) Flag { unsigned v[32]; };
__device__ Flag g_kvflag[3][16][2], g_oflag[8][2][16], g_xflag[16][8];
__device__ uint4 g_rowab[2][SEQ];
__device__ __align__(16) uint32_t g_vw[2][8][3 * DM];
constexpr uint32_t SENT = 0xFFFFFFFFu;
__device__ uint4 g_part[2][8 * SEQ];
__device__ uint4 g_slot[2][16 * 8];
__device__ uint4 g_cand[2][16 * 128];
__device__ uint4 g_ypart[2][128 * DM / 4];
__device__ uint4 g_x2row[128 * 2];
__device__ float2 g_rowln[8][SEQ];
__device__ int g_sel[2];

#define PROFL(l, e)
#define PROF(e) PROFL(layer, e)
#define STEPT(i)
#define SPIN_LIMIT 4000000u
__device__ __forceinline__ uint32_t smem_u32(const void* p) { return (uint32_t)__cvta_generic_to_shared(p); }
__device__ __forceinline__ void mbar_init(uint32_t bar, uint32_t cnt) {
  asm volatile("mbarrier.init.shared::cta.b64 [%0], %1;" ::"r"(bar), "r"(cnt) : "memory");
}
#define ELECT "{\n.reg .pred e;\nelect.sync _|e, 0xffffffff;\n@e "
__device__ __forceinline__ void mbar_expect_tx(uint32_t bar, uint32_t bytes) {
  asm volatile(ELECT "mbarrier.arrive.expect_tx.shared::cta.b64 _, [%0], %1;\n}" ::"r"(bar), "r"(bytes) : "memory");
}
__device__ __forceinline__ void mbar_arrive(uint32_t bar) {
  asm volatile("mbarrier.arrive.shared::cta.b64 _, [%0];" ::"r"(bar) : "memory");
}
__device__ __forceinline__ void mbar_arrive_e(uint32_t bar) {
  asm volatile(ELECT "mbarrier.arrive.shared::cta.b64 _, [%0];\n}" ::"r"(bar) : "memory");
}
__device__ __forceinline__ uint32_t mapa(uint32_t addr, uint32_t cta) {
  uint32_t r; asm("mapa.shared::cluster.u32 %0, %1, %2;" : "=r"(r) : "r"(addr), "r"(cta)); return r;
}
__device__ __forceinline__ void mbar_arrive_cluster(uint32_t bar, uint32_t cta) {
  asm volatile("mbarrier.arrive.shared::cluster.b64 _, [%0];" ::"r"(mapa(bar, cta)) : "memory");
}
#define MBAR_WAIT_ASM(QUAL)                                                                                                \
  asm volatile("{\n.reg .pred p;\nWAIT_LOOP:\n.pragma \"nounroll\";\nmbarrier.try_wait.parity" QUAL ".shared::cta.b64 p, [%0], %1;\n" \
               "@!p bra WAIT_LOOP;\n}" ::"r"(bar), "r"(parity) : "memory")
__device__ __forceinline__ void mbar_wait(uint32_t bar, uint32_t parity) { MBAR_WAIT_ASM(""); }
__device__ __forceinline__ void mbar_wait_cluster(uint32_t bar, uint32_t parity) { MBAR_WAIT_ASM(".acquire.cluster"); }
__device__ __forceinline__ void st_async2(uint32_t addr, float a, float b, uint32_t bar) {
  asm volatile("st.async.weak.shared::cluster.mbarrier::complete_tx::bytes.v2.f32 [%0], {%1, %2}, [%3];"
               ::"r"(addr), "f"(a), "f"(b), "r"(bar) : "memory");
}
__device__ __forceinline__ uint64_t policy_evict_first() {
  uint64_t p; asm volatile("createpolicy.fractional.L2::evict_first.b64 %0, 1.0;" : "=l"(p)); return p;
}
__device__ __forceinline__ void tma_load2(uint32_t dst, const CUtensorMap* m, int c0, int c1, uint32_t bar) {
  asm volatile(ELECT "cp.async.bulk.tensor.2d.shared::cluster.global.mbarrier::complete_tx::bytes [%0], [%1, {%3, %4}], [%2];\n}"
               ::"r"(dst), "l"(m), "r"(bar), "r"(c0), "r"(c1) : "memory");
}
__device__ __forceinline__ void tma_load2_h(uint32_t dst, const CUtensorMap* m, int c0, int c1, uint32_t bar, uint64_t pol) {
  asm volatile(ELECT "cp.async.bulk.tensor.2d.shared::cluster.global.mbarrier::complete_tx::bytes.L2::cache_hint [%0], [%1, {%3, %4}], [%2], %5;\n}"
               ::"r"(dst), "l"(m), "r"(bar), "r"(c0), "r"(c1), "l"(pol) : "memory");
}
__device__ __forceinline__ void tma_load3(uint32_t dst, const CUtensorMap* m, int c0, int c1, int c2, uint32_t bar) {
  asm volatile(ELECT "cp.async.bulk.tensor.3d.shared::cluster.global.mbarrier::complete_tx::bytes [%0], [%1, {%3, %4, %5}], [%2];\n}"
               ::"r"(dst), "l"(m), "r"(bar), "r"(c0), "r"(c1), "r"(c2) : "memory");
}
__device__ __forceinline__ void tma_load3_h(uint32_t dst, const CUtensorMap* m, int c0, int c1, int c2, uint32_t bar, uint64_t pol) {
  asm volatile(ELECT "cp.async.bulk.tensor.3d.shared::cluster.global.mbarrier::complete_tx::bytes.L2::cache_hint [%0], [%1, {%3, %4, %5}], [%2], %6;\n}"
               ::"r"(dst), "l"(m), "r"(bar), "r"(c0), "r"(c1), "r"(c2), "l"(pol) : "memory");
}
__device__ __forceinline__ void tma_load3_mc(uint32_t dst, const CUtensorMap* m, int c0, int c1, int c2, uint32_t bar) {
  asm volatile(ELECT "cp.async.bulk.tensor.3d.shared::cluster.global.mbarrier::complete_tx::bytes.multicast::cluster [%0], [%1, {%3, %4, %5}], [%2], %6;\n}"
               ::"r"(dst), "l"(m), "r"(bar), "r"(c0), "r"(c1), "r"(c2), "h"((uint16_t)3) : "memory");
}
__device__ __forceinline__ void bulk_push(uint32_t dst, uint32_t src, uint32_t bytes, uint32_t bar) {
  asm volatile(ELECT "cp.async.bulk.shared::cluster.shared::cta.mbarrier::complete_tx::bytes [%0], [%1], %2, [%3];\n}"
               ::"r"(dst), "r"(src), "r"(bytes), "r"(bar) : "memory");
}
template <int N> __device__ __forceinline__ void regs_inc() { asm volatile("setmaxnreg.inc.sync.aligned.u32 %0;" ::"n"(N)); }
template <int N> __device__ __forceinline__ void regs_dec() { asm volatile("setmaxnreg.dec.sync.aligned.u32 %0;" ::"n"(N)); }
__device__ __forceinline__ void tma_store(const CUtensorMap* m, uint32_t src, int c0, int c1) {
  asm volatile(ELECT "cp.async.bulk.tensor.2d.global.shared::cta.bulk_group [%0, {%2, %3}], [%1];\n}"
               ::"l"(m), "r"(src), "r"(c0), "r"(c1) : "memory");
}
__device__ __forceinline__ void bulk_load_h(uint32_t dst, const void* src, uint32_t bytes, uint32_t bar, uint64_t pol) {
  asm volatile(ELECT "cp.async.bulk.shared::cluster.global.mbarrier::complete_tx::bytes.L2::cache_hint [%0], [%1], %2, [%3], %4;\n}"
               ::"r"(dst), "l"(src), "r"(bytes), "r"(bar), "l"(pol) : "memory");
}
__device__ __forceinline__ void bulk_store(void* dst, uint32_t src, uint32_t bytes) {
  asm volatile(ELECT "cp.async.bulk.global.shared::cta.bulk_group [%0], [%1], %2;\n}" ::"l"(dst), "r"(src), "r"(bytes) : "memory");
}
__device__ __forceinline__ void bulk_commit() { asm volatile("cp.async.bulk.commit_group;" ::: "memory"); }
__device__ __forceinline__ void bulk_wait_all() { asm volatile("cp.async.bulk.wait_group 0;" ::: "memory"); }
__device__ __forceinline__ void fence_async_smem() { asm volatile("fence.proxy.async.shared::cta;" ::: "memory"); }
__device__ __forceinline__ void fence_async_global() { asm volatile("fence.proxy.async.global;" ::: "memory"); }
__device__ __forceinline__ void prefetch_tmap(const CUtensorMap* m) { asm volatile("prefetch.tensormap [%0];" ::"l"(m) : "memory"); }
__device__ __forceinline__ void named_bar(int id, int n) { asm volatile("bar.sync %0, %1;" ::"r"(id), "r"(n) : "memory"); }
__device__ __forceinline__ bool bar_red_or(int id, int n, bool v) {
  uint32_t r;
  asm volatile("{\n.reg .pred p, q;\nsetp.ne.u32 q, %3, 0;\nbarrier.cta.red.or.pred p, %1, %2, q;\nselp.u32 %0, 1, 0, p;\n}"
               : "=r"(r) : "r"(id), "r"(n), "r"((uint32_t)v) : "memory");
  return r != 0;
}
__device__ __forceinline__ void cluster_arrive() { asm volatile("barrier.cluster.arrive.relaxed.aligned;" ::: "memory"); }
__device__ __forceinline__ void cluster_wait() { asm volatile("barrier.cluster.wait.aligned;" ::: "memory"); }
__device__ __forceinline__ unsigned ld_relaxed(const unsigned* p) {
  unsigned v; asm volatile("ld.relaxed.gpu.global.u32 %0, [%1];" : "=r"(v) : "l"(p) : "memory"); return v;
}
__device__ __forceinline__ uint4 ld_relaxed4(const uint4* p) {
  uint4 v; asm volatile("ld.relaxed.gpu.global.v4.u32 {%0, %1, %2, %3}, [%4];" : "=r"(v.x), "=r"(v.y), "=r"(v.z), "=r"(v.w) : "l"(p) : "memory"); return v;
}
__device__ __forceinline__ void st_relaxed(unsigned* p, unsigned v) {
  asm volatile("st.relaxed.gpu.global.u32 [%0], %1;" ::"l"(p), "r"(v) : "memory");
}
__device__ __forceinline__ uint2 ld_relaxed2(const void* p) {
  uint2 v; asm volatile("ld.relaxed.gpu.global.v2.u32 {%0, %1}, [%2];" : "=r"(v.x), "=r"(v.y) : "l"(p) : "memory"); return v;
}
__device__ __forceinline__ void st_relaxed4(uint4* p, uint4 v) {
  asm volatile("st.relaxed.gpu.global.v4.u32 [%0], {%1, %2, %3, %4};" ::"l"(p), "r"(v.x), "r"(v.y), "r"(v.z), "r"(v.w) : "memory");
}
__device__ __forceinline__ bool valid4(uint4 v) { return v.x != SENT && v.y != SENT && v.z != SENT && v.w != SENT; }
__device__ __forceinline__ uint4 poll4(const uint4* p) {
  uint4 v;
  uint32_t spins = 0;
#pragma unroll 1
  do { v = ld_relaxed4(p); } while (!valid4(v) && ++spins < SPIN_LIMIT);
  return v;
}
__device__ __forceinline__ void set_flag(unsigned* p, unsigned tag) {
  asm volatile(ELECT "st.release.gpu.global.u32 [%0], %1;\n}" ::"l"(p), "r"(tag) : "memory");
}
__device__ __forceinline__ void poll_flag(const unsigned* p, unsigned tag) {
#pragma unroll 1
  for (uint32_t spins = 0; !__all_sync(0xffffffffu, ld_relaxed(p) == tag) && spins < SPIN_LIMIT; spins++) {}
  asm volatile("fence.acquire.gpu;" ::: "memory");
}
__device__ __forceinline__ uint32_t enc(float x) { return __float_as_uint(x + 0.0f) ^ 0x80000000u; }
__device__ __forceinline__ float dec(uint32_t u) { return __uint_as_float(u ^ 0x80000000u); }
__device__ __forceinline__ uint32_t hadd_bf2(uint32_t a, uint32_t b) {
  uint32_t r; asm("add.rn.bf16x2 %0, %1, %2;" : "=r"(r) : "r"(a), "r"(b)); return r;
}
__device__ __forceinline__ uint32_t hsub_bf2(uint32_t a, uint32_t b) {
  uint32_t r; asm("sub.rn.bf16x2 %0, %1, %2;" : "=r"(r) : "r"(a), "r"(b)); return r;
}
__device__ __forceinline__ void wg_fence() { asm volatile("wgmma.fence.sync.aligned;" ::: "memory"); }
__device__ __forceinline__ void wg_commit() { asm volatile("wgmma.commit_group.sync.aligned;" ::: "memory"); }
template <int N> __device__ __forceinline__ void wg_wait() { asm volatile("wgmma.wait_group.sync.aligned %0;" ::"n"(N) : "memory"); }
template <int R> __device__ __forceinline__ void fence_regs(float* d) {
#pragma unroll
  for (int i = 0; i < R; i++) asm volatile("" : "+f"(d[i])::"memory");
}
template <int R> __device__ __forceinline__ void fence_regs_u(uint32_t* d) {
#pragma unroll
  for (int i = 0; i < R; i++) asm volatile("" : "+r"(d[i])::"memory");
}
__host__ __device__ constexpr uint32_t dlo(uint32_t addr, uint32_t lbo) { return ((addr & 0x3FFFF) >> 4) | ((lbo >> 4) << 16); }
constexpr uint32_t H128 = 0x40000040u, H64 = 0x80000020u;
__device__ __forceinline__ void stsm_x4(uint32_t addr, uint32_t r0, uint32_t r1, uint32_t r2, uint32_t r3) {
  asm volatile("stmatrix.sync.aligned.m8n8.x4.shared.b16 [%0], {%1, %2, %3, %4};"
               ::"r"(addr), "r"(r0), "r"(r1), "r"(r2), "r"(r3) : "memory");
}
__device__ __forceinline__ void ldsm_x4(uint32_t addr, uint32_t& r0, uint32_t& r1, uint32_t& r2, uint32_t& r3) {
  asm volatile("ldmatrix.sync.aligned.m8n8.x4.shared.b16 {%0, %1, %2, %3}, [%4];"
               : "=r"(r0), "=r"(r1), "=r"(r2), "=r"(r3) : "r"(addr) : "memory");
}
__device__ __forceinline__ void ldsm_x4_t(uint32_t addr, uint32_t& r0, uint32_t& r1, uint32_t& r2, uint32_t& r3) {
  asm volatile("ldmatrix.sync.aligned.m8n8.x4.trans.shared.b16 {%0, %1, %2, %3}, [%4];"
               : "=r"(r0), "=r"(r1), "=r"(r2), "=r"(r3) : "r"(addr) : "memory");
}
__device__ __forceinline__ void mma_16816(float* d, uint32_t a0, uint32_t a1, uint32_t a2, uint32_t a3, uint32_t b0, uint32_t b1) {
  asm volatile("mma.sync.aligned.m16n8k16.row.col.f32.bf16.bf16.f32 {%0, %1, %2, %3}, {%4, %5, %6, %7}, {%8, %9}, {%0, %1, %2, %3};"
               : "+f"(d[0]), "+f"(d[1]), "+f"(d[2]), "+f"(d[3]) : "r"(a0), "r"(a1), "r"(a2), "r"(a3), "r"(b0), "r"(b1));
}
__device__ __forceinline__ void spin_cycles(int n) {
  const int t0 = (int)clock();
#pragma unroll 1
  while ((int)clock() - t0 < n) {}
}
__device__ __forceinline__ uint32_t pack_bf16(float lo, float hi) {
  uint32_t r; asm("cvt.rn.bf16x2.f32 %0, %1, %2;" : "=r"(r) : "f"(hi), "f"(lo)); return r;
}
__device__ __forceinline__ float bf_lo(uint32_t v) { return __uint_as_float(v << 16); }
__device__ __forceinline__ float bf_hi(uint32_t v) { return __uint_as_float(v & 0xffff0000u); }
__device__ __forceinline__ float rbf(float x) { return __bfloat162float(__float2bfloat16_rn(x)); }
__device__ __forceinline__ float ex2(float x) { float y; asm("ex2.approx.ftz.f32 %0, %1;" : "=f"(y) : "f"(x)); return y; }
__device__ __forceinline__ float rcp(float x) { float y; asm("rcp.approx.ftz.f32 %0, %1;" : "=f"(y) : "f"(x)); return y; }
__device__ __forceinline__ uint32_t shl_clamp(uint32_t v, uint32_t n) {
  uint32_t r; asm("shl.b32 %0, %1, %2;" : "=r"(r) : "r"(v), "r"(n)); return r;
}
__device__ __forceinline__ float warp_sum(float v) {
#pragma unroll
  for (int o = 16; o > 0; o >>= 1) v += __shfl_xor_sync(0xffffffffu, v, o);
  return v;
}
__device__ __forceinline__ float ln_inv(float var) {
  float r;
  asm("sqrt.approx.ftz.f32 %0, %1;" : "=f"(r) : "f"(rbf(rbf(var) + LN_EPS)));
  asm("rcp.approx.ftz.f32 %0, %1;" : "=f"(r) : "f"(rbf(r)));
  return r;
}
__device__ __forceinline__ uint32_t ln_pair(uint32_t x, uint32_t mean2, float inv) {
  const uint32_t d = hsub_bf2(x, mean2);
  return pack_bf16(bf_lo(d) * inv, bf_hi(d) * inv);
}
__device__ __forceinline__ uint32_t add_ln_pair(uint32_t x, uint32_t mean2, float inv) { return hadd_bf2(x, ln_pair(x, mean2, inv)); }
__device__ __forceinline__ uint32_t router_key(float r_bf, int row) {
  uint32_t u = __float_as_uint(r_bf);
  u = (u & 0x80000000u) ? ~u : (u | 0x80000000u);
  return (u & 0xFFFF0000u) | 0x8000u | (uint32_t)(SEQ - 1 - row);
}

template <uint32_t HA = 0x40000040u, uint32_t HB = 0x40000040u>
__device__ __forceinline__ void wg_ss192t(float* d, uint32_t da, uint32_t db, int scale_d) {
  asm volatile("{\n.reg .pred p;\n.reg .b64 dA, dB;\nmov.b64 dA, {%96, %99};\nmov.b64 dB, {%97, %100};\nsetp.ne.b32 p, %98, 0;\n"
    "wgmma.mma_async.sync.aligned.m64n192k16.f32.bf16.bf16 "
    "{%0, %1, %2, %3, %4, %5, %6, %7, %8, %9, %10, %11, %12, %13, %14, %15, "
    "%16, %17, %18, %19, %20, %21, %22, %23, %24, %25, %26, %27, %28, %29, %30, %31, "
    "%32, %33, %34, %35, %36, %37, %38, %39, %40, %41, %42, %43, %44, %45, %46, %47, "
    "%48, %49, %50, %51, %52, %53, %54, %55, %56, %57, %58, %59, %60, %61, %62, %63, "
    "%64, %65, %66, %67, %68, %69, %70, %71, %72, %73, %74, %75, %76, %77, %78, %79, "
    "%80, %81, %82, %83, %84, %85, %86, %87, %88, %89, %90, %91, %92, %93, %94, %95}, "
    "dA, dB, p, 1, 1, 0, 1;\n}\n"
    : "+f"(d[0]), "+f"(d[1]), "+f"(d[2]), "+f"(d[3]), "+f"(d[4]), "+f"(d[5]), "+f"(d[6]), "+f"(d[7]),
      "+f"(d[8]), "+f"(d[9]), "+f"(d[10]), "+f"(d[11]), "+f"(d[12]), "+f"(d[13]), "+f"(d[14]), "+f"(d[15]),
      "+f"(d[16]), "+f"(d[17]), "+f"(d[18]), "+f"(d[19]), "+f"(d[20]), "+f"(d[21]), "+f"(d[22]), "+f"(d[23]),
      "+f"(d[24]), "+f"(d[25]), "+f"(d[26]), "+f"(d[27]), "+f"(d[28]), "+f"(d[29]), "+f"(d[30]), "+f"(d[31]),
      "+f"(d[32]), "+f"(d[33]), "+f"(d[34]), "+f"(d[35]), "+f"(d[36]), "+f"(d[37]), "+f"(d[38]), "+f"(d[39]),
      "+f"(d[40]), "+f"(d[41]), "+f"(d[42]), "+f"(d[43]), "+f"(d[44]), "+f"(d[45]), "+f"(d[46]), "+f"(d[47]),
      "+f"(d[48]), "+f"(d[49]), "+f"(d[50]), "+f"(d[51]), "+f"(d[52]), "+f"(d[53]), "+f"(d[54]), "+f"(d[55]),
      "+f"(d[56]), "+f"(d[57]), "+f"(d[58]), "+f"(d[59]), "+f"(d[60]), "+f"(d[61]), "+f"(d[62]), "+f"(d[63]),
      "+f"(d[64]), "+f"(d[65]), "+f"(d[66]), "+f"(d[67]), "+f"(d[68]), "+f"(d[69]), "+f"(d[70]), "+f"(d[71]),
      "+f"(d[72]), "+f"(d[73]), "+f"(d[74]), "+f"(d[75]), "+f"(d[76]), "+f"(d[77]), "+f"(d[78]), "+f"(d[79]),
      "+f"(d[80]), "+f"(d[81]), "+f"(d[82]), "+f"(d[83]), "+f"(d[84]), "+f"(d[85]), "+f"(d[86]), "+f"(d[87]),
      "+f"(d[88]), "+f"(d[89]), "+f"(d[90]), "+f"(d[91]), "+f"(d[92]), "+f"(d[93]), "+f"(d[94]), "+f"(d[95])
    : "r"(da), "r"(db), "r"(scale_d), "n"(HA), "n"(HB));
}
template <uint32_t HA = 0x40000040u, uint32_t HB = 0x40000040u>
__device__ __forceinline__ void wg_ss192t_z(float* d, uint32_t da, uint32_t db) {
  asm volatile("{\n.reg .pred p;\n.reg .b64 dA, dB;\nmov.b64 dA, {%96, %98};\nmov.b64 dB, {%97, %99};\nsetp.ne.b32 p, 0, 0;\n"
    "wgmma.mma_async.sync.aligned.m64n192k16.f32.bf16.bf16 "
    "{%0, %1, %2, %3, %4, %5, %6, %7, %8, %9, %10, %11, %12, %13, %14, %15, "
    "%16, %17, %18, %19, %20, %21, %22, %23, %24, %25, %26, %27, %28, %29, %30, %31, "
    "%32, %33, %34, %35, %36, %37, %38, %39, %40, %41, %42, %43, %44, %45, %46, %47, "
    "%48, %49, %50, %51, %52, %53, %54, %55, %56, %57, %58, %59, %60, %61, %62, %63, "
    "%64, %65, %66, %67, %68, %69, %70, %71, %72, %73, %74, %75, %76, %77, %78, %79, "
    "%80, %81, %82, %83, %84, %85, %86, %87, %88, %89, %90, %91, %92, %93, %94, %95}, "
    "dA, dB, p, 1, 1, 0, 1;\n}\n"
    : "=f"(d[0]), "=f"(d[1]), "=f"(d[2]), "=f"(d[3]), "=f"(d[4]), "=f"(d[5]), "=f"(d[6]), "=f"(d[7]),
      "=f"(d[8]), "=f"(d[9]), "=f"(d[10]), "=f"(d[11]), "=f"(d[12]), "=f"(d[13]), "=f"(d[14]), "=f"(d[15]),
      "=f"(d[16]), "=f"(d[17]), "=f"(d[18]), "=f"(d[19]), "=f"(d[20]), "=f"(d[21]), "=f"(d[22]), "=f"(d[23]),
      "=f"(d[24]), "=f"(d[25]), "=f"(d[26]), "=f"(d[27]), "=f"(d[28]), "=f"(d[29]), "=f"(d[30]), "=f"(d[31]),
      "=f"(d[32]), "=f"(d[33]), "=f"(d[34]), "=f"(d[35]), "=f"(d[36]), "=f"(d[37]), "=f"(d[38]), "=f"(d[39]),
      "=f"(d[40]), "=f"(d[41]), "=f"(d[42]), "=f"(d[43]), "=f"(d[44]), "=f"(d[45]), "=f"(d[46]), "=f"(d[47]),
      "=f"(d[48]), "=f"(d[49]), "=f"(d[50]), "=f"(d[51]), "=f"(d[52]), "=f"(d[53]), "=f"(d[54]), "=f"(d[55]),
      "=f"(d[56]), "=f"(d[57]), "=f"(d[58]), "=f"(d[59]), "=f"(d[60]), "=f"(d[61]), "=f"(d[62]), "=f"(d[63]),
      "=f"(d[64]), "=f"(d[65]), "=f"(d[66]), "=f"(d[67]), "=f"(d[68]), "=f"(d[69]), "=f"(d[70]), "=f"(d[71]),
      "=f"(d[72]), "=f"(d[73]), "=f"(d[74]), "=f"(d[75]), "=f"(d[76]), "=f"(d[77]), "=f"(d[78]), "=f"(d[79]),
      "=f"(d[80]), "=f"(d[81]), "=f"(d[82]), "=f"(d[83]), "=f"(d[84]), "=f"(d[85]), "=f"(d[86]), "=f"(d[87]),
      "=f"(d[88]), "=f"(d[89]), "=f"(d[90]), "=f"(d[91]), "=f"(d[92]), "=f"(d[93]), "=f"(d[94]), "=f"(d[95])
    : "r"(da), "r"(db), "n"(HA), "n"(HB));
}
template <uint32_t HA = 0x40000040u, uint32_t HB = 0x40000040u>
__device__ __forceinline__ void wg_ss128t(float* d, uint32_t da, uint32_t db, int scale_d) {
  asm volatile("{\n.reg .pred p;\n.reg .b64 dA, dB;\nmov.b64 dA, {%64, %67};\nmov.b64 dB, {%65, %68};\nsetp.ne.b32 p, %66, 0;\n"
    "wgmma.mma_async.sync.aligned.m64n128k16.f32.bf16.bf16 "
    "{%0, %1, %2, %3, %4, %5, %6, %7, %8, %9, %10, %11, %12, %13, %14, %15, "
    "%16, %17, %18, %19, %20, %21, %22, %23, %24, %25, %26, %27, %28, %29, %30, %31, "
    "%32, %33, %34, %35, %36, %37, %38, %39, %40, %41, %42, %43, %44, %45, %46, %47, "
    "%48, %49, %50, %51, %52, %53, %54, %55, %56, %57, %58, %59, %60, %61, %62, %63}, "
    "dA, dB, p, 1, 1, 0, 1;\n}\n"
    : "+f"(d[0]), "+f"(d[1]), "+f"(d[2]), "+f"(d[3]), "+f"(d[4]), "+f"(d[5]), "+f"(d[6]), "+f"(d[7]),
      "+f"(d[8]), "+f"(d[9]), "+f"(d[10]), "+f"(d[11]), "+f"(d[12]), "+f"(d[13]), "+f"(d[14]), "+f"(d[15]),
      "+f"(d[16]), "+f"(d[17]), "+f"(d[18]), "+f"(d[19]), "+f"(d[20]), "+f"(d[21]), "+f"(d[22]), "+f"(d[23]),
      "+f"(d[24]), "+f"(d[25]), "+f"(d[26]), "+f"(d[27]), "+f"(d[28]), "+f"(d[29]), "+f"(d[30]), "+f"(d[31]),
      "+f"(d[32]), "+f"(d[33]), "+f"(d[34]), "+f"(d[35]), "+f"(d[36]), "+f"(d[37]), "+f"(d[38]), "+f"(d[39]),
      "+f"(d[40]), "+f"(d[41]), "+f"(d[42]), "+f"(d[43]), "+f"(d[44]), "+f"(d[45]), "+f"(d[46]), "+f"(d[47]),
      "+f"(d[48]), "+f"(d[49]), "+f"(d[50]), "+f"(d[51]), "+f"(d[52]), "+f"(d[53]), "+f"(d[54]), "+f"(d[55]),
      "+f"(d[56]), "+f"(d[57]), "+f"(d[58]), "+f"(d[59]), "+f"(d[60]), "+f"(d[61]), "+f"(d[62]), "+f"(d[63])
    : "r"(da), "r"(db), "r"(scale_d), "n"(HA), "n"(HB));
}
template <uint32_t HB = 0x40000040u>
__device__ __forceinline__ void wg_rs64(float* d, uint32_t a0, uint32_t a1, uint32_t a2, uint32_t a3, uint32_t db, int scale_d) {
  asm volatile("{\n.reg .pred p;\n.reg .b64 dB;\nmov.b64 dB, {%36, %38};\nsetp.ne.b32 p, %37, 0;\n"
    "wgmma.mma_async.sync.aligned.m64n64k16.f32.bf16.bf16 "
    "{%0, %1, %2, %3, %4, %5, %6, %7, %8, %9, %10, %11, %12, %13, %14, %15, "
    "%16, %17, %18, %19, %20, %21, %22, %23, %24, %25, %26, %27, %28, %29, %30, %31}, "
    "{%32, %33, %34, %35}, dB, p, 1, 1, 0;\n}\n"
    : "+f"(d[0]), "+f"(d[1]), "+f"(d[2]), "+f"(d[3]), "+f"(d[4]), "+f"(d[5]), "+f"(d[6]), "+f"(d[7]),
      "+f"(d[8]), "+f"(d[9]), "+f"(d[10]), "+f"(d[11]), "+f"(d[12]), "+f"(d[13]), "+f"(d[14]), "+f"(d[15]),
      "+f"(d[16]), "+f"(d[17]), "+f"(d[18]), "+f"(d[19]), "+f"(d[20]), "+f"(d[21]), "+f"(d[22]), "+f"(d[23]),
      "+f"(d[24]), "+f"(d[25]), "+f"(d[26]), "+f"(d[27]), "+f"(d[28]), "+f"(d[29]), "+f"(d[30]), "+f"(d[31])
    : "r"(a0), "r"(a1), "r"(a2), "r"(a3), "r"(db), "r"(scale_d), "n"(HB));
}
template <uint32_t HB = 0x40000040u>
__device__ __forceinline__ void wg_rs64_z(float* d, uint32_t a0, uint32_t a1, uint32_t a2, uint32_t a3, uint32_t db) {
  asm volatile("{\n.reg .pred p;\n.reg .b64 dB;\nmov.b64 dB, {%36, %37};\nsetp.ne.b32 p, 0, 0;\n"
    "wgmma.mma_async.sync.aligned.m64n64k16.f32.bf16.bf16 "
    "{%0, %1, %2, %3, %4, %5, %6, %7, %8, %9, %10, %11, %12, %13, %14, %15, "
    "%16, %17, %18, %19, %20, %21, %22, %23, %24, %25, %26, %27, %28, %29, %30, %31}, "
    "{%32, %33, %34, %35}, dB, p, 1, 1, 0;\n}\n"
    : "=f"(d[0]), "=f"(d[1]), "=f"(d[2]), "=f"(d[3]), "=f"(d[4]), "=f"(d[5]), "=f"(d[6]), "=f"(d[7]),
      "=f"(d[8]), "=f"(d[9]), "=f"(d[10]), "=f"(d[11]), "=f"(d[12]), "=f"(d[13]), "=f"(d[14]), "=f"(d[15]),
      "=f"(d[16]), "=f"(d[17]), "=f"(d[18]), "=f"(d[19]), "=f"(d[20]), "=f"(d[21]), "=f"(d[22]), "=f"(d[23]),
      "=f"(d[24]), "=f"(d[25]), "=f"(d[26]), "=f"(d[27]), "=f"(d[28]), "=f"(d[29]), "=f"(d[30]), "=f"(d[31])
    : "r"(a0), "r"(a1), "r"(a2), "r"(a3), "r"(db), "n"(HB));
}
template <uint32_t HB = 0x40000040u>
__device__ __forceinline__ void wg_rs32(float* d, uint32_t a0, uint32_t a1, uint32_t a2, uint32_t a3, uint32_t db, int scale_d) {
  asm volatile("{\n.reg .pred p;\n.reg .b64 dB;\nmov.b64 dB, {%20, %22};\nsetp.ne.b32 p, %21, 0;\n"
    "wgmma.mma_async.sync.aligned.m64n32k16.f32.bf16.bf16 "
    "{%0, %1, %2, %3, %4, %5, %6, %7, %8, %9, %10, %11, %12, %13, %14, %15}, "
    "{%16, %17, %18, %19}, dB, p, 1, 1, 0;\n}\n"
    : "+f"(d[0]), "+f"(d[1]), "+f"(d[2]), "+f"(d[3]), "+f"(d[4]), "+f"(d[5]), "+f"(d[6]), "+f"(d[7]),
      "+f"(d[8]), "+f"(d[9]), "+f"(d[10]), "+f"(d[11]), "+f"(d[12]), "+f"(d[13]), "+f"(d[14]), "+f"(d[15])
    : "r"(a0), "r"(a1), "r"(a2), "r"(a3), "r"(db), "r"(scale_d), "n"(HB));
}
template <uint32_t HB = 0x40000040u>
__device__ __forceinline__ void wg_rs32_z(float* d, uint32_t a0, uint32_t a1, uint32_t a2, uint32_t a3, uint32_t db) {
  asm volatile("{\n.reg .pred p;\n.reg .b64 dB;\nmov.b64 dB, {%20, %21};\nsetp.ne.b32 p, 0, 0;\n"
    "wgmma.mma_async.sync.aligned.m64n32k16.f32.bf16.bf16 "
    "{%0, %1, %2, %3, %4, %5, %6, %7, %8, %9, %10, %11, %12, %13, %14, %15}, "
    "{%16, %17, %18, %19}, dB, p, 1, 1, 0;\n}\n"
    : "=f"(d[0]), "=f"(d[1]), "=f"(d[2]), "=f"(d[3]), "=f"(d[4]), "=f"(d[5]), "=f"(d[6]), "=f"(d[7]),
      "=f"(d[8]), "=f"(d[9]), "=f"(d[10]), "=f"(d[11]), "=f"(d[12]), "=f"(d[13]), "=f"(d[14]), "=f"(d[15])
    : "r"(a0), "r"(a1), "r"(a2), "r"(a3), "r"(db), "n"(HB));
}
template <uint32_t HB = 0x40000040u>
__device__ __forceinline__ void wg_rs40t(float* d, uint32_t a0, uint32_t a1, uint32_t a2, uint32_t a3, uint32_t db, int scale_d) {
  asm volatile("{\n.reg .pred p;\n.reg .b64 dB;\nmov.b64 dB, {%24, %26};\nsetp.ne.b32 p, %25, 0;\n"
    "wgmma.mma_async.sync.aligned.m64n40k16.f32.bf16.bf16 "
    "{%0, %1, %2, %3, %4, %5, %6, %7, %8, %9, %10, %11, %12, %13, %14, %15, "
    "%16, %17, %18, %19}, "
    "{%20, %21, %22, %23}, dB, p, 1, 1, 1;\n}\n"
    : "+f"(d[0]), "+f"(d[1]), "+f"(d[2]), "+f"(d[3]), "+f"(d[4]), "+f"(d[5]), "+f"(d[6]), "+f"(d[7]),
      "+f"(d[8]), "+f"(d[9]), "+f"(d[10]), "+f"(d[11]), "+f"(d[12]), "+f"(d[13]), "+f"(d[14]), "+f"(d[15]),
      "+f"(d[16]), "+f"(d[17]), "+f"(d[18]), "+f"(d[19])
    : "r"(a0), "r"(a1), "r"(a2), "r"(a3), "r"(db), "r"(scale_d), "n"(HB));
}
template <uint32_t HB = 0x40000040u>
__device__ __forceinline__ void wg_rs40t_z(float* d, uint32_t a0, uint32_t a1, uint32_t a2, uint32_t a3, uint32_t db) {
  asm volatile("{\n.reg .pred p;\n.reg .b64 dB;\nmov.b64 dB, {%24, %25};\nsetp.ne.b32 p, 0, 0;\n"
    "wgmma.mma_async.sync.aligned.m64n40k16.f32.bf16.bf16 "
    "{%0, %1, %2, %3, %4, %5, %6, %7, %8, %9, %10, %11, %12, %13, %14, %15, "
    "%16, %17, %18, %19}, "
    "{%20, %21, %22, %23}, dB, p, 1, 1, 1;\n}\n"
    : "=f"(d[0]), "=f"(d[1]), "=f"(d[2]), "=f"(d[3]), "=f"(d[4]), "=f"(d[5]), "=f"(d[6]), "=f"(d[7]),
      "=f"(d[8]), "=f"(d[9]), "=f"(d[10]), "=f"(d[11]), "=f"(d[12]), "=f"(d[13]), "=f"(d[14]), "=f"(d[15]),
      "=f"(d[16]), "=f"(d[17]), "=f"(d[18]), "=f"(d[19])
    : "r"(a0), "r"(a1), "r"(a2), "r"(a3), "r"(db), "n"(HB));
}

constexpr uint32_t SOFF = 1024;
constexpr int STG = 57344, SL_W = 32768, SL_HD = 12288, SL_F = 3 * STG, X_ST = 131072;
__host__ __device__ constexpr int kv_off(int h, int b) { return 16384 + h * 81920 + (b ^ (6 * h)) * 8192; }
__host__ __device__ constexpr int qo_off(int h, int qb) { return (qb >> 1) * 81920 + h * 8192 + (qb & 1) * 4096; }
__host__ __device__ constexpr int wo_off(int st) { return 16384 + st * 32768 + (st >> 1) * 16384; }
constexpr int OFF_ONES = 4 * STG;
constexpr int OFF_PATCH = OFF_ONES + 1024;
constexpr int OFF_CS = OFF_PATCH + 768;
constexpr int OFF_BAR = OFF_CS + 768;
constexpr int OFF_MISC = OFF_BAR + 416;
constexpr int SMEM_BYTES = OFF_MISC + 96;
enum { B_FULL = 0, B_EMPTY = 6, B_HALO = 12, B_CS = 15, B_KVREADY, B_QDONE = B_KVREADY + 2, B_QREADY, B_OST, B_ADONE = B_OST + 2,
       B_QFREE, B_WS, B_WFULL, B_WEMPTY = B_WFULL + 4, B_GU = B_WEMPTY + 4, B_RES = B_GU + 2, B_DN,
       B_HX = B_DN + 2, B_RST, B_E23, B_UNIT, B_COUNT = B_UNIT + 8 };
static_assert(B_COUNT <= 52, "barrier area");
__host__ __device__ constexpr int bar_count(int i) {
  return i >= B_EMPTY && i < B_HALO ? 17 : i == B_CS ? 5 : i == B_QFREE ? 16
       : i == B_KVREADY || i == B_KVREADY + 1 || i == B_QREADY ? 8 : i == B_E23 ? 9 : i == B_ADONE ? 32 : i == B_OST ? 2 : i >= B_UNIT ? 4
       : i == B_QDONE || (i >= B_WEMPTY && i < B_GU) ? 16 : i == B_RST ? 4 : i == B_RES ? 2 : 1;
}
enum { M_KEY = 0, M_MEAN, M_INV, M_WSUM, M_TAG, M_SEL0, M_PMEAN, M_PINV, M_XQ = 8, M_KEYS = 12, M_PROG = 20 };
constexpr int FFN_PIECE = 14336;
constexpr int T_XS = 163840, T_HP = T_XS + 1024;
constexpr float LSUM_MIN = 5.421010862427522e-20f, LSUM_MAX = 1.8446744073709552e19f;
constexpr float SM_C = 0.17677669529663687f * 1.4426950408889634f;
constexpr uint32_t VSTEP = 64u - (64u << 16);
constexpr int DELAY_P = 600, DELAY_S = 2400, DELAY_Y = 400, P1_DELAY = 800, X_STAGGER = 500;
constexpr int GU_PACE = 2000, GU_PACE1 = 1700, GUB_PACE = 900, WS_PACE = 500;
constexpr int RES_K = 6;

struct Params {
  CUtensorMap mapA[2], mapW, mapWo, mapRes[2], mapXst[2], mapG, mapU, mapD, mapWs;
  const bf16 *w_r, *w_d;
  bf16* out;
};

template <int N> __device__ __forceinline__ void exp_pack(const float* s, uint32_t* p) {
#pragma unroll
  for (int b = 0; b < N; b++) {
    p[2 * b] = pack_bf16(ex2(s[4 * b]), ex2(s[4 * b + 1]));
    p[2 * b + 1] = pack_bf16(ex2(s[4 * b + 2]), ex2(s[4 * b + 3]));
  }
}
template <int KIND> __device__ __forceinline__ void edge16(const float* sd, const float* st, uint32_t* pd, uint32_t* pt, int dl, uint32_t mt) {
  if (KIND == 0) { exp_pack<2>(sd, pd); pt[0] = pt[1] = pt[2] = pt[3] = 0; }
  else if (KIND == 1) { exp_pack<2>(st, pt); pd[0] = pd[1] = pd[2] = pd[3] = 0; }
  else {
    const uint32_t a = pack_bf16(ex2(dl >= 0 ? sd[0] : st[0]), ex2(dl >= 1 ? sd[1] : st[1]));
    const uint32_t c = pack_bf16(ex2(dl >= 0 ? sd[6] : st[6]), ex2(dl >= 1 ? sd[7] : st[7]));
    pd[0] = a & ~mt; pt[0] = a & mt; pd[3] = c & ~mt; pt[3] = c & mt;
    pd[1] = pack_bf16(ex2(sd[2]), ex2(sd[3])); pt[1] = 0;
    pt[2] = pack_bf16(ex2(st[4]), ex2(st[5])); pd[2] = 0;
  }
}
__device__ __forceinline__ void edge32(const float* sd, const float* st, uint32_t* pd, uint32_t* pt, int rel, int dl, uint32_t mt) {
  if (rel > 1) { edge16<0>(sd, st, pd, pt, dl, mt); edge16<0>(sd + 8, st + 8, pd + 4, pt + 4, dl, mt); }
  else if (rel == 1) { edge16<0>(sd, st, pd, pt, dl, mt); edge16<2>(sd + 8, st + 8, pd + 4, pt + 4, dl, mt); }
  else if (rel == 0) { edge16<2>(sd, st, pd, pt, dl, mt); edge16<1>(sd + 8, st + 8, pd + 4, pt + 4, dl, mt); }
  else { edge16<1>(sd, st, pd, pt, dl, mt); edge16<1>(sd + 8, st + 8, pd + 4, pt + 4, dl, mt); }
}
__device__ __forceinline__ void qk64(float* s, const uint32_t* qf, uint32_t kd) {
  wg_rs64_z<H64>(s, qf[0], qf[1], qf[2], qf[3], kd);
  wg_rs64<H64>(s, qf[4], qf[5], qf[6], qf[7], kd + 2, 1);
}
__device__ __forceinline__ void qk32x2(float* a, float* b, const uint32_t* qf, uint32_t ka, uint32_t kb) {
  wg_rs32_z<H64>(a, qf[0], qf[1], qf[2], qf[3], ka); wg_rs32_z<H64>(b, qf[0], qf[1], qf[2], qf[3], kb);
  wg_rs32<H64>(a, qf[4], qf[5], qf[6], qf[7], ka + 2, 1); wg_rs32<H64>(b, qf[4], qf[5], qf[6], qf[7], kb + 2, 1);
}
__device__ __forceinline__ void pv32(float* o, const uint32_t* p, uint32_t vd) {
  wg_rs40t<H64>(o, p[0], p[1], p[2], p[3], vd, 1);
  wg_rs40t<H64>(o, p[4], p[5], p[6], p[7], vd + VSTEP, 1);
}

__device__ __forceinline__ void fma8(float* d, uint4 w, float x) {
  d[0] += x * bf_lo(w.x); d[1] += x * bf_hi(w.x); d[2] += x * bf_lo(w.y); d[3] += x * bf_hi(w.y);
  d[4] += x * bf_lo(w.z); d[5] += x * bf_hi(w.z); d[6] += x * bf_lo(w.w); d[7] += x * bf_hi(w.w);
}

__device__ __forceinline__ int fresh_tid() { int r; asm volatile("mov.u32 %0, %%tid.x;" : "=r"(r)); return r; }
__device__ __forceinline__ int fresh_bid() { int r; asm volatile("mov.u32 %0, %%ctaid.x;" : "=r"(r)); return r; }
#define PHASE_IDS                                                                                                              \
  const uint32_t sbase = smem_u32(smem);                                                                                       \
  const int tid = fresh_tid(), bid = fresh_bid();                                                                              \
  const int warp = __shfl_sync(0xffffffffu, tid >> 5, 0), lane = tid & 31;                                                     \
  const int rank = bid & 1, cl = bid >> 1, rb = bid & 7, hp = bid >> 3;                  \
  const int mb = 2 * rb + (hp >> 3), nb = hp & 7;                                            \
  const int wg = warp >> 2, wi = warp & 3, g = lane >> 2, q = lane & 3;                                                        \
  const int mi = lane >> 3, srow = wi * 16 + (mi & 1) * 8 + (lane & 7);      \
  auto bar = [&](int i) { return sbase + OFF_BAR + 8 * i; };                                                                   \
  volatile uint32_t* s_misc = (volatile uint32_t*)(smem + OFF_MISC);                                                           \
  auto load_w = [&](int s, int kt) {                           \
    mbar_expect_tx(bar(B_FULL + s), (s & 1) ? SL_HD : SL_HD + 32768);                        \
    tma_load3_mc(sbase + (s >> 1) * STG + SL_W + (s & 1) * SL_HD + rank * 6144, &P.mapW, hp * 64, kt * 32 + rank * 16, 0, bar(B_FULL + s));              \
  };                                                                                                                           \
  auto load_a = [&](int s, int kt, int layer) { tma_load2(sbase + (s >> 1) * STG, &P.mapA[layer], kt * 32, rb * 256, bar(B_FULL + s)); }; \
  auto load_wo = [&](int k) {                                                 \
    mbar_expect_tx(bar(B_WFULL + (k & 3)), 32768);                                                                             \
    tma_load3_mc(sbase + wo_off(k & 3) + 16384 + rank * 8192, &P.mapWo, nb * 128 + rank * 64, (k >> 3) * 32, (k & 7) * 2, bar(B_WFULL + (k & 3))); \
  };                                                                                                                           \
  auto load_o = [&](int k) {                                                            \
    bulk_load_h(sbase + wo_off(k & 3), g_o + (size_t)(mb * 16 + k) * 16384, 16384, bar(B_WFULL + (k & 3)), policy_evict_first());                    \
  };                                                                                                                           \
  auto load_res = [&](int half, int layer) {      \
    mbar_expect_tx(bar(B_RES), 16384);                                                                                         \
    tma_load2_h(sbase + qo_off(half, 0), &P.mapRes[layer], nb * 128 + half * 64, mb * 128, bar(B_RES), policy_evict_first());  \
    tma_load2_h(sbase + qo_off(half, 2), &P.mapRes[layer], nb * 128 + half * 64, mb * 128 + 64, bar(B_RES), policy_evict_first()); \
  };                                                                                                                           \
  auto store_tile = [&](int layer, int skip, bool wait) {                                           \
    _Pragma("unroll 1")                                                                                                        \
    for (int j = 0; j < 4; j++)                                                                                                \
      if ((j & 1) != skip) tma_store(&P.mapXst[layer], sbase + X_ST + (j & 1) * 16384 + (j >> 1) * 8192, nb * 128 + (j >> 1) * 64, mb * 128 + (j & 1) * 64); \
    bulk_commit();                                                                                                             \
    if (wait) bulk_wait_all();                                                                                                 \
  };                                                                                                                           \
  auto load_ws = [&](int pace) {                                    \
    mbar_expect_tx(bar(B_WS), 4 * SL_HD);                                                                                      \
    _Pragma("unroll 1")                                                                                                        \
    for (int j = 0; j < 4; j++) {                                                                                              \
      tma_load3(sbase + SL_F + j * SL_HD, &P.mapWs, hp * 64, rb * 128 + j * 32, 0, bar(B_WS));                                 \
      if (pace) spin_cycles(pace);                                                                                             \
    }                                                                                                                          \
  };                                                                                                                           \
  auto load_gu = [&](int half, int pace) {                             \
    mbar_expect_tx(bar(B_GU + half), 4 * FFN_PIECE);                                                                           \
    _Pragma("unroll 1")                                                                                                        \
    for (int j = 0; j < 4; j++) {                                                                                              \
      tma_load2_h(sbase + SL_F + j * FFN_PIECE, &P.mapG + (j >> 1), cl * 56, rank * 512 + half * 256 + (j & 1) * 128, bar(B_GU + half), policy_evict_first()); \
      if (j < 3) spin_cycles(pace);                                                                                            \
    }                                                                                                                          \
  };                                                                                                                           \
  auto fetch_gu = [&](uint32_t* a, int ks, int ct) {                 \
    ldsm_x4_t(sbase + SL_F + (mi & 1) * 2 * FFN_PIECE + (ks * 16 + (mi >> 1) * 8 + (lane & 7)) * 112 + ct * 16, a[0], a[1], a[2], a[3]); \
  };                                                                                                                           \
  auto send_gu = [&](float gate, float up, int ct, int part) {        \
    const int u = 8 * ct + g, own = u >= 28;                                                                                   \
    if (q == 0) st_async2(mapa(sbase + T_HP + ((rank * 5 + part) * 28 + u - 28 * own) * 8, own), gate, up, mapa(bar(B_HX), own)); \
  };                                                                                                                           \
  auto hidden = [&]() {                                     \
    const float2* hpart = (const float2*)(smem + T_HP) + min(lane, 27);                                                        \
    float gs[2] = {0.f, 0.f}, us[2] = {0.f, 0.f};                                                                              \
    _Pragma("unroll")                                                                                                          \
    for (int j = 0; j < 10; j++) { const float2 v = hpart[j * 28]; gs[j & 1] += v.x; us[j & 1] += v.y; }                       \
    const float gb = rbf(gs[0] + gs[1]), ub = rbf(us[0] + us[1]);                                                              \
    return lane < 28 ? rbf(__fdividef(gb, 1.f + __expf(-gb))) * ub : 0.f;                                                      \
  };                                                                                                                           \
  (void)load_wo; (void)load_o; (void)load_res; (void)store_tile; (void)fetch_gu; (void)load_ws; (void)load_gu; (void)send_gu; (void)hidden; (void)cl; (void)mb; (void)nb; (void)wg; (void)g; (void)q; (void)srow; (void)s_misc; (void)load_w; (void)load_a;

__global__ void __launch_bounds__(512, 1) mega_kernel(const __grid_constant__ Params P) {
  extern __shared__ __align__(1024) uint8_t smem[];
  {
    PHASE_IDS
    if (warp == 0) {
      if (lane == 0) {
        prefetch_tmap(&P.mapA[0]); prefetch_tmap(&P.mapW);
#pragma unroll
        for (int i = 0; i < 6; i++) mbar_init(bar(B_FULL + i), 1);
        asm volatile("fence.mbarrier_init.release.cluster;" ::: "memory");
      }
      __syncwarp();
      mbar_expect_tx(bar(B_FULL), SL_HD + 32768);
      tma_load3(sbase + SL_W, &P.mapW, hp * 64, 0, 0, bar(B_FULL));
      tma_load3(sbase + SL_W + 6144, &P.mapW, hp * 64, 16, 0, bar(B_FULL));
      load_a(0, 0, 0);
    } else if (tid == 32) {
#pragma unroll
      for (int i = 6; i < B_COUNT; i++) mbar_init(bar(i), bar_count(i));
      asm volatile("fence.mbarrier_init.release.cluster;" ::: "memory");
    } else if (warp == 8) {
      ((uint4*)(smem + OFF_ONES))[lane] = make_uint4(0x3F803F80u, 0x3F803F80u, 0x3F803F80u, 0x3F803F80u);
      ((uint4*)(smem + OFF_ONES))[lane + 32] = make_uint4(0x3F803F80u, 0x3F803F80u, 0x3F803F80u, 0x3F803F80u);
    }
    __syncwarp();
    cluster_arrive(); cluster_wait();
    if (warp == 0) {
      PROFL(0, 1);
      load_w(1, 1);
    } else if (tid == 96) {
      if ((sbase & 0x3FFFF) != SOFF) __trap();
    }
    __syncwarp();
  }

  regs_dec<120>();
#pragma unroll 1
  for (unsigned pass_v = 0;;) {
    const unsigned pass = __shfl_sync(0xffffffffu, pass_v, 0);
    if (__shfl_sync(0xffffffffu, fresh_tid() >> 8, 0)) {
      if (pass > 0) {
        const unsigned layer = pass - 1;
        uint32_t xr[32];
        {
          PHASE_IDS
          float acc[64];
#pragma unroll
          for (int i = 0; i < 64; i++) acc[i] = 0.f;
          const uint32_t da0 = dlo(SOFF, 16) + (wg - 2) * 256;
          constexpr uint32_t db0 = dlo(SOFF + 16384, 8192);
#pragma unroll 1
          for (int k4 = 0; k4 < 4; k4++) {
#pragma unroll
            for (int st = 0; st < 4; st++) {
              mbar_wait(bar(B_WFULL + st), k4 & 1);
              wg_fence();
#pragma unroll
              for (int kk = 0; kk < 4; kk++)
                wg_ss128t<H64, H128>(acc, da0 + (wo_off(st) >> 4) + (kk >> 1) * 512 + (kk & 1) * 2, db0 + (wo_off(st) >> 4) + kk * 128, 1);
              wg_commit();
              if (st == 0 && k4 == 0 && warp == 9) PROF(10);
              if (warp == 9) STEPT(16 + k4 * 4 + st);
              wg_wait<1>();
              if (lane < 2 && (st == 0 ? k4 > 0 : (st < 3 || k4 < 3))) mbar_arrive_cluster(bar(B_WEMPTY + ((st + 3) & 3)), lane);
            }
          }
          mbar_wait(bar(B_RES), layer);
          mbar_wait(bar(B_RST), layer);
          const uint32_t zoff = qo_off(0, (wg - 2) * 2);
#pragma unroll
          for (int j = 0; j < 8; j++)
            ldsm_x4(sbase + zoff + srow * 128 + (j >> 2) * 8192 + ((((2 * j + (mi >> 1)) & 7) ^ (srow & 7)) << 4), xr[4 * j], xr[4 * j + 1], xr[4 * j + 2], xr[4 * j + 3]);
          wg_wait<0>();
          fence_regs<64>(acc);
          if (warp == 9) PROF(11);
#pragma unroll
          for (int j = 0; j < 32; j++) xr[j] = hadd_bf2(xr[j], pack_bf16(acc[2 * j], acc[2 * j + 1]));
        }
        PHASE_IDS
        const uint32_t tag = s_misc[M_TAG];
        const int grow = mb * 128 + (warp - 8) * 16 + g;
        {
          float d[6][4];
#pragma unroll
          for (int i = 0; i < 6; i++) d[i][0] = d[i][1] = d[i][2] = d[i][3] = 0.f;
          const uint4* tab = (const uint4*)(smem + OFF_PATCH + (g == 1 ? q * 64 : (g == 0 ? 256 : 320)));
#pragma unroll
          for (int j2 = 0; j2 < 4; j2++) {
            const uint4 w = tab[j2];
#pragma unroll
            for (int jj = 0; jj < 2; jj++) {
              const uint32_t* a = &xr[8 * j2 + 4 * jj];
              mma_16816(d[jj], a[0], a[1], a[2], a[3], jj ? w.z : w.x, jj ? w.w : w.y);
              mma_16816(d[2 + jj], a[0], a[1], a[2], a[3], a[0], a[2]);
              mma_16816(d[4 + jj], a[0], a[1], a[2], a[3], a[1], a[3]);
            }
          }
          const float sq0 = __shfl_sync(0xffffffffu, (g & 1) ? d[2][1] + d[3][1] : d[2][0] + d[3][0], g * 4 + (g >> 1));
          const float sq1 = __shfl_sync(0xffffffffu, (g & 1) ? d[4][3] + d[5][3] : d[4][2] + d[5][2], g * 4 + (g >> 1));
          uint4* dst = &g_part[layer][nb * SEQ + grow];
          if (q == 0) {
            st_relaxed4(dst, make_uint4(__float_as_uint(d[0][0] + d[1][0]), __float_as_uint(sq0), __float_as_uint(d[0][1] + d[1][1]), tag));
            st_relaxed4(dst + 8, make_uint4(__float_as_uint(d[0][2] + d[1][2]), __float_as_uint(sq1), __float_as_uint(d[0][3] + d[1][3]), tag));
          }
        }
        if (warp == 9) PROF(12);
        if (layer == 0 && lane < 2) mbar_arrive_cluster(bar(B_QFREE), lane);
        asm volatile("bar.arrive 6, 320;" ::: "memory");
        const int t_p = (int)clock();
        const uint32_t zrow = sbase + X_ST + (wg - 2) * 16384 + srow * 128;
        named_bar(5, 256);
#pragma unroll
        for (int j = 0; j < 8; j++)
          stsm_x4(zrow + (j >> 2) * 8192 + ((((2 * j + (mi >> 1)) & 7) ^ (srow & 7)) << 4), xr[4 * j], xr[4 * j + 1], xr[4 * j + 2], xr[4 * j + 3]);
        if (layer == 0) {
          fence_async_smem();
          asm volatile("bar.arrive 8, 288;" ::: "memory");
        }
#pragma unroll 1
        while ((int)clock() - t_p < DELAY_P) {}
        {
          const uint4* src = &g_part[layer][2 * q * SEQ + grow];
          uint4 pp[4];
          uint32_t spins = 0;
#pragma unroll 1
          do {
            pp[0] = ld_relaxed4(src); pp[1] = ld_relaxed4(src + SEQ); pp[2] = ld_relaxed4(src + 8); pp[3] = ld_relaxed4(src + SEQ + 8);
          } while (!__all_sync(0xffffffffu, pp[0].w == tag && pp[1].w == tag && pp[2].w == tag && pp[3].w == tag) && ++spins < SPIN_LIMIT);
          if (warp == 9) PROF(13);
          const int rr = q >> 1;
          float s3[3];
#pragma unroll
          for (int c = 0; c < 3; c++) {
            const float lo = __uint_as_float(c == 0 ? pp[0].x : c == 1 ? pp[0].y : pp[0].z) + __uint_as_float(c == 0 ? pp[1].x : c == 1 ? pp[1].y : pp[1].z);
            const float hi = __uint_as_float(c == 0 ? pp[2].x : c == 1 ? pp[2].y : pp[2].z) + __uint_as_float(c == 0 ? pp[3].x : c == 1 ? pp[3].y : pp[3].z);
            s3[c] = (rr ? hi : lo) + __shfl_xor_sync(0xffffffffu, rr ? lo : hi, 2);
            s3[c] += __shfl_xor_sync(0xffffffffu, s3[c], 1);
          }
          const float mu = s3[0] * (1.f / DM), var = fmaxf(fmaf(-mu, mu, s3[1] * (1.f / DM)), 0.f);
          const float mn = rbf(mu), iv = ln_inv(var);
          const uint32_t ky = router_key(rbf((s3[2] - mn * __uint_as_float(s_misc[M_WSUM])) * iv), grow + 8 * rr);
          const uint32_t wbest = __reduce_max_sync(0xffffffffu, ky);
          s_misc[M_KEYS + warp - 8] = wbest;
          named_bar(5, 256);
          if (__reduce_max_sync(0xffffffffu, s_misc[M_KEYS + (lane & 7)]) == wbest) {
            if (nb == 0 && ky == wbest && (q & 1) == 0) st_relaxed4(&g_slot[layer][mb * 8], make_uint4(ky, __float_as_uint(mn), __float_as_uint(iv), tag));
            const int r = ~wbest & 15;
            if ((r & 7) == g) {
#pragma unroll
              for (int j = 0; j < 4; j++) {
                const uint32_t* a = &xr[8 * j];
                st_relaxed4(&g_cand[layer][mb * 128 + nb * 16 + q * 4 + j],
                            r < 8 ? make_uint4(a[0], a[2], a[4], a[6]) : make_uint4(a[1], a[3], a[5], a[7]));
              }
            }
            __syncwarp();
          }
          if (warp == 9) PROF(14);
          if (layer == 0) {
            if ((q & 1) == 0) {
              g_rowln[nb][grow + 8 * rr] = make_float2(mn, iv);
              if (warp - 8 == nb) {
                const float mu2 = mu + (mu - mn) * iv, inv2 = ln_inv(var * (1.f + iv) * (1.f + iv));
                st_relaxed4(&g_rowab[1][grow + 8 * rr], make_uint4(__float_as_uint((1.f + iv) * inv2), __float_as_uint((mn * iv + rbf(mu2)) * inv2), tag, 0));
              }
            }
            __syncwarp();
          } else {
            const uint32_t m2 = pack_bf16(mn, mn);
            uint8_t* row = smem + X_ST + (wg - 2) * 16384 + (q & 1) * 8192 + (wi * 16 + g + 8 * rr) * 128;
#pragma unroll 2
            for (int j = 0; j < 8; j++) {
              uint4* c = (uint4*)(row + (((j + lane) & 7) << 4));
              const uint4 v = *c;
              *c = make_uint4(add_ln_pair(v.x, m2, iv), add_ln_pair(v.y, m2, iv), add_ln_pair(v.z, m2, iv), add_ln_pair(v.w, m2, iv));
            }
            fence_async_smem();
          }
          if (warp == 15) asm volatile("bar.arrive 7, 512;" ::: "memory");
        }
        if (warp < 15) {
          uint32_t gu[64];
          mbar_wait(bar(B_GU + 1), layer);
#pragma unroll
          for (int j = 0; j < 16; j++) fetch_gu(gu + 4 * j, j, warp - 8);
          fence_async_smem();
          float d[4][4] = {};
          named_bar(7, 512);
#pragma unroll
          for (int hf = 0; hf < 2; hf++) {
            uint4 xv[4] = {};
            if (g == 0) {
#pragma unroll
              for (int j = 0; j < 4; j++) xv[j] = ((const uint4*)(smem + T_XS))[32 + hf * 16 + j * 4 + q];
            }
            __syncwarp();
#pragma unroll
            for (int j = 0; j < 4; j++) {
              const uint32_t* a = gu + hf * 32 + j * 8;
              mma_16816(d[(j & 1) * 2], a[0], a[1], a[2], a[3], xv[j].x, xv[j].y);
              mma_16816(d[(j & 1) * 2 + 1], a[4], a[5], a[6], a[7], xv[j].z, xv[j].w);
            }
          }
          send_gu((d[0][0] + d[1][0]) + (d[2][0] + d[3][0]), (d[0][2] + d[1][2]) + (d[2][2] + d[3][2]), warp - 8, 4);
          __syncwarp();
        }
        if (layer == 0) asm volatile("bar.arrive 9, 512;" ::: "memory");
        else {
        uint32_t wd[64];
        mbar_wait(bar(B_DN), layer);
#pragma unroll
        for (int j = 0; j < 16; j++) {
          const uint32_t row = sbase + wo_off(0) + ((warp - 8) * 2 + (j >> 3)) * 3584 + min((j & 1) * 16 + (mi >> 1) * 8 + (lane & 7), 27) * 128;
          ldsm_x4_t(row + ((((j & 6) + (mi & 1)) ^ ((row >> 7) & 7)) << 4), wd[4 * j], wd[4 * j + 1], wd[4 * j + 2], wd[4 * j + 3]);
        }
        fence_regs_u<64>(wd);
        uint32_t hf[4];
        named_bar(10, 288);
        *(uint4*)hf = *(const uint4*)(smem + OFF_PATCH + 256 + q * 16);
        if (warp == 9) PROF(19);
        float y[4][4] = {};
#pragma unroll
        for (int j = 0; j < 16; j++)
          mma_16816(y[j & 3], wd[4 * j], wd[4 * j + 1], wd[4 * j + 2], wd[4 * j + 3], g == j >> 1 ? hf[(j & 1) * 2] : 0u, g == j >> 1 ? hf[(j & 1) * 2 + 1] : 0u);
        {
          float e[4];
#pragma unroll
          for (int c = 0; c < 4; c++) { const int i = (c & 1) * 2 + (c >> 1); e[c] = (y[0][i] + y[1][i]) + (y[2][i] + y[3][i]); }
          const bool b0 = g & 1, b1 = g & 2;
          float t0 = __shfl_xor_sync(0xffffffffu, b0 ? e[0] : e[1], 4), t1 = __shfl_xor_sync(0xffffffffu, b0 ? e[2] : e[3], 4);
          const float f0 = b0 ? t0 : e[0], f1 = b0 ? e[1] : t0, f2 = b0 ? t1 : e[2], f3 = b0 ? e[3] : t1;
          t0 = __shfl_xor_sync(0xffffffffu, b1 ? f0 : f2, 8); t1 = __shfl_xor_sync(0xffffffffu, b1 ? f1 : f3, 8);
          st_relaxed4(&g_ypart[layer][bid * 256 + (warp - 8) * 32 + (q * 4 + (g & 3)) * 2 + (g >> 2)],
                      b1 ? make_uint4(__float_as_uint(t0), __float_as_uint(t1), __float_as_uint(f2), __float_as_uint(f3)) : make_uint4(__float_as_uint(f0), __float_as_uint(f1), __float_as_uint(t0), __float_as_uint(t1)));
        }
        if (warp == 9) PROF(20);
        asm volatile("bar.arrive 9, 384;" ::: "memory");
        cluster_arrive(); cluster_wait();
        return;
        }
      }
      const unsigned layer = pass;
      named_bar(1 + (fresh_tid() >> 7), 128);
      regs_inc<224>();
      float acc[2][96];
      float pa[2][2], pb[2][2];
      {
        PHASE_IDS
        const uint32_t da0 = dlo(SOFF, 16) + (wg - 2) * 512;
        constexpr uint32_t db0 = dlo(SOFF + SL_W, 2048);
        if (warp == 9) PROF(19 - 2 * layer);
        mbar_wait(bar(B_FULL), 0);
        if (warp == 9) PROF(29);
        if (warp == 9) STEPT(0);
        wg_fence();
        wg_ss192t_z(acc[0], da0, db0); wg_ss192t_z(acc[1], da0 + 1024, db0);
        wg_ss192t(acc[0], da0 + 2, db0 + 384, 1); wg_ss192t(acc[1], da0 + 1026, db0 + 384, 1);
        wg_commit();
        int s = 1, u = 0;
#pragma unroll 1
        for (int i = 1; i < 28; i++) {
          const uint32_t da = da0 + (s >> 1) * (STG >> 4) + (s & 1) * 4, db = db0 + (s >> 1) * (STG >> 4) + (s & 1) * (SL_HD >> 4);
          mbar_wait(bar(B_FULL + s), (u + (s > 1 ? layer : 0)) & 1);
          if (warp == 9 && !(i & 1)) STEPT(i >> 1);
          wg_fence();
          wg_ss192t(acc[0], da, db, 1); wg_ss192t(acc[1], da + 1024, db, 1);
          wg_ss192t(acc[0], da + 2, db + 384, 1); wg_ss192t(acc[1], da + 1026, db + 384, 1);
          wg_commit();
          wg_wait<1>();
          if (lane < 2 && i < 27) mbar_arrive_cluster(bar(B_EMPTY + (s == 0 ? 5 : s - 1)), lane);
          if (++s == 6) { s = 0; u++; }
        }
      }
      PHASE_IDS
      auto last_tile = [&](int m, int j) {
        const int e = (4 + j) % 6;
        const uint32_t da = dlo(SOFF + (e >> 1) * STG + (e & 1) * 64, 16) + (wg - 2) * 512 + m * 1024, db = dlo(SOFF + (e >> 1) * STG + SL_W + (e & 1) * SL_HD, 2048);
        wg_fence();
        wg_ss192t(acc[m], da, db, 1);
        wg_ss192t(acc[m], da + 2, db + 384, 1);
      };
      {
        if (layer == 0) mbar_wait(bar(B_CS), 0);
        const uint32_t tag = s_misc[M_TAG];
        const uint4* src = &g_rowab[layer][rb * 256 + (wg - 2 + (lane >> 4) * 2) * 64 + wi * 16 + (lane & 15)];
        uint4 v;
#pragma unroll
        for (int j = 0; j < 4; j++) {
          if (j == 2) v = ld_relaxed4(src);
          mbar_wait(bar(B_FULL + (4 + j) % 6), j < 2 ? layer : 1);
          last_tile(1, j);
          if (j == 0) { wg_commit(); wg_wait<1>(); mbar_arrive_e(bar(B_E23)); }
        }
        wg_commit();
        last_tile(0, 0);
        wg_commit();
        if (warp != 9) STEPT(4);
#pragma unroll 1
        for (uint32_t spins = 0; !__all_sync(0xffffffffu, v.z == tag) && spins < SPIN_LIMIT; spins++) v = ld_relaxed4(src);
#pragma unroll
        for (int j = 0; j < 4; j++) {
          pa[j >> 1][j & 1] = __uint_as_float(__shfl_sync(0xffffffffu, v.x, g + 8 * j));
          pb[j >> 1][j & 1] = __uint_as_float(__shfl_sync(0xffffffffu, v.y, g + 8 * j));
        }
        if (warp != 9) STEPT(5);
      }
      const int prow = (int)s_misc[M_SEL0] - rb * 256;
      const float4* cs = (const float4*)(smem + OFF_CS) + q;
      auto finish = [&](int m, int b, float2 c, uint32_t* dst) {
        dst[0] = pack_bf16(acc[m][4 * b] * pa[m][0] - c.x * pb[m][0], acc[m][4 * b + 1] * pa[m][0] - c.y * pb[m][0]);
        dst[1] = pack_bf16(acc[m][4 * b + 2] * pa[m][1] - c.x * pb[m][1], acc[m][4 * b + 3] * pa[m][1] - c.y * pb[m][1]);
      };
      auto grp = [](int n) { return n < 8 ? 4 + ((n >> 1) & 1) * 4 + (n >> 2) * 2 + (n & 1) : n - 8; };
      float4 cq[2] = {cs[grp(0) * 4], cs[grp(1) * 4]};
      auto next = [&](int m, int n, uint32_t* r) {
        if (m == 1 && n % 4 == 0) { last_tile(0, 1 + n / 4); wg_commit(); }
        const float4 c = cq[n & 1];
        cq[n & 1] = cs[grp((n + 2) % 12) * 4];
        finish(m, 2 * grp(n), make_float2(c.x, c.y), r); finish(m, 2 * grp(n) + 1, make_float2(c.z, c.w), r + 2);
      };
#pragma unroll
      for (int m = 1; m >= 0; m--) {
        if (m == 1) {
          wg_wait<1>();
          fence_regs<96>(acc[1]);
          mbar_wait(bar(B_E23), layer);
          if (warp != 9) STEPT(0);
        } else {
          wg_wait<0>();
          fence_regs<96>(acc[0]);
          if (warp != 9) STEPT(1);
          if (lane < 2) mbar_arrive_cluster(bar(B_QDONE), lane);
          if (warp == 9) PROF(2);
        }
        const int qb = wg - 2 + 2 * m;
        const bool patch = prow >> 4 == qb * 4 + wi;
#pragma unroll
        for (int jj = 0; jj < 8; jj++) {
          const int h = jj >> 2;
          uint32_t r[4];
          next(m, jj, r);
          if (m == 0 && jj == 0) named_bar(5, 256);
          stsm_x4(sbase + kv_off(h, 4 + 2 * m) + (wg - 2) * 8192 + ((jj >> 1) & 1) * 4096 + srow * 64 + ((((jj & 1) * 2 + (mi >> 1)) ^ ((srow >> 1) & 3)) << 4),
                  r[0], r[1], r[2], r[3]);
        }
        if (patch) {
          mbar_wait(bar(B_CS), 1);
          __syncwarp();
          if (lane < 16)
            *(uint4*)(smem + kv_off(g >> 1, 4 + qb) + (g & 1) * 4096 + (prow & 63) * 64 + ((q ^ ((prow >> 1) & 3)) << 4)) =
                *(const uint4*)(smem + OFF_PATCH + 128 + (g & 1) * 128 + (g >> 1) * 64 + q * 16);
        }
        fence_async_smem();
        __syncwarp();
        mbar_arrive_e(bar(B_KVREADY + 1 - m));
        if (warp != 9) STEPT(3 - m);
        pa[m][0] *= SM_C; pa[m][1] *= SM_C; pb[m][0] *= SM_C; pb[m][1] *= SM_C;
#pragma unroll
        for (int jj = 0; jj < 4; jj++) {
          uint32_t r[4];
          next(m, 8 + jj, r);
          *(uint4*)(smem + qo_off(jj >> 1, 2 * m) + (warp - 8) * 1024 + (jj & 1) * 512 + lane * 16) = make_uint4(r[0], r[1], r[2], r[3]);
        }
        __syncwarp();
        if (patch) {
          *(uint32_t*)(smem + qo_off(lane >> 4, 2 * m) + (warp - 8) * 1024 + (mi & 1) * 512 + ((prow & 7) * 4 + q) * 16 + ((g & 1) * 2 + ((prow >> 3) & 1)) * 4) =
              *(const uint32_t*)(smem + OFF_PATCH + lane * 4);
          __syncwarp();
        }
      }
      if (warp == 9) PROF(3);
      mbar_arrive_e(bar(B_QREADY));
      regs_dec<120>();
    } else {
      if (pass > 0) {
        const unsigned layer = pass - 1;
        PHASE_IDS
        const uint32_t tag = s_misc[M_TAG];
        if (warp == 7) {
              uint32_t* tab = (uint32_t*)(smem + OFF_PATCH);
#pragma unroll
              for (int j = 0; j < 2; j++) { const int w = lane + 32 * j; tab[(w & 3) * 16 + (w >> 2)] = ((const uint32_t*)P.w_r)[nb * 64 + w]; }
              tab[64 + lane] = lane < 16 ? 0x3F803F80u : 0u;
              float tot = 0.f;
#pragma unroll 1
              for (int j = 0; j < 4; j++) {
                const uint4 u = ((const uint4*)P.w_r)[lane + 32 * j];
                tot += bf_lo(u.x) + bf_hi(u.x) + bf_lo(u.y) + bf_hi(u.y) + bf_lo(u.z) + bf_hi(u.z) + bf_lo(u.w) + bf_hi(u.w);
              }
              s_misc[M_WSUM] = __float_as_uint(warp_sum(tot));
        }
              if (layer == 1) {
                const float2 ln = g_rowln[nb][mb * 128 + tid - 128];
                const uint32_t m2 = pack_bf16(ln.x, ln.x);
                uint8_t* row = smem + qo_off(0, wi & 2) + (tid & 63) * 128;
                mbar_wait(bar(B_RES), 1);
#pragma unroll 1
                for (int j = 0; j < 8; j++) {
                  uint4* c = (uint4*)(row + (((j + lane) & 7) << 4));
                  const uint4 v = c[0], w = c[512];
                  c[0] = make_uint4(add_ln_pair(v.x, m2, ln.y), add_ln_pair(v.y, m2, ln.y), add_ln_pair(v.z, m2, ln.y), add_ln_pair(v.w, m2, ln.y));
                  c[512] = make_uint4(add_ln_pair(w.x, m2, ln.y), add_ln_pair(w.y, m2, ln.y), add_ln_pair(w.z, m2, ln.y), add_ln_pair(w.w, m2, ln.y));
                }
                const int prow = (int)s_misc[M_SEL0] - mb * 128;
                __syncwarp();
                if (prow >> 5 == wi && lane < 16)
                  *(uint4*)(smem + qo_off(0, wi & 2) + (lane >> 3) * 8192 + (prow & 63) * 128 + (((lane ^ prow) & 7) << 4)) = poll4(&g_x2row[(nb * 16 + lane) * 2]);
                PROF(30);
              }
              __syncwarp();
              mbar_arrive_e(bar(B_RST));
        if (warp == 4) {
            named_bar(6, 320);
            spin_cycles(DELAY_S);
            uint4 c, u0, u1;
            uint32_t u2, best = 0, spins = 0;
            int src;
#pragma unroll 1
            for (;;) {
              src = (~best & 0x7FFu) >> 7;
              const uint4* xsel = &g_cand[layer][src * 128];
              c = ld_relaxed4(&g_slot[layer][(lane & 15) * 8]);
              u0 = ld_relaxed4(xsel + rank * 64 + lane); u1 = ld_relaxed4(xsel + rank * 64 + 32 + lane);
              u2 = ld_relaxed((const uint32_t*)(xsel + (bid >> 4) * 16 + q * 4) + (bid & 15));
              const uint32_t prev = best;
              best = __reduce_max_sync(0xffffffffu, c.w == tag ? c.x : 0u);
              if ((__all_sync(0xffffffffu, c.w == tag && valid4(u0) && valid4(u1) && u2 != SENT) && best == prev) || ++spins > SPIN_LIMIT) break;
            }
            const float sel_m = __uint_as_float(__shfl_sync(0xffffffffu, c.y, src)), sel_inv = __uint_as_float(__shfl_sync(0xffffffffu, c.z, src));
            const uint32_t m2 = pack_bf16(sel_m, sel_m);
            uint4* xs = (uint4*)(smem + T_XS) + (lane & 16) + q * 4 + (g & 3);
            xs[0] = make_uint4(ln_pair(u0.x, m2, sel_inv), ln_pair(u0.y, m2, sel_inv), ln_pair(u0.z, m2, sel_inv), ln_pair(u0.w, m2, sel_inv));
            xs[32] = make_uint4(ln_pair(u1.x, m2, sel_inv), ln_pair(u1.y, m2, sel_inv), ln_pair(u1.z, m2, sel_inv), ln_pair(u1.w, m2, sel_inv));
            s_misc[M_KEY] = best; s_misc[M_MEAN] = __float_as_uint(sel_m); s_misc[M_INV] = __float_as_uint(sel_inv);
            s_misc[M_XQ + q] = u2;
            if (layer == 0) s_misc[M_SEL0] = ~best & 0x7FFu;
            PROF(16);
        }
        if (layer == 1) {
          named_bar(7, 512);
          const int sel = SEQ - 1 - (int)(s_misc[M_KEY] & 0x7FFFu), skip = sel >> 7 == mb ? (sel >> 6) & 1 : -1;
          if (warp == 7) store_tile(1, skip, false);
          if (warp == 4) {
            mbar_wait_cluster(bar(B_HX), 1);
            ((bf16*)(smem + OFF_PATCH + 256))[((lane >> 1) & 3) * 8 + (lane >> 3) * 2 + (lane & 1)] = __float2bfloat16_rn(hidden());
            asm volatile("bar.arrive 10, 288;" ::: "memory");
          }
#pragma unroll 1
          for (int c = tid - 128; c < 1024 && skip >= 0; c += 128) {
            const int r = c >> 4;
            if (r != (sel & 63))
              *(uint4*)(P.out + (size_t)(mb * 128 + skip * 64 + r) * DM + nb * 128 + (c & 15) * 8) =
                  *(const uint4*)(smem + X_ST + skip * 16384 + ((c >> 3) & 1) * 8192 + r * 128 + (((c ^ r) & 7) << 4));
          }
          __syncwarp();
        } else asm volatile("bar.arrive 7, 512;" ::: "memory");
        if (warp == 5 && layer == 0) {
              named_bar(8, 288);
              if (nb > 0) spin_cycles(X_STAGGER);
              store_tile(0, -1, true);
              set_flag(&g_xflag[mb][nb].v[0], tag);
              PROF(17);
              poll_flag(&g_xflag[2 * rb + (lane & 1)][0].v[0], tag);
              fence_async_global();
              load_a(0, 0, 1); load_a(2, 2, 1);
              PROFL(1, 1);
        }
      }
      named_bar(1 + (fresh_tid() >> 7), 128);
      regs_dec<32>();
#pragma unroll 1
      for (;;) {
      const unsigned pass = __shfl_sync(0xffffffffu, pass_v, 0);
      if (pass > 0) {
        const unsigned layer = pass - 1;
        PHASE_IDS
        const uint32_t tag = s_misc[M_TAG], bkey = s_misc[M_KEY];
        const int sel = SEQ - 1 - (int)(bkey & 0x7FFFu);
        if (warp == 3) {
          if (layer == 1) {
#pragma unroll
            for (int j = 0; j < 3; j++) ((uint4*)g_vw)[bid * 96 + j * 32 + lane] = make_uint4(0, 0, 0, 0);
          }
          if (bid == 0 && lane == 0) g_sel[layer] = sel;
        }
        __syncwarp();
        if (layer == 0) {
          auto load_down = [&](int j) {
            mbar_expect_tx(bar(B_DN + j), 2 * FFN_PIECE);
            bulk_load_h(sbase + SL_F + j * 2 * FFN_PIECE, P.w_d + (size_t)(bid * 28 + j * 14) * DM, 2 * FFN_PIECE, bar(B_DN + j), policy_evict_first());
          };
          if (warp == 5) {
            poll_flag(&g_xflag[2 * rb + (lane & 1)][(lane >> 1) & 7].v[0], tag);
            fence_async_global();
            load_a(4, 4, 1);
          }
          float hv = 0.f;
          if (wg == 1) { mbar_wait_cluster(bar(B_HX), 0); hv = rbf(hidden()); fence_regs<1>(&hv); }
          named_bar(9, 512);
          if (warp == 0) {
            fence_async_smem();
            if (lane < 16) mbar_arrive_cluster(bar(B_QFREE), lane & 1);
            mbar_wait(bar(B_QFREE), 1);
            load_w(4, 4); load_w(5, 5);
            load_down(0);
          } else if (wg == 1) {
            if (warp == 4) { mbar_wait(bar(B_DN), 0); load_down(1); }
            float d[8] = {0.f, 0.f, 0.f, 0.f, 0.f, 0.f, 0.f, 0.f};
            const uint4* wrow = (const uint4*)(smem + SL_F) + tid - 128;
            mbar_wait(bar(B_DN), 0);
            uint4 w0 = wrow[0];
#pragma unroll 1
            for (int j = 0; j < 28; j += 2) {
              const uint4 w1 = wrow[j * 128 + 128];
              fma8(d, w0, __shfl_sync(0xffffffffu, hv, j));
              if (j == 12) mbar_wait(bar(B_DN + 1), 0);
              w0 = wrow[min(j + 2, 27) * 128];
              fma8(d, w1, __shfl_sync(0xffffffffu, hv, j + 1));
            }
            uint4* dst = &g_ypart[0][bid * 256 + (tid - 128) * 2];
            st_relaxed4(dst, make_uint4(__float_as_uint(d[0]), __float_as_uint(d[1]), __float_as_uint(d[2]), __float_as_uint(d[3])));
            st_relaxed4(dst + 1, make_uint4(__float_as_uint(d[4]), __float_as_uint(d[5]), __float_as_uint(d[6]), __float_as_uint(d[7])));
            asm volatile("bar.arrive 11, 160;" ::: "memory");
            PROF(20);
          } else if (warp == 2) {
            named_bar(11, 160);
            fence_async_smem();
            load_ws(WS_PACE);
          }
        } else {
          if (wg == 1) named_bar(9, 384);
          cluster_arrive();
        }
        if (wg == 1) {
          const int t_y = (int)clock();
          const uint32_t xw = s_misc[M_XQ + ((lane & 7) >> 1)];
          const float x = (lane & 1) ? bf_hi(xw) : bf_lo(xw);
          float xn = rbf(rbf(x - __uint_as_float(s_misc[M_MEAN])) * __uint_as_float(s_misc[M_INV]));
          uint32_t u = bkey & 0xFFFF0000u;
          u = (u & 0x80000000u) ? (u & 0x7FFFFFFFu) : (~u & 0xFFFF0000u);
          float sg = rbf(__fdividef(1.f, 1.f + __expf(-__uint_as_float(u))));
          uint32_t* dst = (layer == 0 ? (uint32_t*)&g_x2row[bid * 2] : (uint32_t*)(P.out + (size_t)sel * DM + bid * 8)) + (lane >> 1);
          asm volatile("" : "+f"(xn), "+f"(sg), "+l"(dst));
#pragma unroll 1
          while ((int)clock() - t_y < DELAY_Y) {}
          const uint4* src = &g_ypart[layer][((tid - 128) >> 1) * 256 + bid * 2 + (tid & 1)];
          uint4 v, w;
          uint32_t spins = 0;
#pragma unroll 1
          do { v = ld_relaxed4(src); w = ld_relaxed4(src + 64 * 256); } while (!__all_sync(0xffffffffu, valid4(v) && valid4(w)) && ++spins < SPIN_LIMIT);
          float a[4] = {__uint_as_float(v.x) + __uint_as_float(w.x), __uint_as_float(v.y) + __uint_as_float(w.y),
                        __uint_as_float(v.z) + __uint_as_float(w.z), __uint_as_float(v.w) + __uint_as_float(w.w)};
          const bool b1 = lane & 2, b2 = lane & 4;
          float c0 = (b1 ? a[1] : a[0]) + __shfl_xor_sync(0xffffffffu, b1 ? a[0] : a[1], 2);
          float c1 = (b1 ? a[3] : a[2]) + __shfl_xor_sync(0xffffffffu, b1 ? a[2] : a[3], 2);
          float y = (b2 ? c1 : c0) + __shfl_xor_sync(0xffffffffu, b2 ? c0 : c1, 4);
          y += __shfl_xor_sync(0xffffffffu, y, 8);
          y += __shfl_xor_sync(0xffffffffu, y, 16);
          float* red = (float*)(smem + OFF_PATCH);
          red[wi * 8 + (lane & 1) * 4 + ((lane >> 1) & 3)] = y;
          named_bar(2, 128);
          if (warp == 4) {
            PROF(21);
            y = (red[lane & 7] + red[8 + (lane & 7)]) + (red[16 + (lane & 7)] + red[24 + (lane & 7)]);
            const float res = x + rbf(xn + rbf(rbf(y) * sg));
            const uint32_t pr = pack_bf16(res, __shfl_down_sync(0xffffffffu, res, 1));
            if (lane < 8 && (lane & 1) == 0) st_relaxed(dst, pr);
            PROF(22);
          }
        }
        if (pass == 2) {
          if (bid == 0 && tid == 128) g_epoch = tag;
          bulk_wait_all();
          __syncwarp();
          cluster_wait();
          return;
        }
      }
      const unsigned layer = pass;
      if (__shfl_sync(0xffffffffu, fresh_tid() >> 5, 0) > 1 - (int)layer) {
        PHASE_IDS
        uint4* xrow = (uint4*)(smem + SL_F + 4 * SL_HD);
        if (wg == 1) {
          if (layer == 0) {
            xrow[tid - 128] = make_uint4(0x3F803F80u, 0x3F803F80u, 0x3F803F80u, 0x3F803F80u);
            if (warp == 5) {
              mbar_wait(bar(B_FULL + 5), 0);
              if (lane == 0) {
#pragma unroll 1
                for (int i = 11; i > 0; i--) prefetch_tmap(&P.mapA[0] + i);
              }
              __syncwarp();
              load_ws(WS_PACE);
            }
          } else xrow[tid - 128] = poll4(&g_x2row[(tid - 128) * 2]);
          PROF(23);
        }
        named_bar(12, 192 + 32 * layer);
        if (warp == 1) {
          float mean = 0.f;
#pragma unroll 1
          for (int pass2 = 0; pass2 < 2; pass2++) {
            float acc = 0.f;
#pragma unroll 1
            for (int j = lane; j < 128; j += 32) {
              const uint4 v = xrow[j];
              const uint32_t w[4] = {v.x, v.y, v.z, v.w};
#pragma unroll
              for (int c = 0; c < 4; c++) {
                const float d0 = bf_lo(w[c]) - mean, d1 = bf_hi(w[c]) - mean;
                acc += pass2 ? d0 * d0 + d1 * d1 : d0 + d1;
              }
            }
            acc = warp_sum(acc) * (1.f / DM);
            if (pass2 == 0) mean = acc;
            else { s_misc[M_PMEAN] = __float_as_uint(rbf(mean)); s_misc[M_PINV] = __float_as_uint(ln_inv(acc)); }
          }
        } else {
          mbar_wait(bar(B_WS), layer);
          const uint8_t* wa = smem + SL_F + (g >> 1) * SL_HD + ((warp - 2) >> 1) * 4096 + (g & 1) * 2048;
          const uint32_t* xs = (const uint32_t*)xrow + rb * 64 + g * 8;
          const int ch = (warp & 1) * 4 + q;
          float d[8] = {0.f, 0.f, 0.f, 0.f, 0.f, 0.f, 0.f, 0.f};
          auto wrow = [&](int j) { j = (j ^ ((g & 1) * 4)) & 15; return *(const uint4*)(wa + j * 128 + (((ch ^ j) & 7) << 4)); };
          uint4 w0 = wrow(0);
#pragma unroll 1
          for (int j = 0; j < 16; j += 2) {
            const uint32_t xx = xs[(j >> 1) ^ ((g & 1) * 2)];
            const uint4 w1 = wrow(j + 1);
            fma8(d, w0, bf_lo(xx));
            w0 = wrow(j + 2);
            fma8(d, w1, bf_hi(xx));
          }
#pragma unroll
          for (int c = 0; c < 4; c++) d[c] = ((g & 4) ? d[c + 4] : d[c]) + __shfl_xor_sync(0xffffffffu, (g & 4) ? d[c] : d[c + 4], 16);
#pragma unroll
          for (int c = 0; c < 2; c++) d[c] = ((g & 2) ? d[c + 2] : d[c]) + __shfl_xor_sync(0xffffffffu, (g & 2) ? d[c] : d[c + 2], 8);
          d[0] = ((g & 1) ? d[1] : d[0]) + __shfl_xor_sync(0xffffffffu, (g & 1) ? d[0] : d[1], 4);
          st_relaxed(&g_vw[layer][rb][((warp - 2) >> 1) * DM + hp * 64 + ch * 8 + g], enc(d[0]));
        }
        named_bar(12, 192 + 32 * layer);
        PROF(24);
      }
      PHASE_IDS
      if (wg == 0) {
        if (warp == 0) {
          if (layer == 0) {
#pragma unroll 1
            for (int i = 2; i < 6; i++) { load_w(i, i); if (!(i & 1)) load_a(i, i, 0); }
          }
          int s = 0, u = 0;
#pragma unroll 1
          for (int i = 6; i < 32; i++) {
            if (layer == 1) mbar_arrive_e(bar(B_EMPTY + s));
            mbar_wait(bar(B_EMPTY + s), (u + (s > 1 ? 0 : layer)) & 1);
            if (s & 1) load_a(s - 1, i - 1, layer);
            load_w(s, i);
            if (++s == 6) { s = 0; u++; }
          }
        } else if (warp == 1) {
          if (layer == 0) {
            const uint32_t tag = ld_relaxed(&g_epoch) + 1;
            if (lane < 16) g_rowab[0][rb * 256 + hp * 16 + lane] = make_uint4(0, 0, 0, 0);
            float shift = 0.f, sum = 0.f, sq = 0.f;
            const int r = hp * 16 + (lane >> 1);
#pragma unroll 1
            for (int i = 0; i < 32; i++) {
              mbar_wait(bar(B_FULL + i % 6), (i / 6) & 1);
              const uint8_t* base = smem + ((i % 6) >> 1) * STG + r * 128;
              uint4 v[2];
#pragma unroll
              for (int j = 0; j < 2; j++) v[j] = *(const uint4*)(base + ((((i & 1) * 4 + (lane & 1) * 2 + j) ^ (r & 7)) << 4));
              if (i == 0) shift = __shfl_sync(0xffffffffu, bf_lo(v[0].x), lane & ~1);
#pragma unroll
              for (int j = 0; j < 2; j++) {
                const uint32_t w[4] = {v[j].x, v[j].y, v[j].z, v[j].w};
#pragma unroll
                for (int c = 0; c < 4; c++) {
                  const float d0 = bf_lo(w[c]) - shift, d1 = bf_hi(w[c]) - shift;
                  sum += d0 + d1; sq = fmaf(d0, d0, fmaf(d1, d1, sq));
                }
              }
              fence_async_smem();
              __syncwarp();
              if (i < 26) mbar_arrive_e(bar(B_EMPTY + i % 6));
            }
            sum += __shfl_xor_sync(0xffffffffu, sum, 1); sq += __shfl_xor_sync(0xffffffffu, sq, 1);
            const float dm = sum * (1.f / DM), var = fmaxf(sq * (1.f / DM) - dm * dm, 0.f), mean = shift + dm;
            const float inv = ln_inv(var);
            if ((lane & 1) == 0) st_relaxed4(&g_rowab[0][rb * 256 + r], make_uint4(__float_as_uint(inv), __float_as_uint(rbf(mean) * inv), tag, 0));
          }
          __syncwarp();
          mbar_arrive_e(bar(B_E23));
          if (rb == 0) {
            mbar_wait(bar(B_QDONE), layer);
#pragma unroll 1
            for (int j = lane; j < 512; j += 32) ((uint4*)(smem + kv_off(1, 0)))[j] = make_uint4(0, 0, 0, 0);
            fence_async_smem();
            __syncwarp();
            if (lane < 3) mbar_arrive(bar(B_HALO + lane));
          }
        } else if (warp == 3) {
          if (rb > 0) { mbar_expect_tx(bar(B_HALO), 16384); mbar_expect_tx(bar(B_HALO + 1), 16384); mbar_expect_tx(bar(B_HALO + 2), 32768); }
          fence_async_smem();
          load_gu(0, layer ? GU_PACE1 : GU_PACE);
          PROF(27);
        } else {
          const uint4 sent = make_uint4(SENT, SENT, SENT, SENT), zero = make_uint4(0, 0, 0, 0);
          if (layer == 0) {
            const int f = lane >> 1;
            Flag* fl = f < 2 ? &g_kvflag[rb >> 1][hp][f] : f < 4 ? &g_oflag[rb][f & 1][hp] : &g_xflag[mb][nb];
            if (f < 5 && (f >= 2 || (rank == 1 && rb < 7))) ((uint4*)fl)[lane & 1] = zero;
          }
#pragma unroll 1
          for (int t = lane; t < 128; t += 32) {
            g_ypart[layer][bid * 256 + t] = sent; g_ypart[layer][bid * 256 + 128 + t] = sent;
            g_part[layer][nb * SEQ + mb * 128 + t] = zero;
            if (t < 16) g_cand[layer][mb * 128 + nb * 16 + t] = sent;
            else if (t < 18) { if (nb == 0) g_slot[layer][mb * 8 + t - 16] = zero; }
            else if (t < 20) { if (layer == 0) g_x2row[bid * 2 + t - 18] = sent; }
          }
          __syncwarp();
          mbar_arrive_e(bar(B_CS));
        }
        __syncwarp();
        uint8_t* kvg = g_kv + (size_t)(((rb - 1 + rank) >> 1) * 16 + hp) * 65536;
        if (rank == 0) {
          if (warp == 0) {
            mbar_wait(bar(B_QDONE), layer);
#pragma unroll 1
            for (int j = 0; j < 4; j++) {
              mbar_wait(bar(B_KVREADY + (j >> 1)), layer);
              bulk_push(mapa(sbase + kv_off(j & 1, 2 - (j & 2)), 1), sbase + kv_off(j & 1, 6 - (j & 2)), 16384, mapa(bar(B_HALO + min(j, 2)), 1));
            }
          } else if (warp < 3 && rb > 0) {
            const int p = warp - 1;
            mbar_wait(bar(B_QREADY), layer);
            if (p) spin_cycles(P1_DELAY);
            poll_flag(&g_kvflag[(rb - 1) >> 1][hp][p].v[layer], s_misc[M_TAG]);
            fence_async_global();
#pragma unroll 1
            for (int j = 2 * p; j < 2 * p + 2; j++) bulk_load_h(sbase + kv_off(j & 1, 2 - (j & 2)), kvg + j * 16384, 16384, bar(B_HALO + min(j, 2)), policy_evict_first());
            if (p == 0) PROF(5);
          }
        } else if (warp < 2 && rb < 7) {
          mbar_wait(bar(B_KVREADY + warp), layer);
          if (warp == 1) named_bar(13, 64);
#pragma unroll 1
          for (int j = 2 * warp; j < 2 * warp + 2; j++) bulk_store(kvg + j * 16384, sbase + kv_off(j & 1, 6 - (j & 2)), 16384);
          bulk_commit();
          bulk_wait_all();
          if (warp == 0) asm volatile("bar.arrive 13, 64;" ::: "memory");
          set_flag(&g_kvflag[rb >> 1][hp][warp].v[layer], s_misc[M_TAG]);
          if (warp == 0) PROF(4);
        }
      } else {
        const int t = tid - 128, go = (t >> 5) * DM + hp * 64 + (t & 31) * 2;
        if (layer == 0 && t == 96) { s_misc[M_TAG] = ld_relaxed(&g_epoch) + 1; s_misc[M_SEL0] = 0xFFFFFFFFu; s_misc[M_PROG] = s_misc[M_PROG + 1] = 0; }
        if ((layer == 0 || (int)s_misc[M_SEL0] >> 8 == rb) && warp < 7) {
          spin_cycles(layer ? 300 : 1500);
          uint2 w[8];
          uint32_t spins = 0;
          bool ok;
#pragma unroll 1
          do {
            ok = true;
#pragma unroll
            for (int j = 0; j < 8; j++) w[j] = ld_relaxed2(&g_vw[layer][j][go]);
#pragma unroll
            for (int j = 0; j < 8; j++) ok = ok && w[j].x && w[j].y;
          } while (!__all_sync(0xffffffffu, ok) && ++spins < SPIN_LIMIT);
          float s0 = 0.f, s1 = 0.f;
#pragma unroll
          for (int j = 0; j < 8; j++) { s0 += dec(w[j].x); s1 += dec(w[j].y); }
          float2* csp = (float2*)(smem + OFF_CS) + (t & ~7) + (t & 3) * 2 + ((t >> 2) & 1);
          if (layer == 0) *csp = make_float2(s0, s1);
          else {
            const float2 c = *csp;
            const float a = __uint_as_float(s_misc[M_PINV]) * (warp == 4 ? SM_C : 1.f), b = __uint_as_float(s_misc[M_PMEAN]) * a;
            ((uint32_t*)(smem + OFF_PATCH))[t] = pack_bf16(s0 * a - c.x * b, s1 * a - c.y * b);
          }
          PROF(25);
        }
        __syncwarp();
        mbar_arrive_e(bar(B_CS));
      }
      __syncwarp();
      if (wi == 0) mbar_wait(bar(B_QREADY), layer);
      named_bar(1 + (fresh_tid() >> 7), 128);
      if (__shfl_sync(0xffffffffu, fresh_tid() >> 7, 0) == 0) {
        regs_inc<152>();
        uint32_t gu[112];
        {
          PHASE_IDS
          const uint32_t tag = s_misc[M_TAG];
          mbar_wait(bar(B_GU), layer);
#pragma unroll
          for (int j = 0; j < 28; j++) fetch_gu(gu + 4 * j, warp * 4 + (j & 3), j >> 2);
          fence_async_smem();
          named_bar(1, 128);
          if (warp == 0) {
            mbar_wait(bar(B_ADONE), layer);
#pragma unroll 1
            for (int k = 2; k < 16; k++) {
#pragma unroll 1
              for (uint32_t spins = 0; (int)s_misc[M_PROG + (k >> 3)] <= (k & 7) + 16 * (int)layer && spins < SPIN_LIMIT; spins++) {}
              if (k >= 4) mbar_wait(bar(B_WEMPTY + (k & 3)), ((k >> 2) - 1 + ((k & 2) ? layer : 0)) & 1);
              load_o(k); load_wo(k);
              STEPT(16 + k);
              if (k == RES_K) { mbar_wait(bar(B_OST + 1), layer); load_res(1, layer); }
            }
            if (layer == 1) {
              mbar_wait(bar(B_WEMPTY + 1), 1);
              mbar_expect_tx(bar(B_DN), 4 * FFN_PIECE);
              tma_load3_h(sbase + wo_off(0), &P.mapD, 0, bid * 28, 0, bar(B_DN), policy_evict_first());
            }
            named_bar(6, 320);
            if (layer == 0) {
              mbar_wait(bar(B_QFREE), 0);
#pragma unroll 1
              for (int i = 0; i < 4; i++) load_w(i, i);
            } else tma_load3_h(sbase + wo_off(0) + 2 * FFN_PIECE, &P.mapD, 0, bid * 28, 8, bar(B_DN), policy_evict_first());
          } else if (warp < 3) {
            const int h = warp - 1;
#pragma unroll 1
            for (int qb = 3; qb >= 0; qb--) {
              mbar_wait(bar(B_UNIT + h * 4 + 3 - qb), layer);
              bulk_store(g_o + (size_t)((((rb * 2 + (qb >> 1)) * 2 + h) * 16 + hp) * 2 + (qb & 1)) * 4096, sbase + qo_off(h, qb), 4096);
            }
            bulk_commit();
            if (h == 0 && lane < 2) mbar_arrive_cluster(bar(B_OST), lane);
            bulk_wait_all();
            if (h == 1) mbar_arrive_e(bar(B_OST + 1));
            set_flag(&g_oflag[rb][h][hp].v[layer], tag);
            PROF(28 + 3 * h);
            if (h == 0) { load_res(0, layer); mbar_wait(bar(B_OST), layer); load_wo(0); load_wo(1); }
            int n = 0, first = h;
#pragma unroll 1
            for (uint32_t spins = 0; n < 8 && spins < SPIN_LIMIT; spins++) {
              n = (__ffs(__ballot_sync(0xffffffffu, ld_relaxed(&g_oflag[rb][h][lane & 15].v[layer]) != tag || lane == 16)) - 1) >> 1;
              asm volatile("fence.acquire.gpu;" ::: "memory");
              fence_async_global();
              if (!first && n >= 2) {
                first = 1;
                load_o(0); load_o(1);
                PROF(15);
              }
              s_misc[M_PROG + h] = n + 16 * layer;
            }
            if (h) PROF(26);
          } else {
            mbar_expect_tx(bar(B_HX), 2240);
            mbar_wait(bar(B_HALO + 2), layer);
            if (rb == 0) spin_cycles(2000);
            PROF(6);
            load_gu(1, GUB_PACE);
          }
        }
        PHASE_IDS
        uint4 xa = {}, xb = {};
        named_bar(7, 512);
        if (g == 0) { xa = ((const uint4*)(smem + T_XS))[warp * 8 + q]; xb = ((const uint4*)(smem + T_XS))[warp * 8 + 4 + q]; }
        __syncwarp();
        float d[7][4] = {};
#pragma unroll
        for (int j = 0; j < 28; j++) {
          const int ks = j / 7, ct = j % 7;
          const uint32_t* a = gu + ct * 16 + ks * 4;
          mma_16816(d[ct], a[0], a[1], a[2], a[3], ks == 0 ? xa.x : ks == 1 ? xa.z : ks == 2 ? xb.x : xb.z, ks == 0 ? xa.y : ks == 1 ? xa.w : ks == 2 ? xb.y : xb.w);
        }
#pragma unroll
        for (int ct = 0; ct < 7; ct++) send_gu(d[ct][0], d[ct][2], ct, warp);
        __syncwarp();
        if (warp == 2) PROF(18);
        regs_dec<32>();
        pass_v = pass + 1;
        continue;
      }
      break;
      }
      regs_inc<120>();
    }
    const unsigned layer = pass;
    {
      PHASE_IDS
      mbar_wait(bar(B_QREADY), layer);
      if (warp != 9) STEPT(7);
      const int bmin = rb == 0 ? 4 : 0;
      auto kdesc = [&](int h, int b) { const uint32_t v = dlo(SOFF, 16) + (kv_off(h, b) >> 4); return b < bmin ? dlo(SOFF + kv_off(1, 0), 16) : v; };
      auto vdesc = [&](int h, int b) {
        const uint32_t v = dlo(SOFF + 4096, OFF_ONES - 4096) + (kv_off(h, b) >> 10) * VSTEP;
        return b < bmin ? dlo(SOFF + kv_off(1, 0), 4096) : v;
      };
      const int units = wg == 3 ? 0x8630 : (wg == 2 ? 0x8721 : 0x854);
      auto need = [&](int h, int b) { if (b == 3 || b == 1) mbar_wait(bar(B_HALO + (b == 1 ? 2 : h)), layer); };
      auto load_q = [&](uint32_t* qf, int u) {
        *(uint4*)&qf[0] = *(const uint4*)(smem + qo_off(u >> 2, ~u & 3) + wi * 1024 + lane * 16);
        *(uint4*)&qf[4] = *(const uint4*)(smem + qo_off(u >> 2, ~u & 3) + wi * 1024 + 512 + lane * 16);
      };
      auto store_o = [&](const float* o, int u) {
        const float i0 = rcp(o[16]), i1 = rcp(o[18]);
        if (u >= 4 && lane < 2) mbar_arrive_cluster(bar(B_ADONE), lane);
#pragma unroll
        for (int j = 0; j < 2; j++)
          stsm_x4(sbase + qo_off(u >> 2, ~u & 3) + srow * 64 + (((2 * j + (mi >> 1)) ^ ((srow >> 1) & 3)) << 4),
                  pack_bf16(o[8 * j] * i0, o[8 * j + 1] * i0), pack_bf16(o[8 * j + 2] * i1, o[8 * j + 3] * i1),
                  pack_bf16(o[8 * j + 4] * i0, o[8 * j + 5] * i0), pack_bf16(o[8 * j + 6] * i1, o[8 * j + 7] * i1));
        fence_async_smem();
        __syncwarp();
        mbar_arrive_e(bar(B_UNIT + u));
      };
      int redo = 0;
      {
        const int dl = g - 2 * q;
        const uint32_t mt = shl_clamp(0xFFFFFFFFu, max(16 * dl + 16, 0));
        uint32_t qf[8];
        float s[32];
        load_q(qf, units & 7);
        wg_fence();
        qk64(s, qf, kdesc((units >> 2) & 1, 6 - (units & 3)));
        wg_commit();
        wg_wait<0>();
        fence_regs<32>(s);
#pragma unroll 1
        for (int ul = units; ul != 8; ul >>= 4) {
          const int u = ul & 7, h = u >> 2, qb = 3 - (u & 3);
          float o[20];
          uint32_t p1[16], p2[16], p3[16], p4[16], p5[16];
          if (warp != 9) STEPT(8 + nu * 8);
          exp_pack<8>(s, p1);
          fence_regs_u<16>(p1);
          need(h, qb + 2);
          {
            float s2[32];
            const uint32_t vd = vdesc(h, qb + 3);
            wg_fence();
            qk64(s2, qf, kdesc(h, qb + 2));
            wg_commit();
            wg_rs40t_z<H64>(o, p1[0], p1[1], p1[2], p1[3], vd);
            wg_rs40t<H64>(o, p1[4], p1[5], p1[6], p1[7], vd + VSTEP, 1);
            pv32(o, p1 + 8, vd + 2 * VSTEP);
            wg_commit();
            wg_wait<1>();
            fence_regs<32>(s2);
            if (warp != 9) STEPT(9 + nu * 8);
            exp_pack<8>(s2, p2);
            fence_regs_u<16>(p2);
            wg_wait<0>();
            fence_regs<20>(o);
          }
          need(h, qb + 1);
          {
            float s3[32];
            wg_fence();
            qk64(s3, qf, kdesc(h, qb + 1));
            wg_commit();
            pv32(o, p2, vdesc(h, qb + 2)); pv32(o, p2 + 8, vdesc(h, qb + 2) + 2 * VSTEP);
            wg_commit();
            wg_wait<1>();
            fence_regs<32>(s3);
            if (warp != 9) STEPT(10 + nu * 8);
            exp_pack<8>(s3, p3);
            fence_regs_u<16>(p3);
            wg_wait<0>();
            fence_regs<20>(o);
          }
          need(h, qb);
          const uint32_t kd = kdesc(h, qb + 4), kt = kdesc(h, qb), vd = vdesc(h, qb + 4), vt = vdesc(h, qb);
          {
            float sd[16], st[16];
            wg_fence();
            qk32x2(sd, st, qf, kd, kt);
            wg_commit();
            pv32(o, p3, vdesc(h, qb + 1)); pv32(o, p3 + 8, vdesc(h, qb + 1) + 2 * VSTEP);
            wg_commit();
            wg_wait<1>();
            fence_regs<16>(sd); fence_regs<16>(st);
            if (warp != 9) STEPT(11 + nu * 8);
            edge32(sd, st, p4, p4 + 8, wi, dl, mt);
            fence_regs_u<16>(p4);
            wg_wait<0>();
            fence_regs<20>(o);
          }
          const int un = (ul >> 4) == 8 ? 4 : (ul >> 4) & 7;
          {
            float sd[16], st[16];
            wg_fence();
            qk32x2(sd, st, qf, kd + 128, kt + 128);
            wg_commit();
            pv32(o, p4, vd); pv32(o, p4 + 8, vt);
            wg_commit();
            wg_wait<1>();
            fence_regs<16>(sd); fence_regs<16>(st);
            load_q(qf, un);
            edge32(sd, st, p5, p5 + 8, wi - 2, dl, mt);
            fence_regs_u<16>(p5);
          }
          need(un >> 2, 6 - (un & 3));
          wg_fence();
          pv32(o, p5, vd + 2 * VSTEP); pv32(o, p5 + 8, vt + 2 * VSTEP);
          wg_commit();
          qk64(s, qf, kdesc(un >> 2, 6 - (un & 3)));
          wg_commit();
          wg_wait<1>();
          fence_regs<20>(o);
          if (warp != 9) STEPT(12 + nu * 8);
          const bool unsafe = !(o[16] >= LSUM_MIN && o[16] <= LSUM_MAX && o[18] >= LSUM_MIN && o[18] <= LSUM_MAX);
          if (__any_sync(0xffffffffu, unsafe)) redo |= 1 << u;
          else store_o(o, u);
          wg_wait<0>();
          fence_regs<32>(s);
        }
      }
      if (warp != 9) STEPT(31);
      if (bar_red_or(1 + wg, 128, redo)) {
#pragma unroll 1
        for (int ul = units; ul != 8; ul >>= 4) {
          const int u = ul & 7;
          if (!bar_red_or(1 + wg, 128, redo >> u & 1)) continue;
          const int h = u >> 2, qb = 3 - (u & 3);
          uint32_t qf[8], p[16];
          float o[20], m0 = -INFINITY, m1 = -INFINITY;
          load_q(qf, u);
#pragma unroll
          for (int i = 0; i < 20; i++) o[i] = 0.f;
#pragma unroll 1
          for (int j = 0; j <= (rb == 0 ? qb : 4); j++) {
            const int b = qb + 4 - j;
            float s[32];
            wg_fence();
            qk64(s, qf, kdesc(h, b));
            wg_commit();
            wg_wait<0>();
            fence_regs<32>(s);
            float mx0 = m0, mx1 = m1;
#pragma unroll
            for (int c = 0; c < 8; c++) {
#pragma unroll
              for (int i = 0; i < 4; i++) {
                const int diff = j * 64 + (16 * wi + g + (i >> 1) * 8) - (8 * c + 2 * q + (i & 1));
                if (diff < 0 || diff > 255) s[4 * c + i] = -INFINITY;
              }
              mx0 = fmaxf(mx0, fmaxf(s[4 * c], s[4 * c + 1]));
              mx1 = fmaxf(mx1, fmaxf(s[4 * c + 2], s[4 * c + 3]));
            }
            mx0 = fmaxf(mx0, __shfl_xor_sync(0xffffffffu, mx0, 1)); mx1 = fmaxf(mx1, __shfl_xor_sync(0xffffffffu, mx1, 1));
            mx0 = fmaxf(mx0, __shfl_xor_sync(0xffffffffu, mx0, 2)); mx1 = fmaxf(mx1, __shfl_xor_sync(0xffffffffu, mx1, 2));
            const float r0 = j == 0 ? 0.f : ex2(m0 - mx0), r1 = j == 0 ? 0.f : ex2(m1 - mx1);
            m0 = mx0; m1 = mx1;
#pragma unroll
            for (int i = 0; i < 5; i++) { o[4 * i] *= r0; o[4 * i + 1] *= r0; o[4 * i + 2] *= r1; o[4 * i + 3] *= r1; }
#pragma unroll
            for (int c = 0; c < 8; c++) { s[4 * c] -= m0; s[4 * c + 1] -= m0; s[4 * c + 2] -= m1; s[4 * c + 3] -= m1; }
            exp_pack<8>(s, p);
            fence_regs<20>(o); fence_regs_u<16>(p);
            wg_fence();
            pv32(o, p, vdesc(h, b)); pv32(o, p + 8, vdesc(h, b) + 2 * VSTEP);
            wg_commit();
            wg_wait<0>();
            fence_regs<20>(o);
          }
          named_bar(1 + wg, 128);
          if (redo >> u & 1) store_o(o, u);
          __syncwarp();
        }
      }
      if (wi == 0) PROF(6 + wg);
    }
    pass_v = pass + 1;
  }
}

}

typedef CUresult (*EncodeFn)(CUtensorMap*, CUtensorMapDataType, cuuint32_t, void*, const cuuint64_t*, const cuuint64_t*,
                             const cuuint32_t*, const cuuint32_t*, CUtensorMapInterleave, CUtensorMapSwizzle,
                             CUtensorMapL2promotion, CUtensorMapFloatOOBfill);
static EncodeFn g_encode = nullptr;
struct Dim { uint64_t size, stride; uint32_t box; };
template <int N> static CUtensorMap make_map(const void* ptr, const Dim (&d)[N], int swizzle) {
  CUtensorMap m;
  cuuint64_t dims[N], strides[N];
  cuuint32_t box[N], es[N];
  for (int i = 0; i < N; i++) { dims[i] = d[i].size; strides[i] = d[i].stride; box[i] = d[i].box; es[i] = 1; }
  g_encode(&m, CU_TENSOR_MAP_DATA_TYPE_BFLOAT16, N, const_cast<void*>(ptr), dims, strides + 1, box, es, CU_TENSOR_MAP_INTERLEAVE_NONE,
           swizzle == 128 ? CU_TENSOR_MAP_SWIZZLE_128B : (swizzle == 64 ? CU_TENSOR_MAP_SWIZZLE_64B : CU_TENSOR_MAP_SWIZZLE_NONE),
           swizzle ? CU_TENSOR_MAP_L2_PROMOTION_L2_256B : CU_TENSOR_MAP_L2_PROMOTION_L2_128B, CU_TENSOR_MAP_FLOAT_OOB_FILL_NONE);
  return m;
}
static CUtensorMap map2(const void* ptr, uint64_t inner, uint64_t outer, uint32_t bi, uint32_t bo, int swizzle) {
  const Dim d[2] = {{inner, 0, bi}, {outer, inner * 2, bo}};
  return make_map(ptr, d, swizzle);
}
template <class T> static void* sym_addr(T& sym) { void* p = nullptr; cudaGetSymbolAddress(&p, sym); return p; }

static Params h_p;
static const void* h_key[9];

static cudaLaunchConfig_t launch_cfg(int grid, cudaLaunchAttribute* at) {
  cudaLaunchConfig_t cfg = {};
  cfg.gridDim = dim3(grid); cfg.blockDim = dim3(512); cfg.dynamicSmemBytes = SMEM_BYTES; cfg.stream = cudaStreamPerThread;
  at[0].id = cudaLaunchAttributeClusterDimension;
  at[0].val.clusterDim.x = 2; at[0].val.clusterDim.y = 1; at[0].val.clusterDim.z = 1;
  cfg.attrs = at; cfg.numAttrs = 1;
  return cfg;
}

extern "C" void kernel_launch(void* const* d_in, const int* in_sizes, int n_in, void* d_out, int out_size) {
  const bf16* x = (const bf16*)d_in[0];
  const bf16* wqkv = (const bf16*)d_in[1];
  const bf16* wo = (const bf16*)d_in[2];
  cudaLaunchAttribute at[1];
  bool fresh = g_encode != nullptr && h_key[8] == d_out;
  for (int i = 0; i < 8; i++) fresh = fresh && h_key[i] == d_in[i];
  if (!fresh) {
    if (!g_encode) {
      void* fn = nullptr;
      cudaDriverEntryPointQueryResult st;
      cudaGetDriverEntryPoint("cuTensorMapEncodeTiled", &fn, cudaEnableDefault, &st);
      g_encode = (EncodeFn)fn;
      cudaFuncSetAttribute(mega_kernel, cudaFuncAttributeMaxDynamicSharedMemorySize, SMEM_BYTES);
    }
    bf16* x1 = (bf16*)sym_addr(g_x1);
    Params& p = h_p;
    p.w_r = (const bf16*)d_in[4]; p.w_d = (const bf16*)d_in[7];
    p.out = (bf16*)d_out;
    p.mapA[0] = map2(x, DM, SEQ, 64, 256, 128);
    p.mapA[1] = map2(x1, DM, SEQ, 64, 256, 128);
    { const Dim d[3] = {{DM, 0, 64}, {DM, 3 * DM * 2, 16}, {3, DM * 2, 3}}; p.mapW = make_map(wqkv, d, 128); }
    { const Dim d[3] = {{DM, 0, 64}, {DM, 3 * DM * 2, 32}, {3, DM * 2, 3}}; p.mapWs = make_map(wqkv, d, 128); }
    { const Dim d[3] = {{DM, 0, 64}, {64, DM * 2, 32}, {16, 64 * DM * 2, 2}}; p.mapWo = make_map(wo, d, 128); }
    p.mapRes[0] = map2(x, DM, SEQ, 64, 64, 128);
    p.mapRes[1] = p.mapXst[0] = map2(x1, DM, SEQ, 64, 64, 128);
    p.mapXst[1] = map2(d_out, DM, SEQ, 64, 64, 128);
    p.mapG = map2(d_in[5], FF, DM, 56, 128, 0);
    p.mapU = map2(d_in[6], FF, DM, 56, 128, 0);
    { const Dim d[3] = {{64, 0, 64}, {FF, DM * 2, 28}, {DM / 64, 128, 8}}; p.mapD = make_map(p.w_d, d, 128); }
    for (int i = 0; i < 8; i++) h_key[i] = d_in[i];
    h_key[8] = d_out;
  }
  void* a0[] = {&h_p};
  cudaLaunchConfig_t cfg = launch_cfg(128, at);
  cudaLaunchKernelExC(&cfg, (const void*)mega_kernel, a0);
}
```

```cpp
#include <cuda_runtime.h>
#include <cuda_bf16.h>
#include <cuda.h>
#include <stdint.h>
#pragma nv_diag_suppress 550

namespace {

constexpr int SEQ = 2048, DM = 1024, FF = 3584;
constexpr float LN_EPS = 1e-5f;
typedef __nv_bfloat16 bf16;

__device__ __align__(1024) uint8_t g_kv[3 * 16 * 65536];
__device__ __align__(1024) uint8_t g_o[SEQ * DM * 2];
__device__ __align__(1024) bf16 g_x1[SEQ * DM];
__device__ unsigned g_epoch;
struct __align__(128) Flag { unsigned v[32]; };
__device__ Flag g_kvflag[3][16][2], g_oflag[8][2][16], g_xflag[16][8];
__device__ uint4 g_rowab[2][SEQ];
__device__ __align__(16) uint32_t g_vw[2][8][3 * DM];
constexpr uint32_t SENT = 0xFFFFFFFFu;
__device__ uint4 g_part[2][8 * SEQ];
__device__ uint4 g_slot[2][16 * 8];
__device__ uint4 g_cand[2][16 * 128];
__device__ uint4 g_ypart[2][128 * DM / 4];
__device__ uint4 g_x2row[128 * 2];
__device__ float2 g_rowln[8][SEQ];
__device__ int g_sel[2];

#define PROFL(l, e)
#define PROF(e) PROFL(layer, e)
#define STEPT(i)
#define SPIN_LIMIT 4000000u
__device__ __forceinline__ uint32_t smem_u32(const void* p) { return (uint32_t)__cvta_generic_to_shared(p); }
__device__ __forceinline__ void mbar_init(uint32_t bar, uint32_t cnt) {
  asm volatile("mbarrier.init.shared::cta.b64 [%0], %1;" ::"r"(bar), "r"(cnt) : "memory");
}
#define ELECT "{\n.reg .pred e;\nelect.sync _|e, 0xffffffff;\n@e "
__device__ __forceinline__ void mbar_expect_tx(uint32_t bar, uint32_t bytes) {
  asm volatile(ELECT "mbarrier.arrive.expect_tx.shared::cta.b64 _, [%0], %1;\n}" ::"r"(bar), "r"(bytes) : "memory");
}
__device__ __forceinline__ void mbar_arrive(uint32_t bar) {
  asm volatile("mbarrier.arrive.shared::cta.b64 _, [%0];" ::"r"(bar) : "memory");
}
__device__ __forceinline__ void mbar_arrive_e(uint32_t bar) {
  asm volatile(ELECT "mbarrier.arrive.shared::cta.b64 _, [%0];\n}" ::"r"(bar) : "memory");
}
__device__ __forceinline__ uint32_t mapa(uint32_t addr, uint32_t cta) {
  uint32_t r; asm("mapa.shared::cluster.u32 %0, %1, %2;" : "=r"(r) : "r"(addr), "r"(cta)); return r;
}
__device__ __forceinline__ void mbar_arrive_cluster(uint32_t bar, uint32_t cta) {
  asm volatile("mbarrier.arrive.shared::cluster.b64 _, [%0];" ::"r"(mapa(bar, cta)) : "memory");
}
#define MBAR_WAIT_ASM(QUAL)                                                                                                \
  asm volatile("{\n.reg .pred p;\nWAIT_LOOP:\n.pragma \"nounroll\";\nmbarrier.try_wait.parity" QUAL ".shared::cta.b64 p, [%0], %1;\n" \
               "@!p bra WAIT_LOOP;\n}" ::"r"(bar), "r"(parity) : "memory")
__device__ __forceinline__ void mbar_wait(uint32_t bar, uint32_t parity) { MBAR_WAIT_ASM(""); }
__device__ __forceinline__ void mbar_wait_cluster(uint32_t bar, uint32_t parity) { MBAR_WAIT_ASM(".acquire.cluster"); }
__device__ __forceinline__ void st_async2(uint32_t addr, float a, float b, uint32_t bar) {
  asm volatile("st.async.weak.shared::cluster.mbarrier::complete_tx::bytes.v2.f32 [%0], {%1, %2}, [%3];"
               ::"r"(addr), "f"(a), "f"(b), "r"(bar) : "memory");
}
__device__ __forceinline__ uint64_t policy_evict_first() {
  uint64_t p; asm volatile("createpolicy.fractional.L2::evict_first.b64 %0, 1.0;" : "=l"(p)); return p;
}
__device__ __forceinline__ void tma_load2(uint32_t dst, const CUtensorMap* m, int c0, int c1, uint32_t bar) {
  asm volatile(ELECT "cp.async.bulk.tensor.2d.shared::cluster.global.mbarrier::complete_tx::bytes [%0], [%1, {%3, %4}], [%2];\n}"
               ::"r"(dst), "l"(m), "r"(bar), "r"(c0), "r"(c1) : "memory");
}
__device__ __forceinline__ void tma_load2_h(uint32_t dst, const CUtensorMap* m, int c0, int c1, uint32_t bar, uint64_t pol) {
  asm volatile(ELECT "cp.async.bulk.tensor.2d.shared::cluster.global.mbarrier::complete_tx::bytes.L2::cache_hint [%0], [%1, {%3, %4}], [%2], %5;\n}"
               ::"r"(dst), "l"(m), "r"(bar), "r"(c0), "r"(c1), "l"(pol) : "memory");
}
__device__ __forceinline__ void tma_load3(uint32_t dst, const CUtensorMap* m, int c0, int c1, int c2, uint32_t bar) {
  asm volatile(ELECT "cp.async.bulk.tensor.3d.shared::cluster.global.mbarrier::complete_tx::bytes [%0], [%1, {%3, %4, %5}], [%2];\n}"
               ::"r"(dst), "l"(m), "r"(bar), "r"(c0), "r"(c1), "r"(c2) : "memory");
}
__device__ __forceinline__ void tma_load3_h(uint32_t dst, const CUtensorMap* m, int c0, int c1, int c2, uint32_t bar, uint64_t pol) {
  asm volatile(ELECT "cp.async.bulk.tensor.3d.shared::cluster.global.mbarrier::complete_tx::bytes.L2::cache_hint [%0], [%1, {%3, %4, %5}], [%2], %6;\n}"
               ::"r"(dst), "l"(m), "r"(bar), "r"(c0), "r"(c1), "r"(c2), "l"(pol) : "memory");
}
__device__ __forceinline__ void tma_load3_mc(uint32_t dst, const CUtensorMap* m, int c0, int c1, int c2, uint32_t bar) {
  asm volatile(ELECT "cp.async.bulk.tensor.3d.shared::cluster.global.mbarrier::complete_tx::bytes.multicast::cluster [%0], [%1, {%3, %4, %5}], [%2], %6;\n}"
               ::"r"(dst), "l"(m), "r"(bar), "r"(c0), "r"(c1), "r"(c2), "h"((uint16_t)3) : "memory");
}
__device__ __forceinline__ void bulk_push(uint32_t dst, uint32_t src, uint32_t bytes, uint32_t bar) {
  asm volatile(ELECT "cp.async.bulk.shared::cluster.shared::cta.mbarrier::complete_tx::bytes [%0], [%1], %2, [%3];\n}"
               ::"r"(dst), "r"(src), "r"(bytes), "r"(bar) : "memory");
}
template <int N> __device__ __forceinline__ void regs_inc() { asm volatile("setmaxnreg.inc.sync.aligned.u32 %0;" ::"n"(N)); }
template <int N> __device__ __forceinline__ void regs_dec() { asm volatile("setmaxnreg.dec.sync.aligned.u32 %0;" ::"n"(N)); }
__device__ __forceinline__ void tma_store(const CUtensorMap* m, uint32_t src, int c0, int c1) {
  asm volatile(ELECT "cp.async.bulk.tensor.2d.global.shared::cta.bulk_group [%0, {%2, %3}], [%1];\n}"
               ::"l"(m), "r"(src), "r"(c0), "r"(c1) : "memory");
}
__device__ __forceinline__ void bulk_load_h(uint32_t dst, const void* src, uint32_t bytes, uint32_t bar, uint64_t pol) {
  asm volatile(ELECT "cp.async.bulk.shared::cluster.global.mbarrier::complete_tx::bytes.L2::cache_hint [%0], [%1], %2, [%3], %4;\n}"
               ::"r"(dst), "l"(src), "r"(bytes), "r"(bar), "l"(pol) : "memory");
}
__device__ __forceinline__ void bulk_store(void* dst, uint32_t src, uint32_t bytes) {
  asm volatile(ELECT "cp.async.bulk.global.shared::cta.bulk_group [%0], [%1], %2;\n}" ::"l"(dst), "r"(src), "r"(bytes) : "memory");
}
__device__ __forceinline__ void bulk_commit() { asm volatile("cp.async.bulk.commit_group;" ::: "memory"); }
__device__ __forceinline__ void bulk_wait_all() { asm volatile("cp.async.bulk.wait_group 0;" ::: "memory"); }
__device__ __forceinline__ void fence_async_smem() { asm volatile("fence.proxy.async.shared::cta;" ::: "memory"); }
__device__ __forceinline__ void fence_async_global() { asm volatile("fence.proxy.async.global;" ::: "memory"); }
__device__ __forceinline__ void prefetch_tmap(const CUtensorMap* m) { asm volatile("prefetch.tensormap [%0];" ::"l"(m) : "memory"); }
__device__ __forceinline__ void named_bar(int id, int n) { asm volatile("bar.sync %0, %1;" ::"r"(id), "r"(n) : "memory"); }
__device__ __forceinline__ bool bar_red_or(int id, int n, bool v) {
  uint32_t r;
  asm volatile("{\n.reg .pred p, q;\nsetp.ne.u32 q, %3, 0;\nbarrier.cta.red.or.pred p, %1, %2, q;\nselp.u32 %0, 1, 0, p;\n}"
               : "=r"(r) : "r"(id), "r"(n), "r"((uint32_t)v) : "memory");
  return r != 0;
}
__device__ __forceinline__ void cluster_arrive() { asm volatile("barrier.cluster.arrive.relaxed.aligned;" ::: "memory"); }
__device__ __forceinline__ void cluster_wait() { asm volatile("barrier.cluster.wait.aligned;" ::: "memory"); }
__device__ __forceinline__ unsigned ld_relaxed(const unsigned* p) {
  unsigned v; asm volatile("ld.relaxed.gpu.global.u32 %0, [%1];" : "=r"(v) : "l"(p) : "memory"); return v;
}
__device__ __forceinline__ uint4 ld_relaxed4(const uint4* p) {
  uint4 v; asm volatile("ld.relaxed.gpu.global.v4.u32 {%0, %1, %2, %3}, [%4];" : "=r"(v.x), "=r"(v.y), "=r"(v.z), "=r"(v.w) : "l"(p) : "memory"); return v;
}
__device__ __forceinline__ void st_relaxed(unsigned* p, unsigned v) {
  asm volatile("st.relaxed.gpu.global.u32 [%0], %1;" ::"l"(p), "r"(v) : "memory");
}
__device__ __forceinline__ uint2 ld_relaxed2(const void* p) {
  uint2 v; asm volatile("ld.relaxed.gpu.global.v2.u32 {%0, %1}, [%2];" : "=r"(v.x), "=r"(v.y) : "l"(p) : "memory"); return v;
}
__device__ __forceinline__ void st_relaxed4(uint4* p, uint4 v) {
  asm volatile("st.relaxed.gpu.global.v4.u32 [%0], {%1, %2, %3, %4};" ::"l"(p), "r"(v.x), "r"(v.y), "r"(v.z), "r"(v.w) : "memory");
}
__device__ __forceinline__ bool valid4(uint4 v) { return v.x != SENT && v.y != SENT && v.z != SENT && v.w != SENT; }
__device__ __forceinline__ uint4 poll4(const uint4* p) {
  uint4 v;
  uint32_t spins = 0;
#pragma unroll 1
  do { v = ld_relaxed4(p); } while (!valid4(v) && ++spins < SPIN_LIMIT);
  return v;
}
__device__ __forceinline__ void set_flag(unsigned* p, unsigned tag) {
  asm volatile(ELECT "st.release.gpu.global.u32 [%0], %1;\n}" ::"l"(p), "r"(tag) : "memory");
}
__device__ __forceinline__ void poll_flag(const unsigned* p, unsigned tag) {
#pragma unroll 1
  for (uint32_t spins = 0; !__all_sync(0xffffffffu, ld_relaxed(p) == tag) && spins < SPIN_LIMIT; spins++) {}
  asm volatile("fence.acquire.gpu;" ::: "memory");
}
__device__ __forceinline__ uint32_t enc(float x) { return __float_as_uint(x + 0.0f) ^ 0x80000000u; }
__device__ __forceinline__ float dec(uint32_t u) { return __uint_as_float(u ^ 0x80000000u); }
__device__ __forceinline__ uint32_t hadd_bf2(uint32_t a, uint32_t b) {
  uint32_t r; asm("add.rn.bf16x2 %0, %1, %2;" : "=r"(r) : "r"(a), "r"(b)); return r;
}
__device__ __forceinline__ uint32_t hsub_bf2(uint32_t a, uint32_t b) {
  uint32_t r; asm("sub.rn.bf16x2 %0, %1, %2;" : "=r"(r) : "r"(a), "r"(b)); return r;
}
__device__ __forceinline__ void wg_fence() { asm volatile("wgmma.fence.sync.aligned;" ::: "memory"); }
__device__ __forceinline__ void wg_commit() { asm volatile("wgmma.commit_group.sync.aligned;" ::: "memory"); }
template <int N> __device__ __forceinline__ void wg_wait() { asm volatile("wgmma.wait_group.sync.aligned %0;" ::"n"(N) : "memory"); }
template <int R> __device__ __forceinline__ void fence_regs(float* d) {
#pragma unroll
  for (int i = 0; i < R; i++) asm volatile("" : "+f"(d[i])::"memory");
}
template <int R> __device__ __forceinline__ void fence_regs_u(uint32_t* d) {
#pragma unroll
  for (int i = 0; i < R; i++) asm volatile("" : "+r"(d[i])::"memory");
}
__host__ __device__ constexpr uint32_t dlo(uint32_t addr, uint32_t lbo) { return ((addr & 0x3FFFF) >> 4) | ((lbo >> 4) << 16); }
constexpr uint32_t H128 = 0x40000040u, H64 = 0x80000020u;
__device__ __forceinline__ void stsm_x4(uint32_t addr, uint32_t r0, uint32_t r1, uint32_t r2, uint32_t r3) {
  asm volatile("stmatrix.sync.aligned.m8n8.x4.shared.b16 [%0], {%1, %2, %3, %4};"
               ::"r"(addr), "r"(r0), "r"(r1), "r"(r2), "r"(r3) : "memory");
}
__device__ __forceinline__ void ldsm_x4(uint32_t addr, uint32_t& r0, uint32_t& r1, uint32_t& r2, uint32_t& r3) {
  asm volatile("ldmatrix.sync.aligned.m8n8.x4.shared.b16 {%0, %1, %2, %3}, [%4];"
               : "=r"(r0), "=r"(r1), "=r"(r2), "=r"(r3) : "r"(addr) : "memory");
}
__device__ __forceinline__ void ldsm_x4_t(uint32_t addr, uint32_t& r0, uint32_t& r1, uint32_t& r2, uint32_t& r3) {
  asm volatile("ldmatrix.sync.aligned.m8n8.x4.trans.shared.b16 {%0, %1, %2, %3}, [%4];"
               : "=r"(r0), "=r"(r1), "=r"(r2), "=r"(r3) : "r"(addr) : "memory");
}
__device__ __forceinline__ void mma_16816(float* d, uint32_t a0, uint32_t a1, uint32_t a2, uint32_t a3, uint32_t b0, uint32_t b1) {
  asm volatile("mma.sync.aligned.m16n8k16.row.col.f32.bf16.bf16.f32 {%0, %1, %2, %3}, {%4, %5, %6, %7}, {%8, %9}, {%0, %1, %2, %3};"
               : "+f"(d[0]), "+f"(d[1]), "+f"(d[2]), "+f"(d[3]) : "r"(a0), "r"(a1), "r"(a2), "r"(a3), "r"(b0), "r"(b1));
}
__device__ __forceinline__ void spin_cycles(int n) {
  const int t0 = (int)clock();
#pragma unroll 1
  while ((int)clock() - t0 < n) {}
}
__device__ __forceinline__ uint32_t pack_bf16(float lo, float hi) {
  uint32_t r; asm("cvt.rn.bf16x2.f32 %0, %1, %2;" : "=r"(r) : "f"(hi), "f"(lo)); return r;
}
__device__ __forceinline__ float bf_lo(uint32_t v) { return __uint_as_float(v << 16); }
__device__ __forceinline__ float bf_hi(uint32_t v) { return __uint_as_float(v & 0xffff0000u); }
__device__ __forceinline__ float rbf(float x) { return __bfloat162float(__float2bfloat16_rn(x)); }
__device__ __forceinline__ float ex2(float x) { float y; asm("ex2.approx.ftz.f32 %0, %1;" : "=f"(y) : "f"(x)); return y; }
__device__ __forceinline__ float rcp(float x) { float y; asm("rcp.approx.ftz.f32 %0, %1;" : "=f"(y) : "f"(x)); return y; }
__device__ __forceinline__ uint32_t shl_clamp(uint32_t v, uint32_t n) {
  uint32_t r; asm("shl.b32 %0, %1, %2;" : "=r"(r) : "r"(v), "r"(n)); return r;
}
__device__ __forceinline__ float warp_sum(float v) {
#pragma unroll
  for (int o = 16; o > 0; o >>= 1) v += __shfl_xor_sync(0xffffffffu, v, o);
  return v;
}
__device__ __forceinline__ float ln_inv(float var) {
  float r;
  asm("sqrt.approx.ftz.f32 %0, %1;" : "=f"(r) : "f"(rbf(rbf(var) + LN_EPS)));
  asm("rcp.approx.ftz.f32 %0, %1;" : "=f"(r) : "f"(rbf(r)));
  return r;
}
__device__ __forceinline__ uint32_t ln_pair(uint32_t x, uint32_t mean2, float inv) {
  const uint32_t d = hsub_bf2(x, mean2);
  return pack_bf16(bf_lo(d) * inv, bf_hi(d) * inv);
}
__device__ __forceinline__ uint32_t add_ln_pair(uint32_t x, uint32_t mean2, float inv) { return hadd_bf2(x, ln_pair(x, mean2, inv)); }
__device__ __forceinline__ uint32_t router_key(float r_bf, int row) {
  uint32_t u = __float_as_uint(r_bf);
  u = (u & 0x80000000u) ? ~u : (u | 0x80000000u);
  return (u & 0xFFFF0000u) | 0x8000u | (uint32_t)(SEQ - 1 - row);
}

template <uint32_t HA = 0x40000040u, uint32_t HB = 0x40000040u>
__device__ __forceinline__ void wg_ss192t(float* d, uint32_t da, uint32_t db, int scale_d) {
  asm volatile("{\n.reg .pred p;\n.reg .b64 dA, dB;\nmov.b64 dA, {%96, %99};\nmov.b64 dB, {%97, %100};\nsetp.ne.b32 p, %98, 0;\n"
    "wgmma.mma_async.sync.aligned.m64n192k16.f32.bf16.bf16 "
    "{%0, %1, %2, %3, %4, %5, %6, %7, %8, %9, %10, %11, %12, %13, %14, %15, "
    "%16, %17, %18, %19, %20, %21, %22, %23, %24, %25, %26, %27, %28, %29, %30, %31, "
    "%32, %33, %34, %35, %36, %37, %38, %39, %40, %41, %42, %43, %44, %45, %46, %47, "
    "%48, %49, %50, %51, %52, %53, %54, %55, %56, %57, %58, %59, %60, %61, %62, %63, "
    "%64, %65, %66, %67, %68, %69, %70, %71, %72, %73, %74, %75, %76, %77, %78, %79, "
    "%80, %81, %82, %83, %84, %85, %86, %87, %88, %89, %90, %91, %92, %93, %94, %95}, "
    "dA, dB, p, 1, 1, 0, 1;\n}\n"
    : "+f"(d[0]), "+f"(d[1]), "+f"(d[2]), "+f"(d[3]), "+f"(d[4]), "+f"(d[5]), "+f"(d[6]), "+f"(d[7]),
      "+f"(d[8]), "+f"(d[9]), "+f"(d[10]), "+f"(d[11]), "+f"(d[12]), "+f"(d[13]), "+f"(d[14]), "+f"(d[15]),
      "+f"(d[16]), "+f"(d[17]), "+f"(d[18]), "+f"(d[19]), "+f"(d[20]), "+f"(d[21]), "+f"(d[22]), "+f"(d[23]),
      "+f"(d[24]), "+f"(d[25]), "+f"(d[26]), "+f"(d[27]), "+f"(d[28]), "+f"(d[29]), "+f"(d[30]), "+f"(d[31]),
      "+f"(d[32]), "+f"(d[33]), "+f"(d[34]), "+f"(d[35]), "+f"(d[36]), "+f"(d[37]), "+f"(d[38]), "+f"(d[39]),
      "+f"(d[40]), "+f"(d[41]), "+f"(d[42]), "+f"(d[43]), "+f"(d[44]), "+f"(d[45]), "+f"(d[46]), "+f"(d[47]),
      "+f"(d[48]), "+f"(d[49]), "+f"(d[50]), "+f"(d[51]), "+f"(d[52]), "+f"(d[53]), "+f"(d[54]), "+f"(d[55]),
      "+f"(d[56]), "+f"(d[57]), "+f"(d[58]), "+f"(d[59]), "+f"(d[60]), "+f"(d[61]), "+f"(d[62]), "+f"(d[63]),
      "+f"(d[64]), "+f"(d[65]), "+f"(d[66]), "+f"(d[67]), "+f"(d[68]), "+f"(d[69]), "+f"(d[70]), "+f"(d[71]),
      "+f"(d[72]), "+f"(d[73]), "+f"(d[74]), "+f"(d[75]), "+f"(d[76]), "+f"(d[77]), "+f"(d[78]), "+f"(d[79]),
      "+f"(d[80]), "+f"(d[81]), "+f"(d[82]), "+f"(d[83]), "+f"(d[84]), "+f"(d[85]), "+f"(d[86]), "+f"(d[87]),
      "+f"(d[88]), "+f"(d[89]), "+f"(d[90]), "+f"(d[91]), "+f"(d[92]), "+f"(d[93]), "+f"(d[94]), "+f"(d[95])
    : "r"(da), "r"(db), "r"(scale_d), "n"(HA), "n"(HB));
}
template <uint32_t HA = 0x40000040u, uint32_t HB = 0x40000040u>
__device__ __forceinline__ void wg_ss192t_z(float* d, uint32_t da, uint32_t db) {
  asm volatile("{\n.reg .pred p;\n.reg .b64 dA, dB;\nmov.b64 dA, {%96, %98};\nmov.b64 dB, {%97, %99};\nsetp.ne.b32 p, 0, 0;\n"
    "wgmma.mma_async.sync.aligned.m64n192k16.f32.bf16.bf16 "
    "{%0, %1, %2, %3, %4, %5, %6, %7, %8, %9, %10, %11, %12, %13, %14, %15, "
    "%16, %17, %18, %19, %20, %21, %22, %23, %24, %25, %26, %27, %28, %29, %30, %31, "
    "%32, %33, %34, %35, %36, %37, %38, %39, %40, %41, %42, %43, %44, %45, %46, %47, "
    "%48, %49, %50, %51, %52, %53, %54, %55, %56, %57, %58, %59, %60, %61, %62, %63, "
    "%64, %65, %66, %67, %68, %69, %70, %71, %72, %73, %74, %75, %76, %77, %78, %79, "
    "%80, %81, %82, %83, %84, %85, %86, %87, %88, %89, %90, %91, %92, %93, %94, %95}, "
    "dA, dB, p, 1, 1, 0, 1;\n}\n"
    : "=f"(d[0]), "=f"(d[1]), "=f"(d[2]), "=f"(d[3]), "=f"(d[4]), "=f"(d[5]), "=f"(d[6]), "=f"(d[7]),
      "=f"(d[8]), "=f"(d[9]), "=f"(d[10]), "=f"(d[11]), "=f"(d[12]), "=f"(d[13]), "=f"(d[14]), "=f"(d[15]),
      "=f"(d[16]), "=f"(d[17]), "=f"(d[18]), "=f"(d[19]), "=f"(d[20]), "=f"(d[21]), "=f"(d[22]), "=f"(d[23]),
      "=f"(d[24]), "=f"(d[25]), "=f"(d[26]), "=f"(d[27]), "=f"(d[28]), "=f"(d[29]), "=f"(d[30]), "=f"(d[31]),
      "=f"(d[32]), "=f"(d[33]), "=f"(d[34]), "=f"(d[35]), "=f"(d[36]), "=f"(d[37]), "=f"(d[38]), "=f"(d[39]),
      "=f"(d[40]), "=f"(d[41]), "=f"(d[42]), "=f"(d[43]), "=f"(d[44]), "=f"(d[45]), "=f"(d[46]), "=f"(d[47]),
      "=f"(d[48]), "=f"(d[49]), "=f"(d[50]), "=f"(d[51]), "=f"(d[52]), "=f"(d[53]), "=f"(d[54]), "=f"(d[55]),
      "=f"(d[56]), "=f"(d[57]), "=f"(d[58]), "=f"(d[59]), "=f"(d[60]), "=f"(d[61]), "=f"(d[62]), "=f"(d[63]),
      "=f"(d[64]), "=f"(d[65]), "=f"(d[66]), "=f"(d[67]), "=f"(d[68]), "=f"(d[69]), "=f"(d[70]), "=f"(d[71]),
      "=f"(d[72]), "=f"(d[73]), "=f"(d[74]), "=f"(d[75]), "=f"(d[76]), "=f"(d[77]), "=f"(d[78]), "=f"(d[79]),
      "=f"(d[80]), "=f"(d[81]), "=f"(d[82]), "=f"(d[83]), "=f"(d[84]), "=f"(d[85]), "=f"(d[86]), "=f"(d[87]),
      "=f"(d[88]), "=f"(d[89]), "=f"(d[90]), "=f"(d[91]), "=f"(d[92]), "=f"(d[93]), "=f"(d[94]), "=f"(d[95])
    : "r"(da), "r"(db), "n"(HA), "n"(HB));
}
template <uint32_t HA = 0x40000040u, uint32_t HB = 0x40000040u>
__device__ __forceinline__ void wg_ss128t(float* d, uint32_t da, uint32_t db, int scale_d) {
  asm volatile("{\n.reg .pred p;\n.reg .b64 dA, dB;\nmov.b64 dA, {%64, %67};\nmov.b64 dB, {%65, %68};\nsetp.ne.b32 p, %66, 0;\n"
    "wgmma.mma_async.sync.aligned.m64n128k16.f32.bf16.bf16 "
    "{%0, %1, %2, %3, %4, %5, %6, %7, %8, %9, %10, %11, %12, %13, %14, %15, "
    "%16, %17, %18, %19, %20, %21, %22, %23, %24, %25, %26, %27, %28, %29, %30, %31, "
    "%32, %33, %34, %35, %36, %37, %38, %39, %40, %41, %42, %43, %44, %45, %46, %47, "
    "%48, %49, %50, %51, %52, %53, %54, %55, %56, %57, %58, %59, %60, %61, %62, %63}, "
    "dA, dB, p, 1, 1, 0, 1;\n}\n"
    : "+f"(d[0]), "+f"(d[1]), "+f"(d[2]), "+f"(d[3]), "+f"(d[4]), "+f"(d[5]), "+f"(d[6]), "+f"(d[7]),
      "+f"(d[8]), "+f"(d[9]), "+f"(d[10]), "+f"(d[11]), "+f"(d[12]), "+f"(d[13]), "+f"(d[14]), "+f"(d[15]),
      "+f"(d[16]), "+f"(d[17]), "+f"(d[18]), "+f"(d[19]), "+f"(d[20]), "+f"(d[21]), "+f"(d[22]), "+f"(d[23]),
      "+f"(d[24]), "+f"(d[25]), "+f"(d[26]), "+f"(d[27]), "+f"(d[28]), "+f"(d[29]), "+f"(d[30]), "+f"(d[31]),
      "+f"(d[32]), "+f"(d[33]), "+f"(d[34]), "+f"(d[35]), "+f"(d[36]), "+f"(d[37]), "+f"(d[38]), "+f"(d[39]),
      "+f"(d[40]), "+f"(d[41]), "+f"(d[42]), "+f"(d[43]), "+f"(d[44]), "+f"(d[45]), "+f"(d[46]), "+f"(d[47]),
      "+f"(d[48]), "+f"(d[49]), "+f"(d[50]), "+f"(d[51]), "+f"(d[52]), "+f"(d[53]), "+f"(d[54]), "+f"(d[55]),
      "+f"(d[56]), "+f"(d[57]), "+f"(d[58]), "+f"(d[59]), "+f"(d[60]), "+f"(d[61]), "+f"(d[62]), "+f"(d[63])
    : "r"(da), "r"(db), "r"(scale_d), "n"(HA), "n"(HB));
}
template <uint32_t HB = 0x40000040u>
__device__ __forceinline__ void wg_rs64(float* d, uint32_t a0, uint32_t a1, uint32_t a2, uint32_t a3, uint32_t db, int scale_d) {
  asm volatile("{\n.reg .pred p;\n.reg .b64 dB;\nmov.b64 dB, {%36, %38};\nsetp.ne.b32 p, %37, 0;\n"
    "wgmma.mma_async.sync.aligned.m64n64k16.f32.bf16.bf16 "
    "{%0, %1, %2, %3, %4, %5, %6, %7, %8, %9, %10, %11, %12, %13, %14, %15, "
    "%16, %17, %18, %19, %20, %21, %22, %23, %24, %25, %26, %27, %28, %29, %30, %31}, "
    "{%32, %33, %34, %35}, dB, p, 1, 1, 0;\n}\n"
    : "+f"(d[0]), "+f"(d[1]), "+f"(d[2]), "+f"(d[3]), "+f"(d[4]), "+f"(d[5]), "+f"(d[6]), "+f"(d[7]),
      "+f"(d[8]), "+f"(d[9]), "+f"(d[10]), "+f"(d[11]), "+f"(d[12]), "+f"(d[13]), "+f"(d[14]), "+f"(d[15]),
      "+f"(d[16]), "+f"(d[17]), "+f"(d[18]), "+f"(d[19]), "+f"(d[20]), "+f"(d[21]), "+f"(d[22]), "+f"(d[23]),
      "+f"(d[24]), "+f"(d[25]), "+f"(d[26]), "+f"(d[27]), "+f"(d[28]), "+f"(d[29]), "+f"(d[30]), "+f"(d[31])
    : "r"(a0), "r"(a1), "r"(a2), "r"(a3), "r"(db), "r"(scale_d), "n"(HB));
}
template <uint32_t HB = 0x40000040u>
__device__ __forceinline__ void wg_rs64_z(float* d, uint32_t a0, uint32_t a1, uint32_t a2, uint32_t a3, uint32_t db) {
  asm volatile("{\n.reg .pred p;\n.reg .b64 dB;\nmov.b64 dB, {%36, %37};\nsetp.ne.b32 p, 0, 0;\n"
    "wgmma.mma_async.sync.aligned.m64n64k16.f32.bf16.bf16 "
    "{%0, %1, %2, %3, %4, %5, %6, %7, %8, %9, %10, %11, %12, %13, %14, %15, "
    "%16, %17, %18, %19, %20, %21, %22, %23, %24, %25, %26, %27, %28, %29, %30, %31}, "
    "{%32, %33, %34, %35}, dB, p, 1, 1, 0;\n}\n"
    : "=f"(d[0]), "=f"(d[1]), "=f"(d[2]), "=f"(d[3]), "=f"(d[4]), "=f"(d[5]), "=f"(d[6]), "=f"(d[7]),
      "=f"(d[8]), "=f"(d[9]), "=f"(d[10]), "=f"(d[11]), "=f"(d[12]), "=f"(d[13]), "=f"(d[14]), "=f"(d[15]),
      "=f"(d[16]), "=f"(d[17]), "=f"(d[18]), "=f"(d[19]), "=f"(d[20]), "=f"(d[21]), "=f"(d[22]), "=f"(d[23]),
      "=f"(d[24]), "=f"(d[25]), "=f"(d[26]), "=f"(d[27]), "=f"(d[28]), "=f"(d[29]), "=f"(d[30]), "=f"(d[31])
    : "r"(a0), "r"(a1), "r"(a2), "r"(a3), "r"(db), "n"(HB));
}
template <uint32_t HB = 0x40000040u>
__device__ __forceinline__ void wg_rs32(float* d, uint32_t a0, uint32_t a1, uint32_t a2, uint32_t a3, uint32_t db, int scale_d) {
  asm volatile("{\n.reg .pred p;\n.reg .b64 dB;\nmov.b64 dB, {%20, %22};\nsetp.ne.b32 p, %21, 0;\n"
    "wgmma.mma_async.sync.aligned.m64n32k16.f32.bf16.bf16 "
    "{%0, %1, %2, %3, %4, %5, %6, %7, %8, %9, %10, %11, %12, %13, %14, %15}, "
    "{%16, %17, %18, %19}, dB, p, 1, 1, 0;\n}\n"
    : "+f"(d[0]), "+f"(d[1]), "+f"(d[2]), "+f"(d[3]), "+f"(d[4]), "+f"(d[5]), "+f"(d[6]), "+f"(d[7]),
      "+f"(d[8]), "+f"(d[9]), "+f"(d[10]), "+f"(d[11]), "+f"(d[12]), "+f"(d[13]), "+f"(d[14]), "+f"(d[15])
    : "r"(a0), "r"(a1), "r"(a2), "r"(a3), "r"(db), "r"(scale_d), "n"(HB));
}
template <uint32_t HB = 0x40000040u>
__device__ __forceinline__ void wg_rs32_z(float* d, uint32_t a0, uint32_t a1, uint32_t a2, uint32_t a3, uint32_t db) {
  asm volatile("{\n.reg .pred p;\n.reg .b64 dB;\nmov.b64 dB, {%20, %21};\nsetp.ne.b32 p, 0, 0;\n"
    "wgmma.mma_async.sync.aligned.m64n32k16.f32.bf16.bf16 "
    "{%0, %1, %2, %3, %4, %5, %6, %7, %8, %9, %10, %11, %12, %13, %14, %15}, "
    "{%16, %17, %18, %19}, dB, p, 1, 1, 0;\n}\n"
    : "=f"(d[0]), "=f"(d[1]), "=f"(d[2]), "=f"(d[3]), "=f"(d[4]), "=f"(d[5]), "=f"(d[6]), "=f"(d[7]),
      "=f"(d[8]), "=f"(d[9]), "=f"(d[10]), "=f"(d[11]), "=f"(d[12]), "=f"(d[13]), "=f"(d[14]), "=f"(d[15])
    : "r"(a0), "r"(a1), "r"(a2), "r"(a3), "r"(db), "n"(HB));
}
template <uint32_t HB = 0x40000040u>
__device__ __forceinline__ void wg_rs40t(float* d, uint32_t a0, uint32_t a1, uint32_t a2, uint32_t a3, uint32_t db, int scale_d) {
  asm volatile("{\n.reg .pred p;\n.reg .b64 dB;\nmov.b64 dB, {%24, %26};\nsetp.ne.b32 p, %25, 0;\n"
    "wgmma.mma_async.sync.aligned.m64n40k16.f32.bf16.bf16 "
    "{%0, %1, %2, %3, %4, %5, %6, %7, %8, %9, %10, %11, %12, %13, %14, %15, "
    "%16, %17, %18, %19}, "
    "{%20, %21, %22, %23}, dB, p, 1, 1, 1;\n}\n"
    : "+f"(d[0]), "+f"(d[1]), "+f"(d[2]), "+f"(d[3]), "+f"(d[4]), "+f"(d[5]), "+f"(d[6]), "+f"(d[7]),
      "+f"(d[8]), "+f"(d[9]), "+f"(d[10]), "+f"(d[11]), "+f"(d[12]), "+f"(d[13]), "+f"(d[14]), "+f"(d[15]),
      "+f"(d[16]), "+f"(d[17]), "+f"(d[18]), "+f"(d[19])
    : "r"(a0), "r"(a1), "r"(a2), "r"(a3), "r"(db), "r"(scale_d), "n"(HB));
}
template <uint32_t HB = 0x40000040u>
__device__ __forceinline__ void wg_rs40t_z(float* d, uint32_t a0, uint32_t a1, uint32_t a2, uint32_t a3, uint32_t db) {
  asm volatile("{\n.reg .pred p;\n.reg .b64 dB;\nmov.b64 dB, {%24, %25};\nsetp.ne.b32 p, 0, 0;\n"
    "wgmma.mma_async.sync.aligned.m64n40k16.f32.bf16.bf16 "
    "{%0, %1, %2, %3, %4, %5, %6, %7, %8, %9, %10, %11, %12, %13, %14, %15, "
    "%16, %17, %18, %19}, "
    "{%20, %21, %22, %23}, dB, p, 1, 1, 1;\n}\n"
    : "=f"(d[0]), "=f"(d[1]), "=f"(d[2]), "=f"(d[3]), "=f"(d[4]), "=f"(d[5]), "=f"(d[6]), "=f"(d[7]),
      "=f"(d[8]), "=f"(d[9]), "=f"(d[10]), "=f"(d[11]), "=f"(d[12]), "=f"(d[13]), "=f"(d[14]), "=f"(d[15]),
      "=f"(d[16]), "=f"(d[17]), "=f"(d[18]), "=f"(d[19])
    : "r"(a0), "r"(a1), "r"(a2), "r"(a3), "r"(db), "n"(HB));
}

constexpr uint32_t SOFF = 1024;
constexpr int STG = 57344, SL_W = 32768, SL_HD = 12288, SL_F = 3 * STG, X_ST = 131072;
__host__ __device__ constexpr int kv_off(int h, int b) { return 16384 + h * 81920 + (b ^ (6 * h)) * 8192; }
__host__ __device__ constexpr int qo_off(int h, int qb) { return (qb >> 1) * 81920 + h * 8192 + (qb & 1) * 4096; }
__host__ __device__ constexpr int wo_off(int st) { return 16384 + st * 32768 + (st >> 1) * 16384; }
constexpr int OFF_ONES = 4 * STG;
constexpr int OFF_PATCH = OFF_ONES + 1024;
constexpr int OFF_CS = OFF_PATCH + 768;
constexpr int OFF_BAR = OFF_CS + 768;
constexpr int OFF_MISC = OFF_BAR + 416;
constexpr int SMEM_BYTES = OFF_MISC + 96;
enum { B_FULL = 0, B_EMPTY = 6, B_HALO = 12, B_CS = 15, B_KVREADY, B_QDONE = B_KVREADY + 2, B_QREADY, B_OST, B_ADONE = B_OST + 2,
       B_QFREE, B_WS, B_WFULL, B_WEMPTY = B_WFULL + 4, B_GU = B_WEMPTY + 4, B_RES = B_GU + 2, B_DN,
       B_HX = B_DN + 2, B_RST, B_E23, B_UNIT, B_COUNT = B_UNIT + 8 };
static_assert(B_COUNT <= 52, "barrier area");
__host__ __device__ constexpr int bar_count(int i) {
  return i >= B_EMPTY && i < B_HALO ? 17 : i == B_CS ? 5 : i == B_QFREE ? 16
       : i == B_KVREADY || i == B_KVREADY + 1 || i == B_QREADY ? 8 : i == B_E23 ? 9 : i == B_ADONE ? 32 : i == B_OST ? 2 : i >= B_UNIT ? 4
       : i == B_QDONE || (i >= B_WEMPTY && i < B_GU) ? 16 : i == B_RST ? 4 : i == B_RES ? 2 : 1;
}
enum { M_KEY = 0, M_MEAN, M_INV, M_WSUM, M_TAG, M_SEL0, M_PMEAN, M_PINV, M_XQ = 8, M_KEYS = 12, M_PROG = 20 };
constexpr int FFN_PIECE = 14336;
constexpr int T_XS = 163840, T_HP = T_XS + 1024;
constexpr float LSUM_MIN = 5.421010862427522e-20f, LSUM_MAX = 1.8446744073709552e19f;
constexpr float SM_C = 0.17677669529663687f * 1.4426950408889634f;
constexpr uint32_t VSTEP = 64u - (64u << 16);
constexpr int DELAY_P = 600, DELAY_S = 2400, DELAY_Y = 400, P1_DELAY = 800, X_STAGGER = 500;
constexpr int GU_PACE = 2000, GU_PACE1 = 1700, GUB_PACE = 900, WS_PACE = 500;
constexpr int RES_K = 6;

struct Params {
  CUtensorMap mapA[2], mapW, mapWo, mapRes[2], mapXst[2], mapG, mapU, mapD, mapWs;
  const bf16 *w_r, *w_d;
  bf16* out;
  int role[128];
};

template <int N> __device__ __forceinline__ void exp_pack(const float* s, uint32_t* p) {
#pragma unroll
  for (int b = 0; b < N; b++) {
    p[2 * b] = pack_bf16(ex2(s[4 * b]), ex2(s[4 * b + 1]));
    p[2 * b + 1] = pack_bf16(ex2(s[4 * b + 2]), ex2(s[4 * b + 3]));
  }
}
template <int KIND> __device__ __forceinline__ void edge16(const float* sd, const float* st, uint32_t* pd, uint32_t* pt, int dl, uint32_t mt) {
  if (KIND == 0) { exp_pack<2>(sd, pd); pt[0] = pt[1] = pt[2] = pt[3] = 0; }
  else if (KIND == 1) { exp_pack<2>(st, pt); pd[0] = pd[1] = pd[2] = pd[3] = 0; }
  else {
    const uint32_t a = pack_bf16(ex2(dl >= 0 ? sd[0] : st[0]), ex2(dl >= 1 ? sd[1] : st[1]));
    const uint32_t c = pack_bf16(ex2(dl >= 0 ? sd[6] : st[6]), ex2(dl >= 1 ? sd[7] : st[7]));
    pd[0] = a & ~mt; pt[0] = a & mt; pd[3] = c & ~mt; pt[3] = c & mt;
    pd[1] = pack_bf16(ex2(sd[2]), ex2(sd[3])); pt[1] = 0;
    pt[2] = pack_bf16(ex2(st[4]), ex2(st[5])); pd[2] = 0;
  }
}
__device__ __forceinline__ void edge32(const float* sd, const float* st, uint32_t* pd, uint32_t* pt, int rel, int dl, uint32_t mt) {
  if (rel > 1) { edge16<0>(sd, st, pd, pt, dl, mt); edge16<0>(sd + 8, st + 8, pd + 4, pt + 4, dl, mt); }
  else if (rel == 1) { edge16<0>(sd, st, pd, pt, dl, mt); edge16<2>(sd + 8, st + 8, pd + 4, pt + 4, dl, mt); }
  else if (rel == 0) { edge16<2>(sd, st, pd, pt, dl, mt); edge16<1>(sd + 8, st + 8, pd + 4, pt + 4, dl, mt); }
  else { edge16<1>(sd, st, pd, pt, dl, mt); edge16<1>(sd + 8, st + 8, pd + 4, pt + 4, dl, mt); }
}
__device__ __forceinline__ void qk64(float* s, const uint32_t* qf, uint32_t kd) {
  wg_rs64_z<H64>(s, qf[0], qf[1], qf[2], qf[3], kd);
  wg_rs64<H64>(s, qf[4], qf[5], qf[6], qf[7], kd + 2, 1);
}
__device__ __forceinline__ void qk32x2(float* a, float* b, const uint32_t* qf, uint32_t ka, uint32_t kb) {
  wg_rs32_z<H64>(a, qf[0], qf[1], qf[2], qf[3], ka); wg_rs32_z<H64>(b, qf[0], qf[1], qf[2], qf[3], kb);
  wg_rs32<H64>(a, qf[4], qf[5], qf[6], qf[7], ka + 2, 1); wg_rs32<H64>(b, qf[4], qf[5], qf[6], qf[7], kb + 2, 1);
}
__device__ __forceinline__ void pv32(float* o, const uint32_t* p, uint32_t vd) {
  wg_rs40t<H64>(o, p[0], p[1], p[2], p[3], vd, 1);
  wg_rs40t<H64>(o, p[4], p[5], p[6], p[7], vd + VSTEP, 1);
}

__device__ __forceinline__ void fma8(float* d, uint4 w, float x) {
  d[0] += x * bf_lo(w.x); d[1] += x * bf_hi(w.x); d[2] += x * bf_lo(w.y); d[3] += x * bf_hi(w.y);
  d[4] += x * bf_lo(w.z); d[5] += x * bf_hi(w.z); d[6] += x * bf_lo(w.w); d[7] += x * bf_hi(w.w);
}

__device__ __forceinline__ int fresh_tid() { int r; asm volatile("mov.u32 %0, %%tid.x;" : "=r"(r)); return r; }
__device__ __forceinline__ int fresh_bid() { int r; asm volatile("mov.u32 %0, %%ctaid.x;" : "=r"(r)); return r; }
#define PHASE_IDS                                                                                                              \
  const uint32_t sbase = smem_u32(smem);                                                                                       \
  const int tid = fresh_tid(), bid = P.role[fresh_bid()];                                                                      \
  const int warp = __shfl_sync(0xffffffffu, tid >> 5, 0), lane = tid & 31;                                                     \
  const int rank = bid & 1, cl = bid >> 1, rb = bid & 7, hp = bid >> 3;                  \
  const int mb = 2 * rb + (hp >> 3), nb = hp & 7;                                            \
  const int wg = warp >> 2, wi = warp & 3, g = lane >> 2, q = lane & 3;                                                        \
  const int mi = lane >> 3, srow = wi * 16 + (mi & 1) * 8 + (lane & 7);      \
  auto bar = [&](int i) { return sbase + OFF_BAR + 8 * i; };                                                                   \
  volatile uint32_t* s_misc = (volatile uint32_t*)(smem + OFF_MISC);                                                           \
  auto load_w = [&](int s, int kt) {                           \
    mbar_expect_tx(bar(B_FULL + s), (s & 1) ? SL_HD : SL_HD + 32768);                        \
    tma_load3_mc(sbase + (s >> 1) * STG + SL_W + (s & 1) * SL_HD + rank * 6144, &P.mapW, hp * 64, kt * 32 + rank * 16, 0, bar(B_FULL + s));              \
  };                                                                                                                           \
  auto load_a = [&](int s, int kt, int layer) { tma_load2(sbase + (s >> 1) * STG, &P.mapA[layer], kt * 32, rb * 256, bar(B_FULL + s)); }; \
  auto load_wo = [&](int k) {                                                 \
    mbar_expect_tx(bar(B_WFULL + (k & 3)), 32768);                                                                             \
    tma_load3_mc(sbase + wo_off(k & 3) + 16384 + rank * 8192, &P.mapWo, nb * 128 + rank * 64, (k >> 3) * 32, (k & 7) * 2, bar(B_WFULL + (k & 3))); \
  };                                                                                                                           \
  auto load_o = [&](int k) {                                                            \
    bulk_load_h(sbase + wo_off(k & 3), g_o + (size_t)(mb * 16 + k) * 16384, 16384, bar(B_WFULL + (k & 3)), policy_evict_first());                    \
  };                                                                                                                           \
  auto load_res = [&](int half, int layer) {      \
    mbar_expect_tx(bar(B_RES), 16384);                                                                                         \
    tma_load2_h(sbase + qo_off(half, 0), &P.mapRes[layer], nb * 128 + half * 64, mb * 128, bar(B_RES), policy_evict_first());  \
    tma_load2_h(sbase + qo_off(half, 2), &P.mapRes[layer], nb * 128 + half * 64, mb * 128 + 64, bar(B_RES), policy_evict_first()); \
  };                                                                                                                           \
  auto store_tile = [&](int layer, int skip, bool wait) {                                           \
    _Pragma("unroll 1")                                                                                                        \
    for (int j = 0; j < 4; j++)                                                                                                \
      if ((j & 1) != skip) tma_store(&P.mapXst[layer], sbase + X_ST + (j & 1) * 16384 + (j >> 1) * 8192, nb * 128 + (j >> 1) * 64, mb * 128 + (j & 1) * 64); \
    bulk_commit();                                                                                                             \
    if (wait) bulk_wait_all();                                                                                                 \
  };                                                                                                                           \
  auto load_ws = [&](int pace) {                                    \
    mbar_expect_tx(bar(B_WS), 4 * SL_HD);                                                                                      \
    _Pragma("unroll 1")                                                                                                        \
    for (int j = 0; j < 4; j++) {                                                                                              \
      tma_load3(sbase + SL_F + j * SL_HD, &P.mapWs, hp * 64, rb * 128 + j * 32, 0, bar(B_WS));                                 \
      if (pace) spin_cycles(pace);                                                                                             \
    }                                                                                                                          \
  };                                                                                                                           \
  auto load_gu = [&](int half, int pace) {                             \
    mbar_expect_tx(bar(B_GU + half), 4 * FFN_PIECE);                                                                           \
    _Pragma("unroll 1")                                                                                                        \
    for (int j = 0; j < 4; j++) {                                                                                              \
      tma_load2_h(sbase + SL_F + j * FFN_PIECE, &P.mapG + (j >> 1), cl * 56, rank * 512 + half * 256 + (j & 1) * 128, bar(B_GU + half), policy_evict_first()); \
      if (j < 3) spin_cycles(pace);                                                                                            \
    }                                                                                                                          \
  };                                                                                                                           \
  auto fetch_gu = [&](uint32_t* a, int ks, int ct) {                 \
    ldsm_x4_t(sbase + SL_F + (mi & 1) * 2 * FFN_PIECE + (ks * 16 + (mi >> 1) * 8 + (lane & 7)) * 112 + ct * 16, a[0], a[1], a[2], a[3]); \
  };                                                                                                                           \
  auto send_gu = [&](float gate, float up, int ct, int part) {        \
    const int u = 8 * ct + g, own = u >= 28;                                                                                   \
    if (q == 0) st_async2(mapa(sbase + T_HP + ((rank * 5 + part) * 28 + u - 28 * own) * 8, own), gate, up, mapa(bar(B_HX), own)); \
  };                                                                                                                           \
  auto hidden = [&]() {                                     \
    const float2* hpart = (const float2*)(smem + T_HP) + min(lane, 27);                                                        \
    float gs[2] = {0.f, 0.f}, us[2] = {0.f, 0.f};                                                                              \
    _Pragma("unroll")                                                                                                          \
    for (int j = 0; j < 10; j++) { const float2 v = hpart[j * 28]; gs[j & 1] += v.x; us[j & 1] += v.y; }                       \
    const float gb = rbf(gs[0] + gs[1]), ub = rbf(us[0] + us[1]);                                                              \
    return lane < 28 ? rbf(__fdividef(gb, 1.f + __expf(-gb))) * ub : 0.f;                                                      \
  };                                                                                                                           \
  (void)load_wo; (void)load_o; (void)load_res; (void)store_tile; (void)fetch_gu; (void)load_ws; (void)load_gu; (void)send_gu; (void)hidden; (void)cl; (void)mb; (void)nb; (void)wg; (void)g; (void)q; (void)srow; (void)s_misc; (void)load_w; (void)load_a;

__global__ void __launch_bounds__(512, 1) mega_kernel(const __grid_constant__ Params P) {
  extern __shared__ __align__(1024) uint8_t smem[];
  {
    PHASE_IDS
    if (warp == 0) {
      if (lane == 0) {
        prefetch_tmap(&P.mapA[0]); prefetch_tmap(&P.mapW);
#pragma unroll
        for (int i = 0; i < 6; i++) mbar_init(bar(B_FULL + i), 1);
        asm volatile("fence.mbarrier_init.release.cluster;" ::: "memory");
      }
      __syncwarp();
      mbar_expect_tx(bar(B_FULL), SL_HD + 32768);
      tma_load3(sbase + SL_W, &P.mapW, hp * 64, 0, 0, bar(B_FULL));
      tma_load3(sbase + SL_W + 6144, &P.mapW, hp * 64, 16, 0, bar(B_FULL));
      load_a(0, 0, 0);
    } else if (tid == 32) {
#pragma unroll
      for (int i = 6; i < B_COUNT; i++) mbar_init(bar(i), bar_count(i));
      asm volatile("fence.mbarrier_init.release.cluster;" ::: "memory");
    } else if (warp == 8) {
      ((uint4*)(smem + OFF_ONES))[lane] = make_uint4(0x3F803F80u, 0x3F803F80u, 0x3F803F80u, 0x3F803F80u);
      ((uint4*)(smem + OFF_ONES))[lane + 32] = make_uint4(0x3F803F80u, 0x3F803F80u, 0x3F803F80u, 0x3F803F80u);
    }
    __syncwarp();
    cluster_arrive(); cluster_wait();
    if (warp == 0) {
      PROFL(0, 1);
      load_w(1, 1);
    } else if (tid == 96) {
      if ((sbase & 0x3FFFF) != SOFF) __trap();
    }
    __syncwarp();
  }

  regs_dec<120>();
#pragma unroll 1
  for (unsigned pass_v = 0;;) {
    const unsigned pass = __shfl_sync(0xffffffffu, pass_v, 0);
    if (__shfl_sync(0xffffffffu, fresh_tid() >> 8, 0)) {
      if (pass > 0) {
        const unsigned layer = pass - 1;
        uint32_t xr[32];
        {
          PHASE_IDS
          float acc[64];
#pragma unroll
          for (int i = 0; i < 64; i++) acc[i] = 0.f;
          const uint32_t da0 = dlo(SOFF, 16) + (wg - 2) * 256;
          constexpr uint32_t db0 = dlo(SOFF + 16384, 8192);
#pragma unroll 1
          for (int k4 = 0; k4 < 4; k4++) {
#pragma unroll
            for (int st = 0; st < 4; st++) {
              mbar_wait(bar(B_WFULL + st), k4 & 1);
              wg_fence();
#pragma unroll
              for (int kk = 0; kk < 4; kk++)
                wg_ss128t<H64, H128>(acc, da0 + (wo_off(st) >> 4) + (kk >> 1) * 512 + (kk & 1) * 2, db0 + (wo_off(st) >> 4) + kk * 128, 1);
              wg_commit();
              if (st == 0 && k4 == 0 && warp == 9) PROF(10);
              if (warp == 9) STEPT(16 + k4 * 4 + st);
              wg_wait<1>();
              if (lane < 2 && (st == 0 ? k4 > 0 : (st < 3 || k4 < 3))) mbar_arrive_cluster(bar(B_WEMPTY + ((st + 3) & 3)), lane);
            }
          }
          mbar_wait(bar(B_RES), layer);
          mbar_wait(bar(B_RST), layer);
          const uint32_t zoff = qo_off(0, (wg - 2) * 2);
#pragma unroll
          for (int j = 0; j < 8; j++)
            ldsm_x4(sbase + zoff + srow * 128 + (j >> 2) * 8192 + ((((2 * j + (mi >> 1)) & 7) ^ (srow & 7)) << 4), xr[4 * j], xr[4 * j + 1], xr[4 * j + 2], xr[4 * j + 3]);
          wg_wait<0>();
          fence_regs<64>(acc);
          if (warp == 9) PROF(11);
#pragma unroll
          for (int j = 0; j < 32; j++) xr[j] = hadd_bf2(xr[j], pack_bf16(acc[2 * j], acc[2 * j + 1]));
        }
        PHASE_IDS
        const uint32_t tag = s_misc[M_TAG];
        const int grow = mb * 128 + (warp - 8) * 16 + g;
        {
          float d[6][4];
#pragma unroll
          for (int i = 0; i < 6; i++) d[i][0] = d[i][1] = d[i][2] = d[i][3] = 0.f;
          const uint4* tab = (const uint4*)(smem + OFF_PATCH + (g == 1 ? q * 64 : (g == 0 ? 256 : 320)));
#pragma unroll
          for (int j2 = 0; j2 < 4; j2++) {
            const uint4 w = tab[j2];
#pragma unroll
            for (int jj = 0; jj < 2; jj++) {
              const uint32_t* a = &xr[8 * j2 + 4 * jj];
              mma_16816(d[jj], a[0], a[1], a[2], a[3], jj ? w.z : w.x, jj ? w.w : w.y);
              mma_16816(d[2 + jj], a[0], a[1], a[2], a[3], a[0], a[2]);
              mma_16816(d[4 + jj], a[0], a[1], a[2], a[3], a[1], a[3]);
            }
          }
          const float sq0 = __shfl_sync(0xffffffffu, (g & 1) ? d[2][1] + d[3][1] : d[2][0] + d[3][0], g * 4 + (g >> 1));
          const float sq1 = __shfl_sync(0xffffffffu, (g & 1) ? d[4][3] + d[5][3] : d[4][2] + d[5][2], g * 4 + (g >> 1));
          uint4* dst = &g_part[layer][nb * SEQ + grow];
          if (q == 0) {
            st_relaxed4(dst, make_uint4(__float_as_uint(d[0][0] + d[1][0]), __float_as_uint(sq0), __float_as_uint(d[0][1] + d[1][1]), tag));
            st_relaxed4(dst + 8, make_uint4(__float_as_uint(d[0][2] + d[1][2]), __float_as_uint(sq1), __float_as_uint(d[0][3] + d[1][3]), tag));
          }
        }
        if (warp == 9) PROF(12);
        if (layer == 0 && lane < 2) mbar_arrive_cluster(bar(B_QFREE), lane);
        asm volatile("bar.arrive 6, 320;" ::: "memory");
        const int t_p = (int)clock();
        const uint32_t zrow = sbase + X_ST + (wg - 2) * 16384 + srow * 128;
        named_bar(5, 256);
#pragma unroll
        for (int j = 0; j < 8; j++)
          stsm_x4(zrow + (j >> 2) * 8192 + ((((2 * j + (mi >> 1)) & 7) ^ (srow & 7)) << 4), xr[4 * j], xr[4 * j + 1], xr[4 * j + 2], xr[4 * j + 3]);
        if (layer == 0) {
          fence_async_smem();
          asm volatile("bar.arrive 8, 288;" ::: "memory");
        }
#pragma unroll 1
        while ((int)clock() - t_p < DELAY_P) {}
        {
          const uint4* src = &g_part[layer][2 * q * SEQ + grow];
          uint4 pp[4];
          uint32_t spins = 0;
#pragma unroll 1
          do {
            pp[0] = ld_relaxed4(src); pp[1] = ld_relaxed4(src + SEQ); pp[2] = ld_relaxed4(src + 8); pp[3] = ld_relaxed4(src + SEQ + 8);
          } while (!__all_sync(0xffffffffu, pp[0].w == tag && pp[1].w == tag && pp[2].w == tag && pp[3].w == tag) && ++spins < SPIN_LIMIT);
          if (warp == 9) PROF(13);
          const int rr = q >> 1;
          float s3[3];
#pragma unroll
          for (int c = 0; c < 3; c++) {
            const float lo = __uint_as_float(c == 0 ? pp[0].x : c == 1 ? pp[0].y : pp[0].z) + __uint_as_float(c == 0 ? pp[1].x : c == 1 ? pp[1].y : pp[1].z);
            const float hi = __uint_as_float(c == 0 ? pp[2].x : c == 1 ? pp[2].y : pp[2].z) + __uint_as_float(c == 0 ? pp[3].x : c == 1 ? pp[3].y : pp[3].z);
            s3[c] = (rr ? hi : lo) + __shfl_xor_sync(0xffffffffu, rr ? lo : hi, 2);
            s3[c] += __shfl_xor_sync(0xffffffffu, s3[c], 1);
          }
          const float mu = s3[0] * (1.f / DM), var = fmaxf(fmaf(-mu, mu, s3[1] * (1.f / DM)), 0.f);
          const float mn = rbf(mu), iv = ln_inv(var);
          const uint32_t ky = router_key(rbf((s3[2] - mn * __uint_as_float(s_misc[M_WSUM])) * iv), grow + 8 * rr);
          const uint32_t wbest = __reduce_max_sync(0xffffffffu, ky);
          s_misc[M_KEYS + warp - 8] = wbest;
          named_bar(5, 256);
          if (__reduce_max_sync(0xffffffffu, s_misc[M_KEYS + (lane & 7)]) == wbest) {
            if (nb == 0 && ky == wbest && (q & 1) == 0) st_relaxed4(&g_slot[layer][mb * 8], make_uint4(ky, __float_as_uint(mn), __float_as_uint(iv), tag));
            const int r = ~wbest & 15;
            if ((r & 7) == g) {
#pragma unroll
              for (int j = 0; j < 4; j++) {
                const uint32_t* a = &xr[8 * j];
                st_relaxed4(&g_cand[layer][mb * 128 + nb * 16 + q * 4 + j],
                            r < 8 ? make_uint4(a[0], a[2], a[4], a[6]) : make_uint4(a[1], a[3], a[5], a[7]));
              }
            }
            __syncwarp();
          }
          if (warp == 9) PROF(14);
          if (layer == 0) {
            if ((q & 1) == 0) {
              g_rowln[nb][grow + 8 * rr] = make_float2(mn, iv);
              if (warp - 8 == nb) {
                const float mu2 = mu + (mu - mn) * iv, inv2 = ln_inv(var * (1.f + iv) * (1.f + iv));
                st_relaxed4(&g_rowab[1][grow + 8 * rr], make_uint4(__float_as_uint((1.f + iv) * inv2), __float_as_uint((mn * iv + rbf(mu2)) * inv2), tag, 0));
              }
            }
            __syncwarp();
          } else {
            const uint32_t m2 = pack_bf16(mn, mn);
            uint8_t* row = smem + X_ST + (wg - 2) * 16384 + (q & 1) * 8192 + (wi * 16 + g + 8 * rr) * 128;
#pragma unroll 2
            for (int j = 0; j < 8; j++) {
              uint4* c = (uint4*)(row + (((j + lane) & 7) << 4));
              const uint4 v = *c;
              *c = make_uint4(add_ln_pair(v.x, m2, iv), add_ln_pair(v.y, m2, iv), add_ln_pair(v.z, m2, iv), add_ln_pair(v.w, m2, iv));
            }
            fence_async_smem();
          }
          if (warp == 15) asm volatile("bar.arrive 7, 512;" ::: "memory");
        }
        if (warp < 15) {
          uint32_t gu[64];
          mbar_wait(bar(B_GU + 1), layer);
#pragma unroll
          for (int j = 0; j < 16; j++) fetch_gu(gu + 4 * j, j, warp - 8);
          fence_async_smem();
          float d[4][4] = {};
          named_bar(7, 512);
#pragma unroll
          for (int hf = 0; hf < 2; hf++) {
            uint4 xv[4] = {};
            if (g == 0) {
#pragma unroll
              for (int j = 0; j < 4; j++) xv[j] = ((const uint4*)(smem + T_XS))[32 + hf * 16 + j * 4 + q];
            }
            __syncwarp();
#pragma unroll
            for (int j = 0; j < 4; j++) {
              const uint32_t* a = gu + hf * 32 + j * 8;
              mma_16816(d[(j & 1) * 2], a[0], a[1], a[2], a[3], xv[j].x, xv[j].y);
              mma_16816(d[(j & 1) * 2 + 1], a[4], a[5], a[6], a[7], xv[j].z, xv[j].w);
            }
          }
          send_gu((d[0][0] + d[1][0]) + (d[2][0] + d[3][0]), (d[0][2] + d[1][2]) + (d[2][2] + d[3][2]), warp - 8, 4);
          __syncwarp();
        }
        if (layer == 0) asm volatile("bar.arrive 9, 512;" ::: "memory");
        else {
        uint32_t wd[64];
        mbar_wait(bar(B_DN), layer);
#pragma unroll
        for (int j = 0; j < 16; j++) {
          const uint32_t row = sbase + wo_off(0) + ((warp - 8) * 2 + (j >> 3)) * 3584 + min((j & 1) * 16 + (mi >> 1) * 8 + (lane & 7), 27) * 128;
          ldsm_x4_t(row + ((((j & 6) + (mi & 1)) ^ ((row >> 7) & 7)) << 4), wd[4 * j], wd[4 * j + 1], wd[4 * j + 2], wd[4 * j + 3]);
        }
        fence_regs_u<64>(wd);
        uint32_t hf[4];
        named_bar(10, 288);
        *(uint4*)hf = *(const uint4*)(smem + OFF_PATCH + 256 + q * 16);
        if (warp == 9) PROF(19);
        float y[4][4] = {};
#pragma unroll
        for (int j = 0; j < 16; j++)
          mma_16816(y[j & 3], wd[4 * j], wd[4 * j + 1], wd[4 * j + 2], wd[4 * j + 3], g == j >> 1 ? hf[(j & 1) * 2] : 0u, g == j >> 1 ? hf[(j & 1) * 2 + 1] : 0u);
        {
          float e[4];
#pragma unroll
          for (int c = 0; c < 4; c++) { const int i = (c & 1) * 2 + (c >> 1); e[c] = (y[0][i] + y[1][i]) + (y[2][i] + y[3][i]); }
          const bool b0 = g & 1, b1 = g & 2;
          float t0 = __shfl_xor_sync(0xffffffffu, b0 ? e[0] : e[1], 4), t1 = __shfl_xor_sync(0xffffffffu, b0 ? e[2] : e[3], 4);
          const float f0 = b0 ? t0 : e[0], f1 = b0 ? e[1] : t0, f2 = b0 ? t1 : e[2], f3 = b0 ? e[3] : t1;
          t0 = __shfl_xor_sync(0xffffffffu, b1 ? f0 : f2, 8); t1 = __shfl_xor_sync(0xffffffffu, b1 ? f1 : f3, 8);
          st_relaxed4(&g_ypart[layer][bid * 256 + (warp - 8) * 32 + (q * 4 + (g & 3)) * 2 + (g >> 2)],
                      b1 ? make_uint4(__float_as_uint(t0), __float_as_uint(t1), __float_as_uint(f2), __float_as_uint(f3)) : make_uint4(__float_as_uint(f0), __float_as_uint(f1), __float_as_uint(t0), __float_as_uint(t1)));
        }
        if (warp == 9) PROF(20);
        asm volatile("bar.arrive 9, 384;" ::: "memory");
        cluster_arrive(); cluster_wait();
        return;
        }
      }
      const unsigned layer = pass;
      named_bar(1 + (fresh_tid() >> 7), 128);
      regs_inc<224>();
      float acc[2][96];
      float pa[2][2], pb[2][2];
      {
        PHASE_IDS
        const uint32_t da0 = dlo(SOFF, 16) + (wg - 2) * 512;
        constexpr uint32_t db0 = dlo(SOFF + SL_W, 2048);
        if (warp == 9) PROF(19 - 2 * layer);
        mbar_wait(bar(B_FULL), 0);
        if (warp == 9) PROF(29);
        if (warp == 9) STEPT(0);
        wg_fence();
        wg_ss192t_z(acc[0], da0, db0); wg_ss192t_z(acc[1], da0 + 1024, db0);
        wg_ss192t(acc[0], da0 + 2, db0 + 384, 1); wg_ss192t(acc[1], da0 + 1026, db0 + 384, 1);
        wg_commit();
        int s = 1, u = 0;
#pragma unroll 1
        for (int i = 1; i < 28; i++) {
          const uint32_t da = da0 + (s >> 1) * (STG >> 4) + (s & 1) * 4, db = db0 + (s >> 1) * (STG >> 4) + (s & 1) * (SL_HD >> 4);
          mbar_wait(bar(B_FULL + s), (u + (s > 1 ? layer : 0)) & 1);
          if (warp == 9 && !(i & 1)) STEPT(i >> 1);
          wg_fence();
          wg_ss192t(acc[0], da, db, 1); wg_ss192t(acc[1], da + 1024, db, 1);
          wg_ss192t(acc[0], da + 2, db + 384, 1); wg_ss192t(acc[1], da + 1026, db + 384, 1);
          wg_commit();
          wg_wait<1>();
          if (lane < 2 && i < 27) mbar_arrive_cluster(bar(B_EMPTY + (s == 0 ? 5 : s - 1)), lane);
          if (++s == 6) { s = 0; u++; }
        }
      }
      PHASE_IDS
      auto last_tile = [&](int m, int j) {
        const int e = (4 + j) % 6;
        const uint32_t da = dlo(SOFF + (e >> 1) * STG + (e & 1) * 64, 16) + (wg - 2) * 512 + m * 1024, db = dlo(SOFF + (e >> 1) * STG + SL_W + (e & 1) * SL_HD, 2048);
        wg_fence();
        wg_ss192t(acc[m], da, db, 1);
        wg_ss192t(acc[m], da + 2, db + 384, 1);
      };
      {
        if (layer == 0) mbar_wait(bar(B_CS), 0);
        const uint32_t tag = s_misc[M_TAG];
        const uint4* src = &g_rowab[layer][rb * 256 + (wg - 2 + (lane >> 4) * 2) * 64 + wi * 16 + (lane & 15)];
        uint4 v;
#pragma unroll
        for (int j = 0; j < 4; j++) {
          if (j == 2) v = ld_relaxed4(src);
          mbar_wait(bar(B_FULL + (4 + j) % 6), j < 2 ? layer : 1);
          last_tile(1, j);
          if (j == 0) { wg_commit(); wg_wait<1>(); mbar_arrive_e(bar(B_E23)); }
        }
        wg_commit();
        last_tile(0, 0);
        wg_commit();
        if (warp != 9) STEPT(4);
#pragma unroll 1
        for (uint32_t spins = 0; !__all_sync(0xffffffffu, v.z == tag) && spins < SPIN_LIMIT; spins++) v = ld_relaxed4(src);
#pragma unroll
        for (int j = 0; j < 4; j++) {
          pa[j >> 1][j & 1] = __uint_as_float(__shfl_sync(0xffffffffu, v.x, g + 8 * j));
          pb[j >> 1][j & 1] = __uint_as_float(__shfl_sync(0xffffffffu, v.y, g + 8 * j));
        }
        if (warp != 9) STEPT(5);
      }
      const int prow = (int)s_misc[M_SEL0] - rb * 256;
      const float4* cs = (const float4*)(smem + OFF_CS) + q;
      auto finish = [&](int m, int b, float2 c, uint32_t* dst) {
        dst[0] = pack_bf16(acc[m][4 * b] * pa[m][0] - c.x * pb[m][0], acc[m][4 * b + 1] * pa[m][0] - c.y * pb[m][0]);
        dst[1] = pack_bf16(acc[m][4 * b + 2] * pa[m][1] - c.x * pb[m][1], acc[m][4 * b + 3] * pa[m][1] - c.y * pb[m][1]);
      };
      auto grp = [](int n) { return n < 8 ? 4 + ((n >> 1) & 1) * 4 + (n >> 2) * 2 + (n & 1) : n - 8; };
      float4 cq[2] = {cs[grp(0) * 4], cs[grp(1) * 4]};
      auto next = [&](int m, int n, uint32_t* r) {
        if (m == 1 && n % 4 == 0) { last_tile(0, 1 + n / 4); wg_commit(); }
        const float4 c = cq[n & 1];
        cq[n & 1] = cs[grp((n + 2) % 12) * 4];
        finish(m, 2 * grp(n), make_float2(c.x, c.y), r); finish(m, 2 * grp(n) + 1, make_float2(c.z, c.w), r + 2);
      };
#pragma unroll
      for (int m = 1; m >= 0; m--) {
        if (m == 1) {
          wg_wait<1>();
          fence_regs<96>(acc[1]);
          mbar_wait(bar(B_E23), layer);
          if (warp != 9) STEPT(0);
        } else {
          wg_wait<0>();
          fence_regs<96>(acc[0]);
          if (warp != 9) STEPT(1);
          if (lane < 2) mbar_arrive_cluster(bar(B_QDONE), lane);
          if (warp == 9) PROF(2);
        }
        const int qb = wg - 2 + 2 * m;
        const bool patch = prow >> 4 == qb * 4 + wi;
#pragma unroll
        for (int jj = 0; jj < 8; jj++) {
          const int h = jj >> 2;
          uint32_t r[4];
          next(m, jj, r);
          if (m == 0 && jj == 0) named_bar(5, 256);
          stsm_x4(sbase + kv_off(h, 4 + 2 * m) + (wg - 2) * 8192 + ((jj >> 1) & 1) * 4096 + srow * 64 + ((((jj & 1) * 2 + (mi >> 1)) ^ ((srow >> 1) & 3)) << 4),
                  r[0], r[1], r[2], r[3]);
        }
        if (patch) {
          mbar_wait(bar(B_CS), 1);
          __syncwarp();
          if (lane < 16)
            *(uint4*)(smem + kv_off(g >> 1, 4 + qb) + (g & 1) * 4096 + (prow & 63) * 64 + ((q ^ ((prow >> 1) & 3)) << 4)) =
                *(const uint4*)(smem + OFF_PATCH + 128 + (g & 1) * 128 + (g >> 1) * 64 + q * 16);
        }
        fence_async_smem();
        __syncwarp();
        mbar_arrive_e(bar(B_KVREADY + 1 - m));
        if (warp != 9) STEPT(3 - m);
        pa[m][0] *= SM_C; pa[m][1] *= SM_C; pb[m][0] *= SM_C; pb[m][1] *= SM_C;
#pragma unroll
        for (int jj = 0; jj < 4; jj++) {
          uint32_t r[4];
          next(m, 8 + jj, r);
          *(uint4*)(smem + qo_off(jj >> 1, 2 * m) + (warp - 8) * 1024 + (jj & 1) * 512 + lane * 16) = make_uint4(r[0], r[1], r[2], r[3]);
        }
        __syncwarp();
        if (patch) {
          *(uint32_t*)(smem + qo_off(lane >> 4, 2 * m) + (warp - 8) * 1024 + (mi & 1) * 512 + ((prow & 7) * 4 + q) * 16 + ((g & 1) * 2 + ((prow >> 3) & 1)) * 4) =
              *(const uint32_t*)(smem + OFF_PATCH + lane * 4);
          __syncwarp();
        }
      }
      if (warp == 9) PROF(3);
      mbar_arrive_e(bar(B_QREADY));
      regs_dec<120>();
    } else {
      if (pass > 0) {
        const unsigned layer = pass - 1;
        PHASE_IDS
        const uint32_t tag = s_misc[M_TAG];
        if (warp == 7) {
              uint32_t* tab = (uint32_t*)(smem + OFF_PATCH);
#pragma unroll
              for (int j = 0; j < 2; j++) { const int w = lane + 32 * j; tab[(w & 3) * 16 + (w >> 2)] = ((const uint32_t*)P.w_r)[nb * 64 + w]; }
              tab[64 + lane] = lane < 16 ? 0x3F803F80u : 0u;
              float tot = 0.f;
#pragma unroll 1
              for (int j = 0; j < 4; j++) {
                const uint4 u = ((const uint4*)P.w_r)[lane + 32 * j];
                tot += bf_lo(u.x) + bf_hi(u.x) + bf_lo(u.y) + bf_hi(u.y) + bf_lo(u.z) + bf_hi(u.z) + bf_lo(u.w) + bf_hi(u.w);
              }
              s_misc[M_WSUM] = __float_as_uint(warp_sum(tot));
        }
              if (layer == 1) {
                const float2 ln = g_rowln[nb][mb * 128 + tid - 128];
                const uint32_t m2 = pack_bf16(ln.x, ln.x);
                uint8_t* row = smem + qo_off(0, wi & 2) + (tid & 63) * 128;
                mbar_wait(bar(B_RES), 1);
#pragma unroll 1
                for (int j = 0; j < 8; j++) {
                  uint4* c = (uint4*)(row + (((j + lane) & 7) << 4));
                  const uint4 v = c[0], w = c[512];
                  c[0] = make_uint4(add_ln_pair(v.x, m2, ln.y), add_ln_pair(v.y, m2, ln.y), add_ln_pair(v.z, m2, ln.y), add_ln_pair(v.w, m2, ln.y));
                  c[512] = make_uint4(add_ln_pair(w.x, m2, ln.y), add_ln_pair(w.y, m2, ln.y), add_ln_pair(w.z, m2, ln.y), add_ln_pair(w.w, m2, ln.y));
                }
                const int prow = (int)s_misc[M_SEL0] - mb * 128;
                __syncwarp();
                if (prow >> 5 == wi && lane < 16)
                  *(uint4*)(smem + qo_off(0, wi & 2) + (lane >> 3) * 8192 + (prow & 63) * 128 + (((lane ^ prow) & 7) << 4)) = poll4(&g_x2row[(nb * 16 + lane) * 2]);
                PROF(30);
              }
              __syncwarp();
              mbar_arrive_e(bar(B_RST));
        if (warp == 4) {
            named_bar(6, 320);
            spin_cycles(DELAY_S);
            uint4 c, u0, u1;
            uint32_t u2, best = 0, spins = 0;
            int src;
#pragma unroll 1
            for (;;) {
              src = (~best & 0x7FFu) >> 7;
              const uint4* xsel = &g_cand[layer][src * 128];
              c = ld_relaxed4(&g_slot[layer][(lane & 15) * 8]);
              u0 = ld_relaxed4(xsel + rank * 64 + lane); u1 = ld_relaxed4(xsel + rank * 64 + 32 + lane);
              u2 = ld_relaxed((const uint32_t*)(xsel + (bid >> 4) * 16 + q * 4) + (bid & 15));
              const uint32_t prev = best;
              best = __reduce_max_sync(0xffffffffu, c.w == tag ? c.x : 0u);
              if ((__all_sync(0xffffffffu, c.w == tag && valid4(u0) && valid4(u1) && u2 != SENT) && best == prev) || ++spins > SPIN_LIMIT) break;
            }
            const float sel_m = __uint_as_float(__shfl_sync(0xffffffffu, c.y, src)), sel_inv = __uint_as_float(__shfl_sync(0xffffffffu, c.z, src));
            const uint32_t m2 = pack_bf16(sel_m, sel_m);
            uint4* xs = (uint4*)(smem + T_XS) + (lane & 16) + q * 4 + (g & 3);
            xs[0] = make_uint4(ln_pair(u0.x, m2, sel_inv), ln_pair(u0.y, m2, sel_inv), ln_pair(u0.z, m2, sel_inv), ln_pair(u0.w, m2, sel_inv));
            xs[32] = make_uint4(ln_pair(u1.x, m2, sel_inv), ln_pair(u1.y, m2, sel_inv), ln_pair(u1.z, m2, sel_inv), ln_pair(u1.w, m2, sel_inv));
            s_misc[M_KEY] = best; s_misc[M_MEAN] = __float_as_uint(sel_m); s_misc[M_INV] = __float_as_uint(sel_inv);
            s_misc[M_XQ + q] = u2;
            if (layer == 0) s_misc[M_SEL0] = ~best & 0x7FFu;
            PROF(16);
        }
        if (layer == 1) {
          named_bar(7, 512);
          const int sel = SEQ - 1 - (int)(s_misc[M_KEY] & 0x7FFFu), skip = sel >> 7 == mb ? (sel >> 6) & 1 : -1;
          if (warp == 7) store_tile(1, skip, false);
          if (warp == 4) {
            mbar_wait_cluster(bar(B_HX), 1);
            ((bf16*)(smem + OFF_PATCH + 256))[((lane >> 1) & 3) * 8 + (lane >> 3) * 2 + (lane & 1)] = __float2bfloat16_rn(hidden());
            asm volatile("bar.arrive 10, 288;" ::: "memory");
          }
#pragma unroll 1
          for (int c = tid - 128; c < 1024 && skip >= 0; c += 128) {
            const int r = c >> 4;
            if (r != (sel & 63))
              *(uint4*)(P.out + (size_t)(mb * 128 + skip * 64 + r) * DM + nb * 128 + (c & 15) * 8) =
                  *(const uint4*)(smem + X_ST + skip * 16384 + ((c >> 3) & 1) * 8192 + r * 128 + (((c ^ r) & 7) << 4));
          }
          __syncwarp();
        } else asm volatile("bar.arrive 7, 512;" ::: "memory");
        if (warp == 5 && layer == 0) {
              named_bar(8, 288);
              if (nb > 0) spin_cycles(X_STAGGER);
              store_tile(0, -1, true);
              set_flag(&g_xflag[mb][nb].v[0], tag);
              PROF(17);
              poll_flag(&g_xflag[2 * rb + (lane & 1)][0].v[0], tag);
              fence_async_global();
              load_a(0, 0, 1);
              PROFL(1, 1);
        }
      }
      named_bar(1 + (fresh_tid() >> 7), 128);
      regs_dec<32>();
#pragma unroll 1
      for (;;) {
      const unsigned pass = __shfl_sync(0xffffffffu, pass_v, 0);
      if (pass > 0) {
        const unsigned layer = pass - 1;
        PHASE_IDS
        const uint32_t tag = s_misc[M_TAG], bkey = s_misc[M_KEY];
        const int sel = SEQ - 1 - (int)(bkey & 0x7FFFu);
        if (warp == 3) {
          if (layer == 1) {
#pragma unroll
            for (int j = 0; j < 3; j++) ((uint4*)g_vw)[bid * 96 + j * 32 + lane] = make_uint4(0, 0, 0, 0);
          }
          if (bid == 0 && lane == 0) g_sel[layer] = sel;
        }
        __syncwarp();
        if (layer == 0) {
          auto load_down = [&](int j) {
            mbar_expect_tx(bar(B_DN + j), 2 * FFN_PIECE);
            bulk_load_h(sbase + SL_F + j * 2 * FFN_PIECE, P.w_d + (size_t)(bid * 28 + j * 14) * DM, 2 * FFN_PIECE, bar(B_DN + j), policy_evict_first());
          };
          if (warp == 5) {
            load_a(2, 2, 1);
            poll_flag(&g_xflag[2 * rb + (lane & 1)][(lane >> 1) & 7].v[0], tag);
            fence_async_global();
            load_a(4, 4, 1);
          }
          float hv = 0.f;
          if (wg == 1) { mbar_wait_cluster(bar(B_HX), 0); hv = rbf(hidden()); fence_regs<1>(&hv); }
          named_bar(9, 512);
          if (warp == 0) {
            fence_async_smem();
            if (lane < 16) mbar_arrive_cluster(bar(B_QFREE), lane & 1);
            mbar_wait(bar(B_QFREE), 1);
            load_w(4, 4); load_w(5, 5);
            load_down(0);
          } else if (wg == 1) {
            if (warp == 4) { mbar_wait(bar(B_DN), 0); load_down(1); }
            float d[8] = {0.f, 0.f, 0.f, 0.f, 0.f, 0.f, 0.f, 0.f};
            const uint4* wrow = (const uint4*)(smem + SL_F) + tid - 128;
            mbar_wait(bar(B_DN), 0);
            uint4 w0 = wrow[0];
#pragma unroll 1
            for (int j = 0; j < 28; j += 2) {
              const uint4 w1 = wrow[j * 128 + 128];
              fma8(d, w0, __shfl_sync(0xffffffffu, hv, j));
              if (j == 12) mbar_wait(bar(B_DN + 1), 0);
              w0 = wrow[min(j + 2, 27) * 128];
              fma8(d, w1, __shfl_sync(0xffffffffu, hv, j + 1));
            }
            uint4* dst = &g_ypart[0][bid * 256 + (tid - 128) * 2];
            st_relaxed4(dst, make_uint4(__float_as_uint(d[0]), __float_as_uint(d[1]), __float_as_uint(d[2]), __float_as_uint(d[3])));
            st_relaxed4(dst + 1, make_uint4(__float_as_uint(d[4]), __float_as_uint(d[5]), __float_as_uint(d[6]), __float_as_uint(d[7])));
            asm volatile("bar.arrive 11, 160;" ::: "memory");
            PROF(20);
          } else if (warp == 2) {
            named_bar(11, 160);
            fence_async_smem();
            load_ws(WS_PACE);
          }
        } else {
          if (wg == 1) named_bar(9, 384);
          cluster_arrive();
        }
        if (wg == 1) {
          const int t_y = (int)clock();
          const uint32_t xw = s_misc[M_XQ + ((lane & 7) >> 1)];
          const float x = (lane & 1) ? bf_hi(xw) : bf_lo(xw);
          float xn = rbf(rbf(x - __uint_as_float(s_misc[M_MEAN])) * __uint_as_float(s_misc[M_INV]));
          uint32_t u = bkey & 0xFFFF0000u;
          u = (u & 0x80000000u) ? (u & 0x7FFFFFFFu) : (~u & 0xFFFF0000u);
          float sg = rbf(__fdividef(1.f, 1.f + __expf(-__uint_as_float(u))));
          uint32_t* dst = (layer == 0 ? (uint32_t*)&g_x2row[bid * 2] : (uint32_t*)(P.out + (size_t)sel * DM + bid * 8)) + (lane >> 1);
          asm volatile("" : "+f"(xn), "+f"(sg), "+l"(dst));
#pragma unroll 1
          while ((int)clock() - t_y < DELAY_Y) {}
          const uint4* src = &g_ypart[layer][((tid - 128) >> 1) * 256 + bid * 2 + (tid & 1)];
          uint4 v, w;
          uint32_t spins = 0;
#pragma unroll 1
          do { v = ld_relaxed4(src); w = ld_relaxed4(src + 64 * 256); } while (!__all_sync(0xffffffffu, valid4(v) && valid4(w)) && ++spins < SPIN_LIMIT);
          float a[4] = {__uint_as_float(v.x) + __uint_as_float(w.x), __uint_as_float(v.y) + __uint_as_float(w.y),
                        __uint_as_float(v.z) + __uint_as_float(w.z), __uint_as_float(v.w) + __uint_as_float(w.w)};
          const bool b1 = lane & 2, b2 = lane & 4;
          float c0 = (b1 ? a[1] : a[0]) + __shfl_xor_sync(0xffffffffu, b1 ? a[0] : a[1], 2);
          float c1 = (b1 ? a[3] : a[2]) + __shfl_xor_sync(0xffffffffu, b1 ? a[2] : a[3], 2);
          float y = (b2 ? c1 : c0) + __shfl_xor_sync(0xffffffffu, b2 ? c0 : c1, 4);
          y += __shfl_xor_sync(0xffffffffu, y, 8);
          y += __shfl_xor_sync(0xffffffffu, y, 16);
          float* red = (float*)(smem + OFF_PATCH);
          red[wi * 8 + (lane & 1) * 4 + ((lane >> 1) & 3)] = y;
          named_bar(2, 128);
          if (warp == 4) {
            PROF(21);
            y = (red[lane & 7] + red[8 + (lane & 7)]) + (red[16 + (lane & 7)] + red[24 + (lane & 7)]);
            const float res = x + rbf(xn + rbf(rbf(y) * sg));
            const uint32_t pr = pack_bf16(res, __shfl_down_sync(0xffffffffu, res, 1));
            if (lane < 8 && (lane & 1) == 0) st_relaxed(dst, pr);
            PROF(22);
          }
        }
        if (pass == 2) {
          if (bid == 0 && tid == 128) g_epoch = tag;
          bulk_wait_all();
          __syncwarp();
          cluster_wait();
          return;
        }
      }
      const unsigned layer = pass;
      if (__shfl_sync(0xffffffffu, fresh_tid() >> 5, 0) > 1 - (int)layer) {
        PHASE_IDS
        uint4* xrow = (uint4*)(smem + SL_F + 4 * SL_HD);
        if (wg == 1) {
          if (layer == 0) {
            xrow[tid - 128] = make_uint4(0x3F803F80u, 0x3F803F80u, 0x3F803F80u, 0x3F803F80u);
            if (warp == 5) {
              mbar_wait(bar(B_FULL + 5), 0);
              if (lane == 0) {
#pragma unroll 1
                for (int i = 11; i > 0; i--) prefetch_tmap(&P.mapA[0] + i);
              }
              __syncwarp();
              load_ws(WS_PACE);
            }
          } else xrow[tid - 128] = poll4(&g_x2row[(tid - 128) * 2]);
          PROF(23);
        }
        named_bar(12, 192 + 32 * layer);
        if (warp == 1) {
          float mean = 0.f;
#pragma unroll 1
          for (int pass2 = 0; pass2 < 2; pass2++) {
            float acc = 0.f;
#pragma unroll 1
            for (int j = lane; j < 128; j += 32) {
              const uint4 v = xrow[j];
              const uint32_t w[4] = {v.x, v.y, v.z, v.w};
#pragma unroll
              for (int c = 0; c < 4; c++) {
                const float d0 = bf_lo(w[c]) - mean, d1 = bf_hi(w[c]) - mean;
                acc += pass2 ? d0 * d0 + d1 * d1 : d0 + d1;
              }
            }
            acc = warp_sum(acc) * (1.f / DM);
            if (pass2 == 0) mean = acc;
            else { s_misc[M_PMEAN] = __float_as_uint(rbf(mean)); s_misc[M_PINV] = __float_as_uint(ln_inv(acc)); }
          }
        } else {
          mbar_wait(bar(B_WS), layer);
          const uint8_t* wa = smem + SL_F + (g >> 1) * SL_HD + ((warp - 2) >> 1) * 4096 + (g & 1) * 2048;
          const uint32_t* xs = (const uint32_t*)xrow + rb * 64 + g * 8;
          const int ch = (warp & 1) * 4 + q;
          float d[8] = {0.f, 0.f, 0.f, 0.f, 0.f, 0.f, 0.f, 0.f};
          auto wrow = [&](int j) { j = (j ^ ((g & 1) * 4)) & 15; return *(const uint4*)(wa + j * 128 + (((ch ^ j) & 7) << 4)); };
          uint4 w0 = wrow(0);
#pragma unroll 1
          for (int j = 0; j < 16; j += 2) {
            const uint32_t xx = xs[(j >> 1) ^ ((g & 1) * 2)];
            const uint4 w1 = wrow(j + 1);
            fma8(d, w0, bf_lo(xx));
            w0 = wrow(j + 2);
            fma8(d, w1, bf_hi(xx));
          }
#pragma unroll
          for (int c = 0; c < 4; c++) d[c] = ((g & 4) ? d[c + 4] : d[c]) + __shfl_xor_sync(0xffffffffu, (g & 4) ? d[c] : d[c + 4], 16);
#pragma unroll
          for (int c = 0; c < 2; c++) d[c] = ((g & 2) ? d[c + 2] : d[c]) + __shfl_xor_sync(0xffffffffu, (g & 2) ? d[c] : d[c + 2], 8);
          d[0] = ((g & 1) ? d[1] : d[0]) + __shfl_xor_sync(0xffffffffu, (g & 1) ? d[0] : d[1], 4);
          st_relaxed(&g_vw[layer][rb][((warp - 2) >> 1) * DM + hp * 64 + ch * 8 + g], enc(d[0]));
        }
        named_bar(12, 192 + 32 * layer);
        PROF(24);
      }
      PHASE_IDS
      if (wg == 0) {
        if (warp == 0) {
          if (layer == 0) {
#pragma unroll 1
            for (int i = 2; i < 6; i++) { load_w(i, i); if (!(i & 1)) load_a(i, i, 0); }
          }
          int s = 0, u = 0;
#pragma unroll 1
          for (int i = 6; i < 32; i++) {
            if (layer == 1) mbar_arrive_e(bar(B_EMPTY + s));
            mbar_wait(bar(B_EMPTY + s), (u + (s > 1 ? 0 : layer)) & 1);
            if (s & 1) load_a(s - 1, i - 1, layer);
            load_w(s, i);
            if (++s == 6) { s = 0; u++; }
          }
        } else if (warp == 1) {
          if (layer == 0) {
            const uint32_t tag = ld_relaxed(&g_epoch) + 1;
            if (lane < 16) g_rowab[0][rb * 256 + hp * 16 + lane] = make_uint4(0, 0, 0, 0);
            float shift = 0.f, sum = 0.f, sq = 0.f;
            const int r = hp * 16 + (lane >> 1);
#pragma unroll 1
            for (int i = 0; i < 32; i++) {
              mbar_wait(bar(B_FULL + i % 6), (i / 6) & 1);
              const uint8_t* base = smem + ((i % 6) >> 1) * STG + r * 128;
              uint4 v[2];
#pragma unroll
              for (int j = 0; j < 2; j++) v[j] = *(const uint4*)(base + ((((i & 1) * 4 + (lane & 1) * 2 + j) ^ (r & 7)) << 4));
              if (i == 0) shift = __shfl_sync(0xffffffffu, bf_lo(v[0].x), lane & ~1);
#pragma unroll
              for (int j = 0; j < 2; j++) {
                const uint32_t w[4] = {v[j].x, v[j].y, v[j].z, v[j].w};
#pragma unroll
                for (int c = 0; c < 4; c++) {
                  const float d0 = bf_lo(w[c]) - shift, d1 = bf_hi(w[c]) - shift;
                  sum += d0 + d1; sq = fmaf(d0, d0, fmaf(d1, d1, sq));
                }
              }
              fence_async_smem();
              __syncwarp();
              if (i < 26) mbar_arrive_e(bar(B_EMPTY + i % 6));
            }
            sum += __shfl_xor_sync(0xffffffffu, sum, 1); sq += __shfl_xor_sync(0xffffffffu, sq, 1);
            const float dm = sum * (1.f / DM), var = fmaxf(sq * (1.f / DM) - dm * dm, 0.f), mean = shift + dm;
            const float inv = ln_inv(var);
            if ((lane & 1) == 0) st_relaxed4(&g_rowab[0][rb * 256 + r], make_uint4(__float_as_uint(inv), __float_as_uint(rbf(mean) * inv), tag, 0));
          }
          __syncwarp();
          mbar_arrive_e(bar(B_E23));
          if (rb == 0) {
            mbar_wait(bar(B_QDONE), layer);
#pragma unroll 1
            for (int j = lane; j < 512; j += 32) ((uint4*)(smem + kv_off(1, 0)))[j] = make_uint4(0, 0, 0, 0);
            fence_async_smem();
            __syncwarp();
            if (lane < 3) mbar_arrive(bar(B_HALO + lane));
          }
        } else if (warp == 3) {
          if (rb > 0) { mbar_expect_tx(bar(B_HALO), 16384); mbar_expect_tx(bar(B_HALO + 1), 16384); mbar_expect_tx(bar(B_HALO + 2), 32768); }
          fence_async_smem();
          load_gu(0, layer ? GU_PACE1 : GU_PACE);
          PROF(27);
        } else {
          const uint4 sent = make_uint4(SENT, SENT, SENT, SENT), zero = make_uint4(0, 0, 0, 0);
          if (layer == 0) {
            const int f = lane >> 1;
            Flag* fl = f < 2 ? &g_kvflag[rb >> 1][hp][f] : f < 4 ? &g_oflag[rb][f & 1][hp] : &g_xflag[mb][nb];
            if (f < 5 && (f >= 2 || (rank == 1 && rb < 7))) ((uint4*)fl)[lane & 1] = zero;
          }
#pragma unroll 1
          for (int t = lane; t < 128; t += 32) {
            g_ypart[layer][bid * 256 + t] = sent; g_ypart[layer][bid * 256 + 128 + t] = sent;
            g_part[layer][nb * SEQ + mb * 128 + t] = zero;
            if (t < 16) g_cand[layer][mb * 128 + nb * 16 + t] = sent;
            else if (t < 18) { if (nb == 0) g_slot[layer][mb * 8 + t - 16] = zero; }
            else if (t < 20) { if (layer == 0) g_x2row[bid * 2 + t - 18] = sent; }
          }
          __syncwarp();
          mbar_arrive_e(bar(B_CS));
        }
        __syncwarp();
        uint8_t* kvg = g_kv + (size_t)(((rb - 1 + rank) >> 1) * 16 + hp) * 65536;
        if (rank == 0) {
          if (warp == 0) {
            mbar_wait(bar(B_QDONE), layer);
#pragma unroll 1
            for (int j = 0; j < 4; j++) {
              mbar_wait(bar(B_KVREADY + (j >> 1)), layer);
              bulk_push(mapa(sbase + kv_off(j & 1, 2 - (j & 2)), 1), sbase + kv_off(j & 1, 6 - (j & 2)), 16384, mapa(bar(B_HALO + min(j, 2)), 1));
            }
          } else if (warp < 3 && rb > 0) {
            const int p = warp - 1;
            mbar_wait(bar(B_QREADY), layer);
            if (p) spin_cycles(P1_DELAY);
            poll_flag(&g_kvflag[(rb - 1) >> 1][hp][p].v[layer], s_misc[M_TAG]);
            fence_async_global();
#pragma unroll 1
            for (int j = 2 * p; j < 2 * p + 2; j++) bulk_load_h(sbase + kv_off(j & 1, 2 - (j & 2)), kvg + j * 16384, 16384, bar(B_HALO + min(j, 2)), policy_evict_first());
            if (p == 0) PROF(5);
          }
        } else if (warp < 2 && rb < 7) {
          mbar_wait(bar(B_KVREADY + warp), layer);
          if (warp == 1) named_bar(13, 64);
#pragma unroll 1
          for (int j = 2 * warp; j < 2 * warp + 2; j++) bulk_store(kvg + j * 16384, sbase + kv_off(j & 1, 6 - (j & 2)), 16384);
          bulk_commit();
          bulk_wait_all();
          if (warp == 0) asm volatile("bar.arrive 13, 64;" ::: "memory");
          set_flag(&g_kvflag[rb >> 1][hp][warp].v[layer], s_misc[M_TAG]);
          if (warp == 0) PROF(4);
        }
      } else {
        const int t = tid - 128, go = (t >> 5) * DM + hp * 64 + (t & 31) * 2;
        if (layer == 0 && t == 96) { s_misc[M_TAG] = ld_relaxed(&g_epoch) + 1; s_misc[M_SEL0] = 0xFFFFFFFFu; s_misc[M_PROG] = s_misc[M_PROG + 1] = 0; }
        if ((layer == 0 || (int)s_misc[M_SEL0] >> 8 == rb) && warp < 7) {
          spin_cycles(layer ? 300 : 1500);
          uint2 w[8];
          uint32_t spins = 0;
          bool ok;
#pragma unroll 1
          do {
            ok = true;
#pragma unroll
            for (int j = 0; j < 8; j++) w[j] = ld_relaxed2(&g_vw[layer][j][go]);
#pragma unroll
            for (int j = 0; j < 8; j++) ok = ok && w[j].x && w[j].y;
          } while (!__all_sync(0xffffffffu, ok) && ++spins < SPIN_LIMIT);
          float s0 = 0.f, s1 = 0.f;
#pragma unroll
          for (int j = 0; j < 8; j++) { s0 += dec(w[j].x); s1 += dec(w[j].y); }
          float2* csp = (float2*)(smem + OFF_CS) + (t & ~7) + (t & 3) * 2 + ((t >> 2) & 1);
          if (layer == 0) *csp = make_float2(s0, s1);
          else {
            const float2 c = *csp;
            const float a = __uint_as_float(s_misc[M_PINV]) * (warp == 4 ? SM_C : 1.f), b = __uint_as_float(s_misc[M_PMEAN]) * a;
            ((uint32_t*)(smem + OFF_PATCH))[t] = pack_bf16(s0 * a - c.x * b, s1 * a - c.y * b);
          }
          PROF(25);
        }
        __syncwarp();
        mbar_arrive_e(bar(B_CS));
      }
      __syncwarp();
      if (wi == 0) mbar_wait(bar(B_QREADY), layer);
      named_bar(1 + (fresh_tid() >> 7), 128);
      if (__shfl_sync(0xffffffffu, fresh_tid() >> 7, 0) == 0) {
        regs_inc<152>();
        uint32_t gu[112];
        {
          PHASE_IDS
          const uint32_t tag = s_misc[M_TAG];
          mbar_wait(bar(B_GU), layer);
#pragma unroll
          for (int j = 0; j < 28; j++) fetch_gu(gu + 4 * j, warp * 4 + (j & 3), j >> 2);
          fence_async_smem();
          named_bar(1, 128);
          if (warp == 0) {
            mbar_wait(bar(B_ADONE), layer);
#pragma unroll 1
            for (int k = 2; k < 16; k++) {
#pragma unroll 1
              for (uint32_t spins = 0; (int)s_misc[M_PROG + (k >> 3)] <= (k & 7) + 16 * (int)layer && spins < SPIN_LIMIT; spins++) {}
              if (k >= 4) mbar_wait(bar(B_WEMPTY + (k & 3)), ((k >> 2) - 1 + ((k & 2) ? layer : 0)) & 1);
              load_o(k); load_wo(k);
              STEPT(16 + k);
              if (k == RES_K) { mbar_wait(bar(B_OST + 1), layer); load_res(1, layer); }
            }
            if (layer == 1) {
              mbar_wait(bar(B_WEMPTY + 1), 1);
              mbar_expect_tx(bar(B_DN), 4 * FFN_PIECE);
              tma_load3_h(sbase + wo_off(0), &P.mapD, 0, bid * 28, 0, bar(B_DN), policy_evict_first());
            }
            named_bar(6, 320);
            if (layer == 0) {
              mbar_wait(bar(B_QFREE), 0);
#pragma unroll 1
              for (int i = 0; i < 4; i++) load_w(i, i);
            } else tma_load3_h(sbase + wo_off(0) + 2 * FFN_PIECE, &P.mapD, 0, bid * 28, 8, bar(B_DN), policy_evict_first());
          } else if (warp < 3) {
            const int h = warp - 1;
#pragma unroll 1
            for (int qb = 3; qb >= 0; qb--) {
              mbar_wait(bar(B_UNIT + h * 4 + 3 - qb), layer);
              bulk_store(g_o + (size_t)((((rb * 2 + (qb >> 1)) * 2 + h) * 16 + hp) * 2 + (qb & 1)) * 4096, sbase + qo_off(h, qb), 4096);
            }
            bulk_commit();
            if (h == 0 && lane < 2) mbar_arrive_cluster(bar(B_OST), lane);
            bulk_wait_all();
            if (h == 1) mbar_arrive_e(bar(B_OST + 1));
            set_flag(&g_oflag[rb][h][hp].v[layer], tag);
            PROF(28 + 3 * h);
            if (h == 0) { load_res(0, layer); mbar_wait(bar(B_OST), layer); load_wo(0); load_wo(1); }
            int n = 0, first = h;
#pragma unroll 1
            for (uint32_t spins = 0; n < 8 && spins < SPIN_LIMIT; spins++) {
              n = (__ffs(__ballot_sync(0xffffffffu, ld_relaxed(&g_oflag[rb][h][lane & 15].v[layer]) != tag || lane == 16)) - 1) >> 1;
              asm volatile("fence.acquire.gpu;" ::: "memory");
              fence_async_global();
              if (!first && n >= 2) {
                first = 1;
                load_o(0); load_o(1);
                PROF(15);
              }
              s_misc[M_PROG + h] = n + 16 * layer;
            }
            if (h) PROF(26);
          } else {
            mbar_expect_tx(bar(B_HX), 2240);
            mbar_wait(bar(B_HALO + 2), layer);
            if (rb == 0) spin_cycles(2000);
            PROF(6);
            load_gu(1, GUB_PACE);
          }
        }
        PHASE_IDS
        uint4 xa = {}, xb = {};
        named_bar(7, 512);
        if (g == 0) { xa = ((const uint4*)(smem + T_XS))[warp * 8 + q]; xb = ((const uint4*)(smem + T_XS))[warp * 8 + 4 + q]; }
        __syncwarp();
        float d[7][4] = {};
#pragma unroll
        for (int j = 0; j < 28; j++) {
          const int ks = j / 7, ct = j % 7;
          const uint32_t* a = gu + ct * 16 + ks * 4;
          mma_16816(d[ct], a[0], a[1], a[2], a[3], ks == 0 ? xa.x : ks == 1 ? xa.z : ks == 2 ? xb.x : xb.z, ks == 0 ? xa.y : ks == 1 ? xa.w : ks == 2 ? xb.y : xb.w);
        }
#pragma unroll
        for (int ct = 0; ct < 7; ct++) send_gu(d[ct][0], d[ct][2], ct, warp);
        __syncwarp();
        if (warp == 2) PROF(18);
        regs_dec<32>();
        pass_v = pass + 1;
        continue;
      }
      break;
      }
      regs_inc<120>();
    }
    const unsigned layer = pass;
    {
      PHASE_IDS
      mbar_wait(bar(B_QREADY), layer);
      if (warp != 9) STEPT(7);
      const int bmin = rb == 0 ? 4 : 0;
      auto kdesc = [&](int h, int b) { const uint32_t v = dlo(SOFF, 16) + (kv_off(h, b) >> 4); return b < bmin ? dlo(SOFF + kv_off(1, 0), 16) : v; };
      auto vdesc = [&](int h, int b) {
        const uint32_t v = dlo(SOFF + 4096, OFF_ONES - 4096) + (kv_off(h, b) >> 10) * VSTEP;
        return b < bmin ? dlo(SOFF + kv_off(1, 0), 4096) : v;
      };
      const int units = wg == 3 ? 0x8630 : (wg == 2 ? 0x8721 : 0x854);
      auto need = [&](int h, int b) { if (b == 3 || b == 1) mbar_wait(bar(B_HALO + (b == 1 ? 2 : h)), layer); };
      auto load_q = [&](uint32_t* qf, int u) {
        *(uint4*)&qf[0] = *(const uint4*)(smem + qo_off(u >> 2, ~u & 3) + wi * 1024 + lane * 16);
        *(uint4*)&qf[4] = *(const uint4*)(smem + qo_off(u >> 2, ~u & 3) + wi * 1024 + 512 + lane * 16);
      };
      auto store_o = [&](const float* o, int u) {
        const float i0 = rcp(o[16]), i1 = rcp(o[18]);
        if (u >= 4 && lane < 2) mbar_arrive_cluster(bar(B_ADONE), lane);
#pragma unroll
        for (int j = 0; j < 2; j++)
          stsm_x4(sbase + qo_off(u >> 2, ~u & 3) + srow * 64 + (((2 * j + (mi >> 1)) ^ ((srow >> 1) & 3)) << 4),
                  pack_bf16(o[8 * j] * i0, o[8 * j + 1] * i0), pack_bf16(o[8 * j + 2] * i1, o[8 * j + 3] * i1),
                  pack_bf16(o[8 * j + 4] * i0, o[8 * j + 5] * i0), pack_bf16(o[8 * j + 6] * i1, o[8 * j + 7] * i1));
        fence_async_smem();
        __syncwarp();
        mbar_arrive_e(bar(B_UNIT + u));
      };
      int redo = 0;
      {
        const int dl = g - 2 * q;
        const uint32_t mt = shl_clamp(0xFFFFFFFFu, max(16 * dl + 16, 0));
        uint32_t qf[8];
        float s[32];
        load_q(qf, units & 7);
        wg_fence();
        qk64(s, qf, kdesc((units >> 2) & 1, 6 - (units & 3)));
        wg_commit();
        wg_wait<0>();
        fence_regs<32>(s);
#pragma unroll 1
        for (int ul = units; ul != 8; ul >>= 4) {
          const int u = ul & 7, h = u >> 2, qb = 3 - (u & 3);
          float o[20];
          uint32_t p1[16], p2[16], p3[16], p4[16], p5[16];
          if (warp != 9) STEPT(8 + nu * 8);
          exp_pack<8>(s, p1);
          fence_regs_u<16>(p1);
          need(h, qb + 2);
          {
            float s2[32];
            const uint32_t vd = vdesc(h, qb + 3);
            wg_fence();
            qk64(s2, qf, kdesc(h, qb + 2));
            wg_commit();
            wg_rs40t_z<H64>(o, p1[0], p1[1], p1[2], p1[3], vd);
            wg_rs40t<H64>(o, p1[4], p1[5], p1[6], p1[7], vd + VSTEP, 1);
            pv32(o, p1 + 8, vd + 2 * VSTEP);
            wg_commit();
            wg_wait<1>();
            fence_regs<32>(s2);
            if (warp != 9) STEPT(9 + nu * 8);
            exp_pack<8>(s2, p2);
            fence_regs_u<16>(p2);
            wg_wait<0>();
            fence_regs<20>(o);
          }
          need(h, qb + 1);
          {
            float s3[32];
            wg_fence();
            qk64(s3, qf, kdesc(h, qb + 1));
            wg_commit();
            pv32(o, p2, vdesc(h, qb + 2)); pv32(o, p2 + 8, vdesc(h, qb + 2) + 2 * VSTEP);
            wg_commit();
            wg_wait<1>();
            fence_regs<32>(s3);
            if (warp != 9) STEPT(10 + nu * 8);
            exp_pack<8>(s3, p3);
            fence_regs_u<16>(p3);
            wg_wait<0>();
            fence_regs<20>(o);
          }
          need(h, qb);
          const uint32_t kd = kdesc(h, qb + 4), kt = kdesc(h, qb), vd = vdesc(h, qb + 4), vt = vdesc(h, qb);
          {
            float sd[16], st[16];
            wg_fence();
            qk32x2(sd, st, qf, kd, kt);
            wg_commit();
            pv32(o, p3, vdesc(h, qb + 1)); pv32(o, p3 + 8, vdesc(h, qb + 1) + 2 * VSTEP);
            wg_commit();
            wg_wait<1>();
            fence_regs<16>(sd); fence_regs<16>(st);
            if (warp != 9) STEPT(11 + nu * 8);
            edge32(sd, st, p4, p4 + 8, wi, dl, mt);
            fence_regs_u<16>(p4);
            wg_wait<0>();
            fence_regs<20>(o);
          }
          const int un = (ul >> 4) == 8 ? 4 : (ul >> 4) & 7;
          {
            float sd[16], st[16];
            wg_fence();
            qk32x2(sd, st, qf, kd + 128, kt + 128);
            wg_commit();
            pv32(o, p4, vd); pv32(o, p4 + 8, vt);
            wg_commit();
            wg_wait<1>();
            fence_regs<16>(sd); fence_regs<16>(st);
            load_q(qf, un);
            edge32(sd, st, p5, p5 + 8, wi - 2, dl, mt);
            fence_regs_u<16>(p5);
          }
          need(un >> 2, 6 - (un & 3));
          wg_fence();
          pv32(o, p5, vd + 2 * VSTEP); pv32(o, p5 + 8, vt + 2 * VSTEP);
          wg_commit();
          qk64(s, qf, kdesc(un >> 2, 6 - (un & 3)));
          wg_commit();
          wg_wait<1>();
          fence_regs<20>(o);
          if (warp != 9) STEPT(12 + nu * 8);
          const bool unsafe = !(o[16] >= LSUM_MIN && o[16] <= LSUM_MAX && o[18] >= LSUM_MIN && o[18] <= LSUM_MAX);
          if (__any_sync(0xffffffffu, unsafe)) redo |= 1 << u;
          else store_o(o, u);
          wg_wait<0>();
          fence_regs<32>(s);
        }
      }
      if (warp != 9) STEPT(31);
      if (bar_red_or(1 + wg, 128, redo)) {
#pragma unroll 1
        for (int ul = units; ul != 8; ul >>= 4) {
          const int u = ul & 7;
          if (!bar_red_or(1 + wg, 128, redo >> u & 1)) continue;
          const int h = u >> 2, qb = 3 - (u & 3);
          uint32_t qf[8], p[16];
          float o[20], m0 = -INFINITY, m1 = -INFINITY;
          load_q(qf, u);
#pragma unroll
          for (int i = 0; i < 20; i++) o[i] = 0.f;
#pragma unroll 1
          for (int j = 0; j <= (rb == 0 ? qb : 4); j++) {
            const int b = qb + 4 - j;
            float s[32];
            wg_fence();
            qk64(s, qf, kdesc(h, b));
            wg_commit();
            wg_wait<0>();
            fence_regs<32>(s);
            float mx0 = m0, mx1 = m1;
#pragma unroll
            for (int c = 0; c < 8; c++) {
#pragma unroll
              for (int i = 0; i < 4; i++) {
                const int diff = j * 64 + (16 * wi + g + (i >> 1) * 8) - (8 * c + 2 * q + (i & 1));
                if (diff < 0 || diff > 255) s[4 * c + i] = -INFINITY;
              }
              mx0 = fmaxf(mx0, fmaxf(s[4 * c], s[4 * c + 1]));
              mx1 = fmaxf(mx1, fmaxf(s[4 * c + 2], s[4 * c + 3]));
            }
            mx0 = fmaxf(mx0, __shfl_xor_sync(0xffffffffu, mx0, 1)); mx1 = fmaxf(mx1, __shfl_xor_sync(0xffffffffu, mx1, 1));
            mx0 = fmaxf(mx0, __shfl_xor_sync(0xffffffffu, mx0, 2)); mx1 = fmaxf(mx1, __shfl_xor_sync(0xffffffffu, mx1, 2));
            const float r0 = j == 0 ? 0.f : ex2(m0 - mx0), r1 = j == 0 ? 0.f : ex2(m1 - mx1);
            m0 = mx0; m1 = mx1;
#pragma unroll
            for (int i = 0; i < 5; i++) { o[4 * i] *= r0; o[4 * i + 1] *= r0; o[4 * i + 2] *= r1; o[4 * i + 3] *= r1; }
#pragma unroll
            for (int c = 0; c < 8; c++) { s[4 * c] -= m0; s[4 * c + 1] -= m0; s[4 * c + 2] -= m1; s[4 * c + 3] -= m1; }
            exp_pack<8>(s, p);
            fence_regs<20>(o); fence_regs_u<16>(p);
            wg_fence();
            pv32(o, p, vdesc(h, b)); pv32(o, p + 8, vdesc(h, b) + 2 * VSTEP);
            wg_commit();
            wg_wait<0>();
            fence_regs<20>(o);
          }
          named_bar(1 + wg, 128);
          if (redo >> u & 1) store_o(o, u);
          __syncwarp();
        }
      }
      if (wi == 0) PROF(6 + wg);
    }
    pass_v = pass + 1;
  }
}

}

typedef CUresult (*EncodeFn)(CUtensorMap*, CUtensorMapDataType, cuuint32_t, void*, const cuuint64_t*, const cuuint64_t*,
                             const cuuint32_t*, const cuuint32_t*, CUtensorMapInterleave, CUtensorMapSwizzle,
                             CUtensorMapL2promotion, CUtensorMapFloatOOBfill);
static EncodeFn g_encode = nullptr;
struct Dim { uint64_t size, stride; uint32_t box; };
template <int N> static CUtensorMap make_map(const void* ptr, const Dim (&d)[N], int swizzle) {
  CUtensorMap m;
  cuuint64_t dims[N], strides[N];
  cuuint32_t box[N], es[N];
  for (int i = 0; i < N; i++) { dims[i] = d[i].size; strides[i] = d[i].stride; box[i] = d[i].box; es[i] = 1; }
  g_encode(&m, CU_TENSOR_MAP_DATA_TYPE_BFLOAT16, N, const_cast<void*>(ptr), dims, strides + 1, box, es, CU_TENSOR_MAP_INTERLEAVE_NONE,
           swizzle == 128 ? CU_TENSOR_MAP_SWIZZLE_128B : (swizzle == 64 ? CU_TENSOR_MAP_SWIZZLE_64B : CU_TENSOR_MAP_SWIZZLE_NONE),
           swizzle ? CU_TENSOR_MAP_L2_PROMOTION_L2_256B : CU_TENSOR_MAP_L2_PROMOTION_L2_128B, CU_TENSOR_MAP_FLOAT_OOB_FILL_NONE);
  return m;
}
static CUtensorMap map2(const void* ptr, uint64_t inner, uint64_t outer, uint32_t bi, uint32_t bo, int swizzle) {
  const Dim d[2] = {{inner, 0, bi}, {outer, inner * 2, bo}};
  return make_map(ptr, d, swizzle);
}
template <class T> static void* sym_addr(T& sym) { void* p = nullptr; cudaGetSymbolAddress(&p, sym); return p; }

static Params h_p;
static const void* h_key[9];

static cudaLaunchConfig_t launch_cfg(int grid, cudaLaunchAttribute* at) {
  cudaLaunchConfig_t cfg = {};
  cfg.gridDim = dim3(grid); cfg.blockDim = dim3(512); cfg.dynamicSmemBytes = SMEM_BYTES; cfg.stream = cudaStreamPerThread;
  at[0].id = cudaLaunchAttributeClusterDimension;
  at[0].val.clusterDim.x = 2; at[0].val.clusterDim.y = 1; at[0].val.clusterDim.z = 1;
  cfg.attrs = at; cfg.numAttrs = 1;
  return cfg;
}

extern "C" void kernel_launch(void* const* d_in, const int* in_sizes, int n_in, void* d_out, int out_size) {
  const bf16* x = (const bf16*)d_in[0];
  const bf16* wqkv = (const bf16*)d_in[1];
  const bf16* wo = (const bf16*)d_in[2];
  cudaLaunchAttribute at[1];
  bool fresh = g_encode != nullptr && h_key[8] == d_out;
  for (int i = 0; i < 8; i++) fresh = fresh && h_key[i] == d_in[i];
  if (!fresh) {
    if (!g_encode) {
      void* fn = nullptr;
      cudaDriverEntryPointQueryResult st;
      cudaGetDriverEntryPoint("cuTensorMapEncodeTiled", &fn, cudaEnableDefault, &st);
      g_encode = (EncodeFn)fn;
      cudaFuncSetAttribute(mega_kernel, cudaFuncAttributeMaxDynamicSharedMemorySize, SMEM_BYTES);
    }
    bf16* x1 = (bf16*)sym_addr(g_x1);
    Params& p = h_p;
    p.w_r = (const bf16*)d_in[4]; p.w_d = (const bf16*)d_in[7];
    p.out = (bf16*)d_out;
    p.mapA[0] = map2(x, DM, SEQ, 64, 256, 128);
    p.mapA[1] = map2(x1, DM, SEQ, 64, 256, 128);
    { const Dim d[3] = {{DM, 0, 64}, {DM, 3 * DM * 2, 16}, {3, DM * 2, 3}}; p.mapW = make_map(wqkv, d, 128); }
    { const Dim d[3] = {{DM, 0, 64}, {DM, 3 * DM * 2, 32}, {3, DM * 2, 3}}; p.mapWs = make_map(wqkv, d, 128); }
    { const Dim d[3] = {{DM, 0, 64}, {64, DM * 2, 32}, {16, 64 * DM * 2, 2}}; p.mapWo = make_map(wo, d, 128); }
    p.mapRes[0] = map2(x, DM, SEQ, 64, 64, 128);
    p.mapRes[1] = p.mapXst[0] = map2(x1, DM, SEQ, 64, 64, 128);
    p.mapXst[1] = map2(d_out, DM, SEQ, 64, 64, 128);
    p.mapG = map2(d_in[5], FF, DM, 56, 128, 0);
    p.mapU = map2(d_in[6], FF, DM, 56, 128, 0);
    { const Dim d[3] = {{64, 0, 64}, {FF, DM * 2, 28}, {DM / 64, 128, 8}}; p.mapD = make_map(p.w_d, d, 128); }
    for (int b = 0; b < 128; b++) {
      static const int perm[8] = {0, 6, 4, 5, 1, 2, 3, 7};
      const int c = b >> 1, col = c < 4 ? 0 : (c < 36 ? (c - 4) & 7 : (c - 36) % 7 + 1), j = c < 4 ? 4 + c : (c < 36 ? (c - 4) >> 3 : 4 + (c - 36) / 7);
      p.role[b] = (b & 1) | (perm[col] >> 1) << 1 | j << 3 | (perm[col] & 1) << 6;
    }
    for (int i = 0; i < 8; i++) h_key[i] = d_in[i];
    h_key[8] = d_out;
  }
  void* a0[] = {&h_p};
  cudaLaunchConfig_t cfg = launch_cfg(128, at);
  cudaLaunchKernelExC(&cfg, (const void*)mega_kernel, a0);
}
```

```cpp
#include <cuda_runtime.h>
#include <cuda_bf16.h>
#include <cuda.h>
#include <stdint.h>
#pragma nv_diag_suppress 550

namespace {

constexpr int SEQ = 2048, DM = 1024, FF = 3584;
constexpr float LN_EPS = 1e-5f;
typedef __nv_bfloat16 bf16;

__device__ __align__(1024) uint8_t g_kv[3 * 16 * 65536];
__device__ __align__(1024) uint8_t g_o[SEQ * DM * 2];
__device__ __align__(1024) bf16 g_x1[SEQ * DM];
__device__ unsigned g_epoch;
struct __align__(128) Flag { unsigned v[32]; };
__device__ Flag g_kvflag[3][16][2], g_oflag[8][2][16], g_xflag[16][8];
__device__ uint4 g_rowab[2][SEQ];
__device__ __align__(16) uint32_t g_vw[2][8][3 * DM];
constexpr uint32_t SENT = 0xFFFFFFFFu;
__device__ uint4 g_part[2][8 * SEQ];
__device__ uint4 g_slot[2][16 * 8];
__device__ uint4 g_cand[2][16 * 128];
__device__ uint4 g_ypart[2][128 * DM / 4];
__device__ uint4 g_x2row[128 * 2];
__device__ float2 g_rowln[8][SEQ];
__device__ int g_sel[2];

#define PROFL(l, e)
#define PROF(e) PROFL(layer, e)
#define STEPT(i)
#define SPIN_LIMIT 4000000u
__device__ __forceinline__ uint32_t smem_u32(const void* p) { return (uint32_t)__cvta_generic_to_shared(p); }
__device__ __forceinline__ void mbar_init(uint32_t bar, uint32_t cnt) {
  asm volatile("mbarrier.init.shared::cta.b64 [%0], %1;" ::"r"(bar), "r"(cnt) : "memory");
}
#define ELECT "{\n.reg .pred e;\nelect.sync _|e, 0xffffffff;\n@e "
__device__ __forceinline__ void mbar_expect_tx(uint32_t bar, uint32_t bytes) {
  asm volatile(ELECT "mbarrier.arrive.expect_tx.shared::cta.b64 _, [%0], %1;\n}" ::"r"(bar), "r"(bytes) : "memory");
}
__device__ __forceinline__ void mbar_arrive(uint32_t bar) {
  asm volatile("mbarrier.arrive.shared::cta.b64 _, [%0];" ::"r"(bar) : "memory");
}
__device__ __forceinline__ void mbar_arrive_e(uint32_t bar) {
  asm volatile(ELECT "mbarrier.arrive.shared::cta.b64 _, [%0];\n}" ::"r"(bar) : "memory");
}
__device__ __forceinline__ uint32_t mapa(uint32_t addr, uint32_t cta) {
  uint32_t r; asm("mapa.shared::cluster.u32 %0, %1, %2;" : "=r"(r) : "r"(addr), "r"(cta)); return r;
}
__device__ __forceinline__ void mbar_arrive_cluster(uint32_t bar, uint32_t cta) {
  asm volatile("mbarrier.arrive.shared::cluster.b64 _, [%0];" ::"r"(mapa(bar, cta)) : "memory");
}
#define MBAR_WAIT_ASM(QUAL)                                                                                                \
  asm volatile("{\n.reg .pred p;\nWAIT_LOOP:\n.pragma \"nounroll\";\nmbarrier.try_wait.parity" QUAL ".shared::cta.b64 p, [%0], %1;\n" \
               "@!p bra WAIT_LOOP;\n}" ::"r"(bar), "r"(parity) : "memory")
__device__ __forceinline__ void mbar_wait(uint32_t bar, uint32_t parity) { MBAR_WAIT_ASM(""); }
__device__ __forceinline__ void mbar_wait_cluster(uint32_t bar, uint32_t parity) { MBAR_WAIT_ASM(".acquire.cluster"); }
__device__ __forceinline__ void st_async2(uint32_t addr, float a, float b, uint32_t bar) {
  asm volatile("st.async.weak.shared::cluster.mbarrier::complete_tx::bytes.v2.f32 [%0], {%1, %2}, [%3];"
               ::"r"(addr), "f"(a), "f"(b), "r"(bar) : "memory");
}
__device__ __forceinline__ uint64_t policy_evict_first() {
  uint64_t p; asm volatile("createpolicy.fractional.L2::evict_first.b64 %0, 1.0;" : "=l"(p)); return p;
}
__device__ __forceinline__ void tma_load2(uint32_t dst, const CUtensorMap* m, int c0, int c1, uint32_t bar) {
  asm volatile(ELECT "cp.async.bulk.tensor.2d.shared::cluster.global.mbarrier::complete_tx::bytes [%0], [%1, {%3, %4}], [%2];\n}"
               ::"r"(dst), "l"(m), "r"(bar), "r"(c0), "r"(c1) : "memory");
}
__device__ __forceinline__ void tma_load2_h(uint32_t dst, const CUtensorMap* m, int c0, int c1, uint32_t bar, uint64_t pol) {
  asm volatile(ELECT "cp.async.bulk.tensor.2d.shared::cluster.global.mbarrier::complete_tx::bytes.L2::cache_hint [%0], [%1, {%3, %4}], [%2], %5;\n}"
               ::"r"(dst), "l"(m), "r"(bar), "r"(c0), "r"(c1), "l"(pol) : "memory");
}
__device__ __forceinline__ void tma_load3(uint32_t dst, const CUtensorMap* m, int c0, int c1, int c2, uint32_t bar) {
  asm volatile(ELECT "cp.async.bulk.tensor.3d.shared::cluster.global.mbarrier::complete_tx::bytes [%0], [%1, {%3, %4, %5}], [%2];\n}"
               ::"r"(dst), "l"(m), "r"(bar), "r"(c0), "r"(c1), "r"(c2) : "memory");
}
__device__ __forceinline__ void tma_load3_h(uint32_t dst, const CUtensorMap* m, int c0, int c1, int c2, uint32_t bar, uint64_t pol) {
  asm volatile(ELECT "cp.async.bulk.tensor.3d.shared::cluster.global.mbarrier::complete_tx::bytes.L2::cache_hint [%0], [%1, {%3, %4, %5}], [%2], %6;\n}"
               ::"r"(dst), "l"(m), "r"(bar), "r"(c0), "r"(c1), "r"(c2), "l"(pol) : "memory");
}
__device__ __forceinline__ void tma_load3_mc(uint32_t dst, const CUtensorMap* m, int c0, int c1, int c2, uint32_t bar) {
  asm volatile(ELECT "cp.async.bulk.tensor.3d.shared::cluster.global.mbarrier::complete_tx::bytes.multicast::cluster [%0], [%1, {%3, %4, %5}], [%2], %6;\n}"
               ::"r"(dst), "l"(m), "r"(bar), "r"(c0), "r"(c1), "r"(c2), "h"((uint16_t)3) : "memory");
}
__device__ __forceinline__ void bulk_push(uint32_t dst, uint32_t src, uint32_t bytes, uint32_t bar) {
  asm volatile(ELECT "cp.async.bulk.shared::cluster.shared::cta.mbarrier::complete_tx::bytes [%0], [%1], %2, [%3];\n}"
               ::"r"(dst), "r"(src), "r"(bytes), "r"(bar) : "memory");
}
template <int N> __device__ __forceinline__ void regs_inc() { asm volatile("setmaxnreg.inc.sync.aligned.u32 %0;" ::"n"(N)); }
template <int N> __device__ __forceinline__ void regs_dec() { asm volatile("setmaxnreg.dec.sync.aligned.u32 %0;" ::"n"(N)); }
__device__ __forceinline__ void tma_store(const CUtensorMap* m, uint32_t src, int c0, int c1) {
  asm volatile(ELECT "cp.async.bulk.tensor.2d.global.shared::cta.bulk_group [%0, {%2, %3}], [%1];\n}"
               ::"l"(m), "r"(src), "r"(c0), "r"(c1) : "memory");
}
__device__ __forceinline__ void bulk_load_h(uint32_t dst, const void* src, uint32_t bytes, uint32_t bar, uint64_t pol) {
  asm volatile(ELECT "cp.async.bulk.shared::cluster.global.mbarrier::complete_tx::bytes.L2::cache_hint [%0], [%1], %2, [%3], %4;\n}"
               ::"r"(dst), "l"(src), "r"(bytes), "r"(bar), "l"(pol) : "memory");
}
__device__ __forceinline__ void bulk_store(void* dst, uint32_t src, uint32_t bytes) {
  asm volatile(ELECT "cp.async.bulk.global.shared::cta.bulk_group [%0], [%1], %2;\n}" ::"l"(dst), "r"(src), "r"(bytes) : "memory");
}
__device__ __forceinline__ void bulk_commit() { asm volatile("cp.async.bulk.commit_group;" ::: "memory"); }
__device__ __forceinline__ void bulk_wait_all() { asm volatile("cp.async.bulk.wait_group 0;" ::: "memory"); }
__device__ __forceinline__ void fence_async_smem() { asm volatile("fence.proxy.async.shared::cta;" ::: "memory"); }
__device__ __forceinline__ void fence_async_global() { asm volatile("fence.proxy.async.global;" ::: "memory"); }
__device__ __forceinline__ void prefetch_tmap(const CUtensorMap* m) { asm volatile("prefetch.tensormap [%0];" ::"l"(m) : "memory"); }
__device__ __forceinline__ void named_bar(int id, int n) { asm volatile("bar.sync %0, %1;" ::"r"(id), "r"(n) : "memory"); }
__device__ __forceinline__ bool bar_red_or(int id, int n, bool v) {
  uint32_t r;
  asm volatile("{\n.reg .pred p, q;\nsetp.ne.u32 q, %3, 0;\nbarrier.cta.red.or.pred p, %1, %2, q;\nselp.u32 %0, 1, 0, p;\n}"
               : "=r"(r) : "r"(id), "r"(n), "r"((uint32_t)v) : "memory");
  return r != 0;
}
__device__ __forceinline__ void cluster_arrive() { asm volatile("barrier.cluster.arrive.relaxed.aligned;" ::: "memory"); }
__device__ __forceinline__ void cluster_wait() { asm volatile("barrier.cluster.wait.aligned;" ::: "memory"); }
__device__ __forceinline__ unsigned ld_relaxed(const unsigned* p) {
  unsigned v; asm volatile("ld.relaxed.gpu.global.u32 %0, [%1];" : "=r"(v) : "l"(p) : "memory"); return v;
}
__device__ __forceinline__ uint4 ld_relaxed4(const uint4* p) {
  uint4 v; asm volatile("ld.relaxed.gpu.global.v4.u32 {%0, %1, %2, %3}, [%4];" : "=r"(v.x), "=r"(v.y), "=r"(v.z), "=r"(v.w) : "l"(p) : "memory"); return v;
}
__device__ __forceinline__ void st_relaxed(unsigned* p, unsigned v) {
  asm volatile("st.relaxed.gpu.global.u32 [%0], %1;" ::"l"(p), "r"(v) : "memory");
}
__device__ __forceinline__ uint2 ld_relaxed2(const void* p) {
  uint2 v; asm volatile("ld.relaxed.gpu.global.v2.u32 {%0, %1}, [%2];" : "=r"(v.x), "=r"(v.y) : "l"(p) : "memory"); return v;
}
__device__ __forceinline__ void st_relaxed4(uint4* p, uint4 v) {
  asm volatile("st.relaxed.gpu.global.v4.u32 [%0], {%1, %2, %3, %4};" ::"l"(p), "r"(v.x), "r"(v.y), "r"(v.z), "r"(v.w) : "memory");
}
__device__ __forceinline__ bool valid4(uint4 v) { return v.x != SENT && v.y != SENT && v.z != SENT && v.w != SENT; }
__device__ __forceinline__ uint4 poll4(const uint4* p) {
  uint4 v;
  uint32_t spins = 0;
#pragma unroll 1
  do { v = ld_relaxed4(p); } while (!valid4(v) && ++spins < SPIN_LIMIT);
  return v;
}
__device__ __forceinline__ void set_flag(unsigned* p, unsigned tag) {
  asm volatile(ELECT "st.release.gpu.global.u32 [%0], %1;\n}" ::"l"(p), "r"(tag) : "memory");
}
__device__ __forceinline__ void poll_flag(const unsigned* p, unsigned tag) {
#pragma unroll 1
  for (uint32_t spins = 0; !__all_sync(0xffffffffu, ld_relaxed(p) == tag) && spins < SPIN_LIMIT; spins++) {}
  asm volatile("fence.acquire.gpu;" ::: "memory");
}
__device__ __forceinline__ uint32_t enc(float x) { return __float_as_uint(x + 0.0f) ^ 0x80000000u; }
__device__ __forceinline__ float dec(uint32_t u) { return __uint_as_float(u ^ 0x80000000u); }
__device__ __forceinline__ uint32_t hadd_bf2(uint32_t a, uint32_t b) {
  uint32_t r; asm("add.rn.bf16x2 %0, %1, %2;" : "=r"(r) : "r"(a), "r"(b)); return r;
}
__device__ __forceinline__ uint32_t hsub_bf2(uint32_t a, uint32_t b) {
  uint32_t r; asm("sub.rn.bf16x2 %0, %1, %2;" : "=r"(r) : "r"(a), "r"(b)); return r;
}
__device__ __forceinline__ void wg_fence() { asm volatile("wgmma.fence.sync.aligned;" ::: "memory"); }
__device__ __forceinline__ void wg_commit() { asm volatile("wgmma.commit_group.sync.aligned;" ::: "memory"); }
template <int N> __device__ __forceinline__ void wg_wait() { asm volatile("wgmma.wait_group.sync.aligned %0;" ::"n"(N) : "memory"); }
template <int R> __device__ __forceinline__ void fence_regs(float* d) {
#pragma unroll
  for (int i = 0; i < R; i++) asm volatile("" : "+f"(d[i])::"memory");
}
template <int R> __device__ __forceinline__ void fence_regs_u(uint32_t* d) {
#pragma unroll
  for (int i = 0; i < R; i++) asm volatile("" : "+r"(d[i])::"memory");
}
__host__ __device__ constexpr uint32_t dlo(uint32_t addr, uint32_t lbo) { return ((addr & 0x3FFFF) >> 4) | ((lbo >> 4) << 16); }
constexpr uint32_t H128 = 0x40000040u, H64 = 0x80000020u;
__device__ __forceinline__ void stsm_x4(uint32_t addr, uint32_t r0, uint32_t r1, uint32_t r2, uint32_t r3) {
  asm volatile("stmatrix.sync.aligned.m8n8.x4.shared.b16 [%0], {%1, %2, %3, %4};"
               ::"r"(addr), "r"(r0), "r"(r1), "r"(r2), "r"(r3) : "memory");
}
__device__ __forceinline__ void ldsm_x4(uint32_t addr, uint32_t& r0, uint32_t& r1, uint32_t& r2, uint32_t& r3) {
  asm volatile("ldmatrix.sync.aligned.m8n8.x4.shared.b16 {%0, %1, %2, %3}, [%4];"
               : "=r"(r0), "=r"(r1), "=r"(r2), "=r"(r3) : "r"(addr) : "memory");
}
__device__ __forceinline__ void ldsm_x4_t(uint32_t addr, uint32_t& r0, uint32_t& r1, uint32_t& r2, uint32_t& r3) {
  asm volatile("ldmatrix.sync.aligned.m8n8.x4.trans.shared.b16 {%0, %1, %2, %3}, [%4];"
               : "=r"(r0), "=r"(r1), "=r"(r2), "=r"(r3) : "r"(addr) : "memory");
}
__device__ __forceinline__ void mma_16816(float* d, uint32_t a0, uint32_t a1, uint32_t a2, uint32_t a3, uint32_t b0, uint32_t b1) {
  asm volatile("mma.sync.aligned.m16n8k16.row.col.f32.bf16.bf16.f32 {%0, %1, %2, %3}, {%4, %5, %6, %7}, {%8, %9}, {%0, %1, %2, %3};"
               : "+f"(d[0]), "+f"(d[1]), "+f"(d[2]), "+f"(d[3]) : "r"(a0), "r"(a1), "r"(a2), "r"(a3), "r"(b0), "r"(b1));
}
__device__ __forceinline__ void spin_cycles(int n) {
  const int t0 = (int)clock();
#pragma unroll 1
  while ((int)clock() - t0 < n) {}
}
__device__ __forceinline__ uint32_t pack_bf16(float lo, float hi) {
  uint32_t r; asm("cvt.rn.bf16x2.f32 %0, %1, %2;" : "=r"(r) : "f"(hi), "f"(lo)); return r;
}
__device__ __forceinline__ float bf_lo(uint32_t v) { return __uint_as_float(v << 16); }
__device__ __forceinline__ float bf_hi(uint32_t v) { return __uint_as_float(v & 0xffff0000u); }
__device__ __forceinline__ float rbf(float x) { return __bfloat162float(__float2bfloat16_rn(x)); }
__device__ __forceinline__ float ex2(float x) { float y; asm("ex2.approx.ftz.f32 %0, %1;" : "=f"(y) : "f"(x)); return y; }
__device__ __forceinline__ float rcp(float x) { float y; asm("rcp.approx.ftz.f32 %0, %1;" : "=f"(y) : "f"(x)); return y; }
__device__ __forceinline__ uint32_t shl_clamp(uint32_t v, uint32_t n) {
  uint32_t r; asm("shl.b32 %0, %1, %2;" : "=r"(r) : "r"(v), "r"(n)); return r;
}
__device__ __forceinline__ float warp_sum(float v) {
#pragma unroll
  for (int o = 16; o > 0; o >>= 1) v += __shfl_xor_sync(0xffffffffu, v, o);
  return v;
}
__device__ __forceinline__ float ln_inv(float var) {
  float r;
  asm("sqrt.approx.ftz.f32 %0, %1;" : "=f"(r) : "f"(rbf(rbf(var) + LN_EPS)));
  asm("rcp.approx.ftz.f32 %0, %1;" : "=f"(r) : "f"(rbf(r)));
  return r;
}
__device__ __forceinline__ uint32_t ln_pair(uint32_t x, uint32_t mean2, float inv) {
  const uint32_t d = hsub_bf2(x, mean2);
  return pack_bf16(bf_lo(d) * inv, bf_hi(d) * inv);
}
__device__ __forceinline__ uint32_t add_ln_pair(uint32_t x, uint32_t mean2, float inv) { return hadd_bf2(x, ln_pair(x, mean2, inv)); }
__device__ __forceinline__ uint32_t router_key(float r_bf, int row) {
  uint32_t u = __float_as_uint(r_bf);
  u = (u & 0x80000000u) ? ~u : (u | 0x80000000u);
  return (u & 0xFFFF0000u) | 0x8000u | (uint32_t)(SEQ - 1 - row);
}

template <uint32_t HA = 0x40000040u, uint32_t HB = 0x40000040u>
__device__ __forceinline__ void wg_ss192t(float* d, uint32_t da, uint32_t db, int scale_d) {
  asm volatile("{\n.reg .pred p;\n.reg .b64 dA, dB;\nmov.b64 dA, {%96, %99};\nmov.b64 dB, {%97, %100};\nsetp.ne.b32 p, %98, 0;\n"
    "wgmma.mma_async.sync.aligned.m64n192k16.f32.bf16.bf16 "
    "{%0, %1, %2, %3, %4, %5, %6, %7, %8, %9, %10, %11, %12, %13, %14, %15, "
    "%16, %17, %18, %19, %20, %21, %22, %23, %24, %25, %26, %27, %28, %29, %30, %31, "
    "%32, %33, %34, %35, %36, %37, %38, %39, %40, %41, %42, %43, %44, %45, %46, %47, "
    "%48, %49, %50, %51, %52, %53, %54, %55, %56, %57, %58, %59, %60, %61, %62, %63, "
    "%64, %65, %66, %67, %68, %69, %70, %71, %72, %73, %74, %75, %76, %77, %78, %79, "
    "%80, %81, %82, %83, %84, %85, %86, %87, %88, %89, %90, %91, %92, %93, %94, %95}, "
    "dA, dB, p, 1, 1, 0, 1;\n}\n"
    : "+f"(d[0]), "+f"(d[1]), "+f"(d[2]), "+f"(d[3]), "+f"(d[4]), "+f"(d[5]), "+f"(d[6]), "+f"(d[7]),
      "+f"(d[8]), "+f"(d[9]), "+f"(d[10]), "+f"(d[11]), "+f"(d[12]), "+f"(d[13]), "+f"(d[14]), "+f"(d[15]),
      "+f"(d[16]), "+f"(d[17]), "+f"(d[18]), "+f"(d[19]), "+f"(d[20]), "+f"(d[21]), "+f"(d[22]), "+f"(d[23]),
      "+f"(d[24]), "+f"(d[25]), "+f"(d[26]), "+f"(d[27]), "+f"(d[28]), "+f"(d[29]), "+f"(d[30]), "+f"(d[31]),
      "+f"(d[32]), "+f"(d[33]), "+f"(d[34]), "+f"(d[35]), "+f"(d[36]), "+f"(d[37]), "+f"(d[38]), "+f"(d[39]),
      "+f"(d[40]), "+f"(d[41]), "+f"(d[42]), "+f"(d[43]), "+f"(d[44]), "+f"(d[45]), "+f"(d[46]), "+f"(d[47]),
      "+f"(d[48]), "+f"(d[49]), "+f"(d[50]), "+f"(d[51]), "+f"(d[52]), "+f"(d[53]), "+f"(d[54]), "+f"(d[55]),
      "+f"(d[56]), "+f"(d[57]), "+f"(d[58]), "+f"(d[59]), "+f"(d[60]), "+f"(d[61]), "+f"(d[62]), "+f"(d[63]),
      "+f"(d[64]), "+f"(d[65]), "+f"(d[66]), "+f"(d[67]), "+f"(d[68]), "+f"(d[69]), "+f"(d[70]), "+f"(d[71]),
      "+f"(d[72]), "+f"(d[73]), "+f"(d[74]), "+f"(d[75]), "+f"(d[76]), "+f"(d[77]), "+f"(d[78]), "+f"(d[79]),
      "+f"(d[80]), "+f"(d[81]), "+f"(d[82]), "+f"(d[83]), "+f"(d[84]), "+f"(d[85]), "+f"(d[86]), "+f"(d[87]),
      "+f"(d[88]), "+f"(d[89]), "+f"(d[90]), "+f"(d[91]), "+f"(d[92]), "+f"(d[93]), "+f"(d[94]), "+f"(d[95])
    : "r"(da), "r"(db), "r"(scale_d), "n"(HA), "n"(HB));
}
template <uint32_t HA = 0x40000040u, uint32_t HB = 0x40000040u>
__device__ __forceinline__ void wg_ss192t_z(float* d, uint32_t da, uint32_t db) {
  asm volatile("{\n.reg .pred p;\n.reg .b64 dA, dB;\nmov.b64 dA, {%96, %98};\nmov.b64 dB, {%97, %99};\nsetp.ne.b32 p, 0, 0;\n"
    "wgmma.mma_async.sync.aligned.m64n192k16.f32.bf16.bf16 "
    "{%0, %1, %2, %3, %4, %5, %6, %7, %8, %9, %10, %11, %12, %13, %14, %15, "
    "%16, %17, %18, %19, %20, %21, %22, %23, %24, %25, %26, %27, %28, %29, %30, %31, "
    "%32, %33, %34, %35, %36, %37, %38, %39, %40, %41, %42, %43, %44, %45, %46, %47, "
    "%48, %49, %50, %51, %52, %53, %54, %55, %56, %57, %58, %59, %60, %61, %62, %63, "
    "%64, %65, %66, %67, %68, %69, %70, %71, %72, %73, %74, %75, %76, %77, %78, %79, "
    "%80, %81, %82, %83, %84, %85, %86, %87, %88, %89, %90, %91, %92, %93, %94, %95}, "
    "dA, dB, p, 1, 1, 0, 1;\n}\n"
    : "=f"(d[0]), "=f"(d[1]), "=f"(d[2]), "=f"(d[3]), "=f"(d[4]), "=f"(d[5]), "=f"(d[6]), "=f"(d[7]),
      "=f"(d[8]), "=f"(d[9]), "=f"(d[10]), "=f"(d[11]), "=f"(d[12]), "=f"(d[13]), "=f"(d[14]), "=f"(d[15]),
      "=f"(d[16]), "=f"(d[17]), "=f"(d[18]), "=f"(d[19]), "=f"(d[20]), "=f"(d[21]), "=f"(d[22]), "=f"(d[23]),
      "=f"(d[24]), "=f"(d[25]), "=f"(d[26]), "=f"(d[27]), "=f"(d[28]), "=f"(d[29]), "=f"(d[30]), "=f"(d[31]),
      "=f"(d[32]), "=f"(d[33]), "=f"(d[34]), "=f"(d[35]), "=f"(d[36]), "=f"(d[37]), "=f"(d[38]), "=f"(d[39]),
      "=f"(d[40]), "=f"(d[41]), "=f"(d[42]), "=f"(d[43]), "=f"(d[44]), "=f"(d[45]), "=f"(d[46]), "=f"(d[47]),
      "=f"(d[48]), "=f"(d[49]), "=f"(d[50]), "=f"(d[51]), "=f"(d[52]), "=f"(d[53]), "=f"(d[54]), "=f"(d[55]),
      "=f"(d[56]), "=f"(d[57]), "=f"(d[58]), "=f"(d[59]), "=f"(d[60]), "=f"(d[61]), "=f"(d[62]), "=f"(d[63]),
      "=f"(d[64]), "=f"(d[65]), "=f"(d[66]), "=f"(d[67]), "=f"(d[68]), "=f"(d[69]), "=f"(d[70]), "=f"(d[71]),
      "=f"(d[72]), "=f"(d[73]), "=f"(d[74]), "=f"(d[75]), "=f"(d[76]), "=f"(d[77]), "=f"(d[78]), "=f"(d[79]),
      "=f"(d[80]), "=f"(d[81]), "=f"(d[82]), "=f"(d[83]), "=f"(d[84]), "=f"(d[85]), "=f"(d[86]), "=f"(d[87]),
      "=f"(d[88]), "=f"(d[89]), "=f"(d[90]), "=f"(d[91]), "=f"(d[92]), "=f"(d[93]), "=f"(d[94]), "=f"(d[95])
    : "r"(da), "r"(db), "n"(HA), "n"(HB));
}
template <uint32_t HA = 0x40000040u, uint32_t HB = 0x40000040u>
__device__ __forceinline__ void wg_ss128t(float* d, uint32_t da, uint32_t db, int scale_d) {
  asm volatile("{\n.reg .pred p;\n.reg .b64 dA, dB;\nmov.b64 dA, {%64, %67};\nmov.b64 dB, {%65, %68};\nsetp.ne.b32 p, %66, 0;\n"
    "wgmma.mma_async.sync.aligned.m64n128k16.f32.bf16.bf16 "
    "{%0, %1, %2, %3, %4, %5, %6, %7, %8, %9, %10, %11, %12, %13, %14, %15, "
    "%16, %17, %18, %19, %20, %21, %22, %23, %24, %25, %26, %27, %28, %29, %30, %31, "
    "%32, %33, %34, %35, %36, %37, %38, %39, %40, %41, %42, %43, %44, %45, %46, %47, "
    "%48, %49, %50, %51, %52, %53, %54, %55, %56, %57, %58, %59, %60, %61, %62, %63}, "
    "dA, dB, p, 1, 1, 0, 1;\n}\n"
    : "+f"(d[0]), "+f"(d[1]), "+f"(d[2]), "+f"(d[3]), "+f"(d[4]), "+f"(d[5]), "+f"(d[6]), "+f"(d[7]),
      "+f"(d[8]), "+f"(d[9]), "+f"(d[10]), "+f"(d[11]), "+f"(d[12]), "+f"(d[13]), "+f"(d[14]), "+f"(d[15]),
      "+f"(d[16]), "+f"(d[17]), "+f"(d[18]), "+f"(d[19]), "+f"(d[20]), "+f"(d[21]), "+f"(d[22]), "+f"(d[23]),
      "+f"(d[24]), "+f"(d[25]), "+f"(d[26]), "+f"(d[27]), "+f"(d[28]), "+f"(d[29]), "+f"(d[30]), "+f"(d[31]),
      "+f"(d[32]), "+f"(d[33]), "+f"(d[34]), "+f"(d[35]), "+f"(d[36]), "+f"(d[37]), "+f"(d[38]), "+f"(d[39]),
      "+f"(d[40]), "+f"(d[41]), "+f"(d[42]), "+f"(d[43]), "+f"(d[44]), "+f"(d[45]), "+f"(d[46]), "+f"(d[47]),
      "+f"(d[48]), "+f"(d[49]), "+f"(d[50]), "+f"(d[51]), "+f"(d[52]), "+f"(d[53]), "+f"(d[54]), "+f"(d[55]),
      "+f"(d[56]), "+f"(d[57]), "+f"(d[58]), "+f"(d[59]), "+f"(d[60]), "+f"(d[61]), "+f"(d[62]), "+f"(d[63])
    : "r"(da), "r"(db), "r"(scale_d), "n"(HA), "n"(HB));
}
template <uint32_t HB = 0x40000040u>
__device__ __forceinline__ void wg_rs64(float* d, uint32_t a0, uint32_t a1, uint32_t a2, uint32_t a3, uint32_t db, int scale_d) {
  asm volatile("{\n.reg .pred p;\n.reg .b64 dB;\nmov.b64 dB, {%36, %38};\nsetp.ne.b32 p, %37, 0;\n"
    "wgmma.mma_async.sync.aligned.m64n64k16.f32.bf16.bf16 "
    "{%0, %1, %2, %3, %4, %5, %6, %7, %8, %9, %10, %11, %12, %13, %14, %15, "
    "%16, %17, %18, %19, %20, %21, %22, %23, %24, %25, %26, %27, %28, %29, %30, %31}, "
    "{%32, %33, %34, %35}, dB, p, 1, 1, 0;\n}\n"
    : "+f"(d[0]), "+f"(d[1]), "+f"(d[2]), "+f"(d[3]), "+f"(d[4]), "+f"(d[5]), "+f"(d[6]), "+f"(d[7]),
      "+f"(d[8]), "+f"(d[9]), "+f"(d[10]), "+f"(d[11]), "+f"(d[12]), "+f"(d[13]), "+f"(d[14]), "+f"(d[15]),
      "+f"(d[16]), "+f"(d[17]), "+f"(d[18]), "+f"(d[19]), "+f"(d[20]), "+f"(d[21]), "+f"(d[22]), "+f"(d[23]),
      "+f"(d[24]), "+f"(d[25]), "+f"(d[26]), "+f"(d[27]), "+f"(d[28]), "+f"(d[29]), "+f"(d[30]), "+f"(d[31])
    : "r"(a0), "r"(a1), "r"(a2), "r"(a3), "r"(db), "r"(scale_d), "n"(HB));
}
template <uint32_t HB = 0x40000040u>
__device__ __forceinline__ void wg_rs64_z(float* d, uint32_t a0, uint32_t a1, uint32_t a2, uint32_t a3, uint32_t db) {
  asm volatile("{\n.reg .pred p;\n.reg .b64 dB;\nmov.b64 dB, {%36, %37};\nsetp.ne.b32 p, 0, 0;\n"
    "wgmma.mma_async.sync.aligned.m64n64k16.f32.bf16.bf16 "
    "{%0, %1, %2, %3, %4, %5, %6, %7, %8, %9, %10, %11, %12, %13, %14, %15, "
    "%16, %17, %18, %19, %20, %21, %22, %23, %24, %25, %26, %27, %28, %29, %30, %31}, "
    "{%32, %33, %34, %35}, dB, p, 1, 1, 0;\n}\n"
    : "=f"(d[0]), "=f"(d[1]), "=f"(d[2]), "=f"(d[3]), "=f"(d[4]), "=f"(d[5]), "=f"(d[6]), "=f"(d[7]),
      "=f"(d[8]), "=f"(d[9]), "=f"(d[10]), "=f"(d[11]), "=f"(d[12]), "=f"(d[13]), "=f"(d[14]), "=f"(d[15]),
      "=f"(d[16]), "=f"(d[17]), "=f"(d[18]), "=f"(d[19]), "=f"(d[20]), "=f"(d[21]), "=f"(d[22]), "=f"(d[23]),
      "=f"(d[24]), "=f"(d[25]), "=f"(d[26]), "=f"(d[27]), "=f"(d[28]), "=f"(d[29]), "=f"(d[30]), "=f"(d[31])
    : "r"(a0), "r"(a1), "r"(a2), "r"(a3), "r"(db), "n"(HB));
}
template <uint32_t HB = 0x40000040u>
__device__ __forceinline__ void wg_rs32(float* d, uint32_t a0, uint32_t a1, uint32_t a2, uint32_t a3, uint32_t db, int scale_d) {
  asm volatile("{\n.reg .pred p;\n.reg .b64 dB;\nmov.b64 dB, {%20, %22};\nsetp.ne.b32 p, %21, 0;\n"
    "wgmma.mma_async.sync.aligned.m64n32k16.f32.bf16.bf16 "
    "{%0, %1, %2, %3, %4, %5, %6, %7, %8, %9, %10, %11, %12, %13, %14, %15}, "
    "{%16, %17, %18, %19}, dB, p, 1, 1, 0;\n}\n"
    : "+f"(d[0]), "+f"(d[1]), "+f"(d[2]), "+f"(d[3]), "+f"(d[4]), "+f"(d[5]), "+f"(d[6]), "+f"(d[7]),
      "+f"(d[8]), "+f"(d[9]), "+f"(d[10]), "+f"(d[11]), "+f"(d[12]), "+f"(d[13]), "+f"(d[14]), "+f"(d[15])
    : "r"(a0), "r"(a1), "r"(a2), "r"(a3), "r"(db), "r"(scale_d), "n"(HB));
}
template <uint32_t HB = 0x40000040u>
__device__ __forceinline__ void wg_rs32_z(float* d, uint32_t a0, uint32_t a1, uint32_t a2, uint32_t a3, uint32_t db) {
  asm volatile("{\n.reg .pred p;\n.reg .b64 dB;\nmov.b64 dB, {%20, %21};\nsetp.ne.b32 p, 0, 0;\n"
    "wgmma.mma_async.sync.aligned.m64n32k16.f32.bf16.bf16 "
    "{%0, %1, %2, %3, %4, %5, %6, %7, %8, %9, %10, %11, %12, %13, %14, %15}, "
    "{%16, %17, %18, %19}, dB, p, 1, 1, 0;\n}\n"
    : "=f"(d[0]), "=f"(d[1]), "=f"(d[2]), "=f"(d[3]), "=f"(d[4]), "=f"(d[5]), "=f"(d[6]), "=f"(d[7]),
      "=f"(d[8]), "=f"(d[9]), "=f"(d[10]), "=f"(d[11]), "=f"(d[12]), "=f"(d[13]), "=f"(d[14]), "=f"(d[15])
    : "r"(a0), "r"(a1), "r"(a2), "r"(a3), "r"(db), "n"(HB));
}
template <uint32_t HB = 0x40000040u>
__device__ __forceinline__ void wg_rs40t(float* d, uint32_t a0, uint32_t a1, uint32_t a2, uint32_t a3, uint32_t db, int scale_d) {
  asm volatile("{\n.reg .pred p;\n.reg .b64 dB;\nmov.b64 dB, {%24, %26};\nsetp.ne.b32 p, %25, 0;\n"
    "wgmma.mma_async.sync.aligned.m64n40k16.f32.bf16.bf16 "
    "{%0, %1, %2, %3, %4, %5, %6, %7, %8, %9, %10, %11, %12, %13, %14, %15, "
    "%16, %17, %18, %19}, "
    "{%20, %21, %22, %23}, dB, p, 1, 1, 1;\n}\n"
    : "+f"(d[0]), "+f"(d[1]), "+f"(d[2]), "+f"(d[3]), "+f"(d[4]), "+f"(d[5]), "+f"(d[6]), "+f"(d[7]),
      "+f"(d[8]), "+f"(d[9]), "+f"(d[10]), "+f"(d[11]), "+f"(d[12]), "+f"(d[13]), "+f"(d[14]), "+f"(d[15]),
      "+f"(d[16]), "+f"(d[17]), "+f"(d[18]), "+f"(d[19])
    : "r"(a0), "r"(a1), "r"(a2), "r"(a3), "r"(db), "r"(scale_d), "n"(HB));
}
template <uint32_t HB = 0x40000040u>
__device__ __forceinline__ void wg_rs40t_z(float* d, uint32_t a0, uint32_t a1, uint32_t a2, uint32_t a3, uint32_t db) {
  asm volatile("{\n.reg .pred p;\n.reg .b64 dB;\nmov.b64 dB, {%24, %25};\nsetp.ne.b32 p, 0, 0;\n"
    "wgmma.mma_async.sync.aligned.m64n40k16.f32.bf16.bf16 "
    "{%0, %1, %2, %3, %4, %5, %6, %7, %8, %9, %10, %11, %12, %13, %14, %15, "
    "%16, %17, %18, %19}, "
    "{%20, %21, %22, %23}, dB, p, 1, 1, 1;\n}\n"
    : "=f"(d[0]), "=f"(d[1]), "=f"(d[2]), "=f"(d[3]), "=f"(d[4]), "=f"(d[5]), "=f"(d[6]), "=f"(d[7]),
      "=f"(d[8]), "=f"(d[9]), "=f"(d[10]), "=f"(d[11]), "=f"(d[12]), "=f"(d[13]), "=f"(d[14]), "=f"(d[15]),
      "=f"(d[16]), "=f"(d[17]), "=f"(d[18]), "=f"(d[19])
    : "r"(a0), "r"(a1), "r"(a2), "r"(a3), "r"(db), "n"(HB));
}

constexpr uint32_t SOFF = 1024;
constexpr int STG = 57344, SL_W = 32768, SL_HD = 12288, SL_F = 3 * STG, X_ST = 131072;
__host__ __device__ constexpr int kv_off(int h, int b) { return 16384 + h * 81920 + (b ^ (6 * h)) * 8192; }
__host__ __device__ constexpr int qo_off(int h, int qb) { return (qb >> 1) * 81920 + h * 8192 + (qb & 1) * 4096; }
__host__ __device__ constexpr int wo_off(int st) { return 16384 + st * 32768 + (st >> 1) * 16384; }
constexpr int OFF_ONES = 4 * STG;
constexpr int OFF_PATCH = OFF_ONES + 1024;
constexpr int OFF_CS = OFF_PATCH + 768;
constexpr int OFF_BAR = OFF_CS + 768;
constexpr int OFF_MISC = OFF_BAR + 416;
constexpr int SMEM_BYTES = OFF_MISC + 96;
enum { B_FULL = 0, B_EMPTY = 6, B_HALO = 12, B_CS = 15, B_KVREADY, B_QDONE = B_KVREADY + 2, B_QREADY, B_OST, B_ADONE = B_OST + 2,
       B_QFREE, B_WS, B_WFULL, B_WEMPTY = B_WFULL + 4, B_GU = B_WEMPTY + 4, B_RES = B_GU + 2, B_DN,
       B_HX = B_DN + 2, B_RST, B_E23, B_UNIT, B_COUNT = B_UNIT + 8 };
static_assert(B_COUNT <= 52, "barrier area");
__host__ __device__ constexpr int bar_count(int i) {
  return i >= B_EMPTY && i < B_HALO ? 17 : i == B_CS ? 5 : i == B_QFREE ? 16
       : i == B_KVREADY || i == B_KVREADY + 1 || i == B_QREADY ? 8 : i == B_E23 ? 9 : i == B_ADONE ? 32 : i == B_OST ? 2 : i >= B_UNIT ? 4
       : i == B_QDONE || (i >= B_WEMPTY && i < B_GU) ? 16 : i == B_RST ? 4 : i == B_RES ? 2 : 1;
}
enum { M_KEY = 0, M_MEAN, M_INV, M_WSUM, M_TAG, M_SEL0, M_PMEAN, M_PINV, M_XQ = 8, M_KEYS = 12, M_PROG = 20 };
constexpr int FFN_PIECE = 14336;
constexpr int T_XS = 163840, T_HP = T_XS + 1024;
constexpr float LSUM_MIN = 5.421010862427522e-20f, LSUM_MAX = 1.8446744073709552e19f;
constexpr float SM_C = 0.17677669529663687f * 1.4426950408889634f;
constexpr uint32_t VSTEP = 64u - (64u << 16);
constexpr int DELAY_P = 600, DELAY_S = 2000, DELAY_Y = 500, P1_DELAY = 800, X_STAGGER = 500;
constexpr int GU_PACE = 2000, GU_PACE1 = 1700, GUB_PACE = 900, WS_PACE = 500;
constexpr int RES_K = 4;

struct Params {
  CUtensorMap mapA[2], mapW, mapWo, mapRes[2], mapXst[2], mapG, mapU, mapD, mapWs;
  const bf16 *w_r, *w_d;
  bf16* out;
  int role[128];
};

template <int N> __device__ __forceinline__ void exp_pack(const float* s, uint32_t* p) {
#pragma unroll
  for (int b = 0; b < N; b++) {
    p[2 * b] = pack_bf16(ex2(s[4 * b]), ex2(s[4 * b + 1]));
    p[2 * b + 1] = pack_bf16(ex2(s[4 * b + 2]), ex2(s[4 * b + 3]));
  }
}
template <int KIND> __device__ __forceinline__ void edge16(const float* sd, const float* st, uint32_t* pd, uint32_t* pt, int dl, uint32_t mt) {
  if (KIND == 0) { exp_pack<2>(sd, pd); pt[0] = pt[1] = pt[2] = pt[3] = 0; }
  else if (KIND == 1) { exp_pack<2>(st, pt); pd[0] = pd[1] = pd[2] = pd[3] = 0; }
  else {
    const uint32_t a = pack_bf16(ex2(dl >= 0 ? sd[0] : st[0]), ex2(dl >= 1 ? sd[1] : st[1]));
    const uint32_t c = pack_bf16(ex2(dl >= 0 ? sd[6] : st[6]), ex2(dl >= 1 ? sd[7] : st[7]));
    pd[0] = a & ~mt; pt[0] = a & mt; pd[3] = c & ~mt; pt[3] = c & mt;
    pd[1] = pack_bf16(ex2(sd[2]), ex2(sd[3])); pt[1] = 0;
    pt[2] = pack_bf16(ex2(st[4]), ex2(st[5])); pd[2] = 0;
  }
}
__device__ __forceinline__ void edge32(const float* sd, const float* st, uint32_t* pd, uint32_t* pt, int rel, int dl, uint32_t mt) {
  if (rel > 1) { edge16<0>(sd, st, pd, pt, dl, mt); edge16<0>(sd + 8, st + 8, pd + 4, pt + 4, dl, mt); }
  else if (rel == 1) { edge16<0>(sd, st, pd, pt, dl, mt); edge16<2>(sd + 8, st + 8, pd + 4, pt + 4, dl, mt); }
  else if (rel == 0) { edge16<2>(sd, st, pd, pt, dl, mt); edge16<1>(sd + 8, st + 8, pd + 4, pt + 4, dl, mt); }
  else { edge16<1>(sd, st, pd, pt, dl, mt); edge16<1>(sd + 8, st + 8, pd + 4, pt + 4, dl, mt); }
}
__device__ __forceinline__ void qk64(float* s, const uint32_t* qf, uint32_t kd) {
  wg_rs64_z<H64>(s, qf[0], qf[1], qf[2], qf[3], kd);
  wg_rs64<H64>(s, qf[4], qf[5], qf[6], qf[7], kd + 2, 1);
}
__device__ __forceinline__ void qk32x2(float* a, float* b, const uint32_t* qf, uint32_t ka, uint32_t kb) {
  wg_rs32_z<H64>(a, qf[0], qf[1], qf[2], qf[3], ka); wg_rs32_z<H64>(b, qf[0], qf[1], qf[2], qf[3], kb);
  wg_rs32<H64>(a, qf[4], qf[5], qf[6], qf[7], ka + 2, 1); wg_rs32<H64>(b, qf[4], qf[5], qf[6], qf[7], kb + 2, 1);
}
__device__ __forceinline__ void pv32(float* o, const uint32_t* p, uint32_t vd) {
  wg_rs40t<H64>(o, p[0], p[1], p[2], p[3], vd, 1);
  wg_rs40t<H64>(o, p[4], p[5], p[6], p[7], vd + VSTEP, 1);
}

__device__ __forceinline__ void fma8(float* d, uint4 w, float x) {
  d[0] += x * bf_lo(w.x); d[1] += x * bf_hi(w.x); d[2] += x * bf_lo(w.y); d[3] += x * bf_hi(w.y);
  d[4] += x * bf_lo(w.z); d[5] += x * bf_hi(w.z); d[6] += x * bf_lo(w.w); d[7] += x * bf_hi(w.w);
}

__device__ __forceinline__ int fresh_tid() { int r; asm volatile("mov.u32 %0, %%tid.x;" : "=r"(r)); return r; }
__device__ __forceinline__ int fresh_bid() { int r; asm volatile("mov.u32 %0, %%ctaid.x;" : "=r"(r)); return r; }
#define PHASE_IDS                                                                                                              \
  const uint32_t sbase = smem_u32(smem);                                                                                       \
  const int tid = fresh_tid(), bid = P.role[fresh_bid()];                                                                      \
  const int warp = __shfl_sync(0xffffffffu, tid >> 5, 0), lane = tid & 31;                                                     \
  const int rank = bid & 1, rb = bid & 7, hp = bid >> 3, cl = (rb >> 1) * 16 + hp;                  \
  const int mb = 2 * rb + (hp >> 3), nb = hp & 7;                                            \
  const int wg = warp >> 2, wi = warp & 3, g = lane >> 2, q = lane & 3;                                                        \
  const int mi = lane >> 3, srow = wi * 16 + (mi & 1) * 8 + (lane & 7);      \
  auto bar = [&](int i) { return sbase + OFF_BAR + 8 * i; };                                                                   \
  volatile uint32_t* s_misc = (volatile uint32_t*)(smem + OFF_MISC);                                                           \
  auto load_w = [&](int s, int kt) {                           \
    mbar_expect_tx(bar(B_FULL + s), (s & 1) ? SL_HD : SL_HD + 32768);                        \
    tma_load3_mc(sbase + (s >> 1) * STG + SL_W + (s & 1) * SL_HD + rank * 6144, &P.mapW, hp * 64, kt * 32 + rank * 16, 0, bar(B_FULL + s));              \
  };                                                                                                                           \
  auto load_a = [&](int s, int kt, int layer) { tma_load2(sbase + (s >> 1) * STG, &P.mapA[layer], kt * 32, rb * 256, bar(B_FULL + s)); }; \
  auto load_wo = [&](int k) {                                                 \
    mbar_expect_tx(bar(B_WFULL + (k & 3)), 32768);                                                                             \
    tma_load3_mc(sbase + wo_off(k & 3) + 16384 + rank * 8192, &P.mapWo, nb * 128 + rank * 64, (k >> 3) * 32, (k & 7) * 2, bar(B_WFULL + (k & 3))); \
  };                                                                                                                           \
  auto load_o = [&](int k) {                                                            \
    bulk_load_h(sbase + wo_off(k & 3), g_o + (size_t)(mb * 16 + k) * 16384, 16384, bar(B_WFULL + (k & 3)), policy_evict_first());                    \
  };                                                                                                                           \
  auto load_res = [&](int half, int layer) {      \
    mbar_expect_tx(bar(B_RES), 16384);                                                                                         \
    tma_load2_h(sbase + qo_off(half, 0), &P.mapRes[layer], nb * 128 + half * 64, mb * 128, bar(B_RES), policy_evict_first());  \
    tma_load2_h(sbase + qo_off(half, 2), &P.mapRes[layer], nb * 128 + half * 64, mb * 128 + 64, bar(B_RES), policy_evict_first()); \
  };                                                                                                                           \
  auto store_tile = [&](int layer, int skip, bool wait) {                                           \
    _Pragma("unroll 1")                                                                                                        \
    for (int j = 0; j < 4; j++)                                                                                                \
      if ((j & 1) != skip) tma_store(&P.mapXst[layer], sbase + X_ST + (j & 1) * 16384 + (j >> 1) * 8192, nb * 128 + (j >> 1) * 64, mb * 128 + (j & 1) * 64); \
    bulk_commit();                                                                                                             \
    if (wait) bulk_wait_all();                                                                                                 \
  };                                                                                                                           \
  auto load_ws = [&](int pace) {                                    \
    mbar_expect_tx(bar(B_WS), 4 * SL_HD);                                                                                      \
    _Pragma("unroll 1")                                                                                                        \
    for (int j = 0; j < 4; j++) {                                                                                              \
      tma_load3(sbase + SL_F + j * SL_HD, &P.mapWs, hp * 64, rb * 128 + j * 32, 0, bar(B_WS));                                 \
      if (pace) spin_cycles(pace);                                                                                             \
    }                                                                                                                          \
  };                                                                                                                           \
  auto load_gu = [&](int half, int pace) {                             \
    mbar_expect_tx(bar(B_GU + half), 4 * FFN_PIECE);                                                                           \
    _Pragma("unroll 1")                                                                                                        \
    for (int j = 0; j < 4; j++) {                                                                                              \
      tma_load2_h(sbase + SL_F + j * FFN_PIECE, &P.mapG + (j >> 1), cl * 56, rank * 512 + half * 256 + (j & 1) * 128, bar(B_GU + half), policy_evict_first()); \
      if (j < 3) spin_cycles(pace);                                                                                            \
    }                                                                                                                          \
  };                                                                                                                           \
  auto fetch_gu = [&](uint32_t* a, int ks, int ct) {                 \
    ldsm_x4_t(sbase + SL_F + (mi & 1) * 2 * FFN_PIECE + (ks * 16 + (mi >> 1) * 8 + (lane & 7)) * 112 + ct * 16, a[0], a[1], a[2], a[3]); \
  };                                                                                                                           \
  auto send_gu = [&](float gate, float up, int ct, int part) {        \
    const int u = 8 * ct + g, own = u >= 28;                                                                                   \
    if (q == 0) st_async2(mapa(sbase + T_HP + ((rank * 5 + part) * 28 + u - 28 * own) * 8, own), gate, up, mapa(bar(B_HX), own)); \
  };                                                                                                                           \
  auto hidden = [&]() {                                     \
    const float2* hpart = (const float2*)(smem + T_HP) + min(lane, 27);                                                        \
    float gs[2] = {0.f, 0.f}, us[2] = {0.f, 0.f};                                                                              \
    _Pragma("unroll")                                                                                                          \
    for (int j = 0; j < 10; j++) { const float2 v = hpart[j * 28]; gs[j & 1] += v.x; us[j & 1] += v.y; }                       \
    const float gb = rbf(gs[0] + gs[1]), ub = rbf(us[0] + us[1]);                                                              \
    return lane < 28 ? rbf(__fdividef(gb, 1.f + __expf(-gb))) * ub : 0.f;                                                      \
  };                                                                                                                           \
  (void)load_wo; (void)load_o; (void)load_res; (void)store_tile; (void)fetch_gu; (void)load_ws; (void)load_gu; (void)send_gu; (void)hidden; (void)cl; (void)mb; (void)nb; (void)wg; (void)g; (void)q; (void)srow; (void)s_misc; (void)load_w; (void)load_a;

__global__ void __launch_bounds__(512, 1) mega_kernel(const __grid_constant__ Params P) {
  extern __shared__ __align__(1024) uint8_t smem[];
  {
    PHASE_IDS
    if (warp == 0) {
      if (lane == 0) {
        prefetch_tmap(&P.mapA[0]); prefetch_tmap(&P.mapW);
#pragma unroll
        for (int i = 0; i < 6; i++) mbar_init(bar(B_FULL + i), 1);
        asm volatile("fence.mbarrier_init.release.cluster;" ::: "memory");
      }
      __syncwarp();
      mbar_expect_tx(bar(B_FULL), SL_HD + 32768);
      tma_load3(sbase + SL_W, &P.mapW, hp * 64, 0, 0, bar(B_FULL));
      tma_load3(sbase + SL_W + 6144, &P.mapW, hp * 64, 16, 0, bar(B_FULL));
      load_a(0, 0, 0);
    } else if (tid == 32) {
#pragma unroll
      for (int i = 6; i < B_COUNT; i++) mbar_init(bar(i), bar_count(i));
      asm volatile("fence.mbarrier_init.release.cluster;" ::: "memory");
    } else if (warp == 8) {
      ((uint4*)(smem + OFF_ONES))[lane] = make_uint4(0x3F803F80u, 0x3F803F80u, 0x3F803F80u, 0x3F803F80u);
      ((uint4*)(smem + OFF_ONES))[lane + 32] = make_uint4(0x3F803F80u, 0x3F803F80u, 0x3F803F80u, 0x3F803F80u);
    }
    __syncwarp();
    cluster_arrive(); cluster_wait();
    if (warp == 0) {
      PROFL(0, 1);
      load_w(1, 1);
    } else if (tid == 96) {
      if ((sbase & 0x3FFFF) != SOFF) __trap();
    }
    __syncwarp();
  }

  regs_dec<120>();
#pragma unroll 1
  for (unsigned pass_v = 0;;) {
    const unsigned pass = __shfl_sync(0xffffffffu, pass_v, 0);
    if (__shfl_sync(0xffffffffu, fresh_tid() >> 8, 0)) {
      if (pass > 0) {
        const unsigned layer = pass - 1;
        uint32_t xr[32];
        {
          PHASE_IDS
          float acc[64];
#pragma unroll
          for (int i = 0; i < 64; i++) acc[i] = 0.f;
          const uint32_t da0 = dlo(SOFF, 16) + (wg - 2) * 256;
          constexpr uint32_t db0 = dlo(SOFF + 16384, 8192);
#pragma unroll 1
          for (int k4 = 0; k4 < 4; k4++) {
#pragma unroll
            for (int st = 0; st < 4; st++) {
              mbar_wait(bar(B_WFULL + st), k4 & 1);
              wg_fence();
#pragma unroll
              for (int kk = 0; kk < 4; kk++)
                wg_ss128t<H64, H128>(acc, da0 + (wo_off(st) >> 4) + (kk >> 1) * 512 + (kk & 1) * 2, db0 + (wo_off(st) >> 4) + kk * 128, 1);
              wg_commit();
              if (st == 0 && k4 == 0 && warp == 9) PROF(10);
              if (warp == 9) STEPT(16 + k4 * 4 + st);
              wg_wait<1>();
              if (lane < 2 && (st == 0 ? k4 > 0 : (st < 3 || k4 < 3))) mbar_arrive_cluster(bar(B_WEMPTY + ((st + 3) & 3)), lane);
            }
          }
          mbar_wait(bar(B_RES), layer);
          mbar_wait(bar(B_RST), layer);
          const uint32_t zoff = qo_off(0, (wg - 2) * 2);
#pragma unroll
          for (int j = 0; j < 8; j++)
            ldsm_x4(sbase + zoff + srow * 128 + (j >> 2) * 8192 + ((((2 * j + (mi >> 1)) & 7) ^ (srow & 7)) << 4), xr[4 * j], xr[4 * j + 1], xr[4 * j + 2], xr[4 * j + 3]);
          wg_wait<0>();
          fence_regs<64>(acc);
          if (warp == 9) PROF(11);
#pragma unroll
          for (int j = 0; j < 32; j++) xr[j] = hadd_bf2(xr[j], pack_bf16(acc[2 * j], acc[2 * j + 1]));
        }
        PHASE_IDS
        const uint32_t tag = s_misc[M_TAG];
        const int grow = mb * 128 + (warp - 8) * 16 + g;
        {
          float d[6][4];
#pragma unroll
          for (int i = 0; i < 6; i++) d[i][0] = d[i][1] = d[i][2] = d[i][3] = 0.f;
          const uint4* tab = (const uint4*)(smem + OFF_PATCH + (g == 1 ? q * 64 : (g == 0 ? 256 : 320)));
#pragma unroll
          for (int j2 = 0; j2 < 4; j2++) {
            const uint4 w = tab[j2];
#pragma unroll
            for (int jj = 0; jj < 2; jj++) {
              const uint32_t* a = &xr[8 * j2 + 4 * jj];
              mma_16816(d[jj], a[0], a[1], a[2], a[3], jj ? w.z : w.x, jj ? w.w : w.y);
              mma_16816(d[2 + jj], a[0], a[1], a[2], a[3], a[0], a[2]);
              mma_16816(d[4 + jj], a[0], a[1], a[2], a[3], a[1], a[3]);
            }
          }
          const float sq0 = __shfl_sync(0xffffffffu, (g & 1) ? d[2][1] + d[3][1] : d[2][0] + d[3][0], g * 4 + (g >> 1));
          const float sq1 = __shfl_sync(0xffffffffu, (g & 1) ? d[4][3] + d[5][3] : d[4][2] + d[5][2], g * 4 + (g >> 1));
          uint4* dst = &g_part[layer][nb * SEQ + grow];
          if (q == 0) {
            st_relaxed4(dst, make_uint4(__float_as_uint(d[0][0] + d[1][0]), __float_as_uint(sq0), __float_as_uint(d[0][1] + d[1][1]), tag));
            st_relaxed4(dst + 8, make_uint4(__float_as_uint(d[0][2] + d[1][2]), __float_as_uint(sq1), __float_as_uint(d[0][3] + d[1][3]), tag));
          }
        }
        if (warp == 9) PROF(12);
        if (layer == 0 && lane < 2) mbar_arrive_cluster(bar(B_QFREE), lane);
        asm volatile("bar.arrive 6, 320;" ::: "memory");
        const int t_p = (int)clock();
        const uint32_t zrow = sbase + X_ST + (wg - 2) * 16384 + srow * 128;
        named_bar(5, 256);
#pragma unroll
        for (int j = 0; j < 8; j++)
          stsm_x4(zrow + (j >> 2) * 8192 + ((((2 * j + (mi >> 1)) & 7) ^ (srow & 7)) << 4), xr[4 * j], xr[4 * j + 1], xr[4 * j + 2], xr[4 * j + 3]);
        if (layer == 0) {
          fence_async_smem();
          asm volatile("bar.arrive 8, 288;" ::: "memory");
        }
#pragma unroll 1
        while ((int)clock() - t_p < DELAY_P) {}
        {
          const int rr = q >> 1;
          const uint4* src = &g_part[layer][(q & 1) * 4 * SEQ + grow + 8 * rr];
          uint4 pp[4];
          uint32_t spins = 0;
#pragma unroll 1
          do {
#pragma unroll
            for (int j = 0; j < 4; j++) pp[j] = ld_relaxed4(src + j * SEQ);
          } while (!__all_sync(0xffffffffu, pp[0].w == tag && pp[1].w == tag && pp[2].w == tag && pp[3].w == tag) && ++spins < SPIN_LIMIT);
          if (warp == 9) PROF(13);
          float s3[3] = {(__uint_as_float(pp[0].x) + __uint_as_float(pp[1].x)) + (__uint_as_float(pp[2].x) + __uint_as_float(pp[3].x)),
                         (__uint_as_float(pp[0].y) + __uint_as_float(pp[1].y)) + (__uint_as_float(pp[2].y) + __uint_as_float(pp[3].y)),
                         (__uint_as_float(pp[0].z) + __uint_as_float(pp[1].z)) + (__uint_as_float(pp[2].z) + __uint_as_float(pp[3].z))};
#pragma unroll
          for (int c = 0; c < 3; c++) s3[c] += __shfl_xor_sync(0xffffffffu, s3[c], 1);
          const float mu = s3[0] * (1.f / DM), var = fmaxf(fmaf(-mu, mu, s3[1] * (1.f / DM)), 0.f);
          const float mn = rbf(mu), iv = ln_inv(var);
          const uint32_t ky = router_key(rbf((s3[2] - mn * __uint_as_float(s_misc[M_WSUM])) * iv), grow + 8 * rr);
          const uint32_t wbest = __reduce_max_sync(0xffffffffu, ky);
          s_misc[M_KEYS + warp - 8] = wbest;
          named_bar(5, 256);
          if (__reduce_max_sync(0xffffffffu, s_misc[M_KEYS + (lane & 7)]) == wbest) {
            if (nb == 0 && ky == wbest && (q & 1) == 0) st_relaxed4(&g_slot[layer][mb * 8], make_uint4(ky, __float_as_uint(mn), __float_as_uint(iv), tag));
            const int r = ~wbest & 15;
            if ((r & 7) == g) {
#pragma unroll
              for (int j = 0; j < 4; j++) {
                const uint32_t* a = &xr[8 * j];
                st_relaxed4(&g_cand[layer][mb * 128 + nb * 16 + q * 4 + j],
                    r < 8 ? make_uint4(a[0], a[2], a[4], a[6]) : make_uint4(a[1], a[3], a[5], a[7]));
              }
            }
            __syncwarp();
          }
          if (warp == 9) PROF(14);
          if (layer == 0) {
            if ((q & 1) == 0) {
              g_rowln[nb][grow + 8 * rr] = make_float2(mn, iv);
              if (warp - 8 == nb) {
                const float mu2 = mu + (mu - mn) * iv, inv2 = ln_inv(var * (1.f + iv) * (1.f + iv));
                st_relaxed4(&g_rowab[1][grow + 8 * rr], make_uint4(__float_as_uint((1.f + iv) * inv2), __float_as_uint((mn * iv + rbf(mu2)) * inv2), tag, 0));
              }
            }
            __syncwarp();
          } else {
            const uint32_t m2 = pack_bf16(mn, mn);
            uint8_t* row = smem + X_ST + (wg - 2) * 16384 + (q & 1) * 8192 + (wi * 16 + g + 8 * rr) * 128;
#pragma unroll 2
            for (int j = 0; j < 8; j++) {
              uint4* c = (uint4*)(row + (((j + lane) & 7) << 4));
              const uint4 v = *c;
              *c = make_uint4(add_ln_pair(v.x, m2, iv), add_ln_pair(v.y, m2, iv), add_ln_pair(v.z, m2, iv), add_ln_pair(v.w, m2, iv));
            }
            fence_async_smem();
          }
          if (warp == 15) asm volatile("bar.arrive 7, 512;" ::: "memory");
        }
        if (warp < 15) {
          uint32_t gu[64];
          mbar_wait(bar(B_GU + 1), layer);
#pragma unroll
          for (int j = 0; j < 16; j++) fetch_gu(gu + 4 * j, j, warp - 8);
          fence_async_smem();
          float d[4][4] = {};
          named_bar(7, 512);
#pragma unroll
          for (int hf = 0; hf < 2; hf++) {
            uint4 xv[4] = {};
            if (g == 0) {
#pragma unroll
              for (int j = 0; j < 4; j++) xv[j] = ((const uint4*)(smem + T_XS))[32 + hf * 16 + j * 4 + q];
            }
            __syncwarp();
#pragma unroll
            for (int j = 0; j < 4; j++) {
              const uint32_t* a = gu + hf * 32 + j * 8;
              mma_16816(d[(j & 1) * 2], a[0], a[1], a[2], a[3], xv[j].x, xv[j].y);
              mma_16816(d[(j & 1) * 2 + 1], a[4], a[5], a[6], a[7], xv[j].z, xv[j].w);
            }
          }
          send_gu((d[0][0] + d[1][0]) + (d[2][0] + d[3][0]), (d[0][2] + d[1][2]) + (d[2][2] + d[3][2]), warp - 8, 4);
          __syncwarp();
        }
        if (layer == 0) asm volatile("bar.arrive 9, 512;" ::: "memory");
        else {
          uint32_t wd[64];
          mbar_wait(bar(B_DN), layer);
#pragma unroll
          for (int j = 0; j < 16; j++) {
            const uint32_t row = sbase + wo_off(0) + ((warp - 8) * 2 + (j >> 3)) * 3584 + min((j & 1) * 16 + (mi >> 1) * 8 + (lane & 7), 27) * 128;
            ldsm_x4_t(row + ((((j & 6) + (mi & 1)) ^ ((row >> 7) & 7)) << 4), wd[4 * j], wd[4 * j + 1], wd[4 * j + 2], wd[4 * j + 3]);
          }
          fence_regs_u<64>(wd);
          uint32_t hf[4];
          named_bar(10, 288);
          *(uint4*)hf = *(const uint4*)(smem + OFF_PATCH + 256 + q * 16);
          if (warp == 9) PROF(19);
          float y[4][4] = {};
#pragma unroll
          for (int j = 0; j < 16; j++)
            mma_16816(y[j & 3], wd[4 * j], wd[4 * j + 1], wd[4 * j + 2], wd[4 * j + 3], g == j >> 1 ? hf[(j & 1) * 2] : 0u, g == j >> 1 ? hf[(j & 1) * 2 + 1] : 0u);
          {
            float e[4];
#pragma unroll
            for (int c = 0; c < 4; c++) { const int i = (c & 1) * 2 + (c >> 1); e[c] = (y[0][i] + y[1][i]) + (y[2][i] + y[3][i]); }
            const bool b0 = g & 1, b1 = g & 2;
            float t0 = __shfl_xor_sync(0xffffffffu, b0 ? e[0] : e[1], 4), t1 = __shfl_xor_sync(0xffffffffu, b0 ? e[2] : e[3], 4);
            const float f0 = b0 ? t0 : e[0], f1 = b0 ? e[1] : t0, f2 = b0 ? t1 : e[2], f3 = b0 ? e[3] : t1;
            t0 = __shfl_xor_sync(0xffffffffu, b1 ? f0 : f2, 8); t1 = __shfl_xor_sync(0xffffffffu, b1 ? f1 : f3, 8);
            st_relaxed4(&g_ypart[layer][bid * 256 + (warp - 8) * 32 + (q * 4 + (g & 3)) * 2 + (g >> 2)],
                b1 ? make_uint4(__float_as_uint(t0), __float_as_uint(t1), __float_as_uint(f2), __float_as_uint(f3)) : make_uint4(__float_as_uint(f0), __float_as_uint(f1), __float_as_uint(t0), __float_as_uint(t1)));
          }
          if (warp == 9) PROF(20);
          asm volatile("bar.arrive 9, 384;" ::: "memory");
          cluster_arrive(); cluster_wait();
          return;
        }
      }
      const unsigned layer = pass;
      named_bar(1 + (fresh_tid() >> 7), 128);
      regs_inc<224>();
      float acc[2][96];
      float pa[2][2], pb[2][2];
      {
        PHASE_IDS
        const uint32_t da0 = dlo(SOFF, 16) + (wg - 2) * 512;
        constexpr uint32_t db0 = dlo(SOFF + SL_W, 2048);
        if (warp == 9) PROF(19 - 2 * layer);
        mbar_wait(bar(B_FULL), 0);
        if (warp == 9) PROF(29);
        if (warp == 9) STEPT(0);
        wg_fence();
        wg_ss192t_z(acc[0], da0, db0); wg_ss192t_z(acc[1], da0 + 1024, db0);
        wg_ss192t(acc[0], da0 + 2, db0 + 384, 1); wg_ss192t(acc[1], da0 + 1026, db0 + 384, 1);
        wg_commit();
        int s = 1, u = 0;
#pragma unroll 1
        for (int i = 1; i < 28; i++) {
          const uint32_t da = da0 + (s >> 1) * (STG >> 4) + (s & 1) * 4, db = db0 + (s >> 1) * (STG >> 4) + (s & 1) * (SL_HD >> 4);
          mbar_wait(bar(B_FULL + s), (u + (s > 1 ? layer : 0)) & 1);
          if (warp == 9 && !(i & 1)) STEPT(i >> 1);
          wg_fence();
          wg_ss192t(acc[0], da, db, 1); wg_ss192t(acc[1], da + 1024, db, 1);
          wg_ss192t(acc[0], da + 2, db + 384, 1); wg_ss192t(acc[1], da + 1026, db + 384, 1);
          wg_commit();
          wg_wait<1>();
          if (lane < 2 && i < 27) mbar_arrive_cluster(bar(B_EMPTY + (s == 0 ? 5 : s - 1)), lane);
          if (++s == 6) { s = 0; u++; }
        }
      }
      PHASE_IDS
      auto last_tile = [&](int m, int j) {
        const int e = (4 + j) % 6;
        const uint32_t da = dlo(SOFF + (e >> 1) * STG + (e & 1) * 64, 16) + (wg - 2) * 512 + m * 1024, db = dlo(SOFF + (e >> 1) * STG + SL_W + (e & 1) * SL_HD, 2048);
        wg_fence();
        wg_ss192t(acc[m], da, db, 1);
        wg_ss192t(acc[m], da + 2, db + 384, 1);
      };
      {
        if (layer == 0) mbar_wait(bar(B_CS), 0);
        const uint32_t tag = s_misc[M_TAG];
        const uint4* src = &g_rowab[layer][rb * 256 + (wg - 2 + (lane >> 4) * 2) * 64 + wi * 16 + (lane & 15)];
        uint4 v;
#pragma unroll
        for (int j = 0; j < 4; j++) {
          if (j == 2) v = ld_relaxed4(src);
          mbar_wait(bar(B_FULL + (4 + j) % 6), j < 2 ? layer : 1);
          last_tile(1, j);
          if (j == 0) { wg_commit(); wg_wait<1>(); mbar_arrive_e(bar(B_E23)); }
        }
        wg_commit();
        last_tile(0, 0);
        wg_commit();
        if (warp != 9) STEPT(4);
#pragma unroll 1
        for (uint32_t spins = 0; !__all_sync(0xffffffffu, v.z == tag) && spins < SPIN_LIMIT; spins++) v = ld_relaxed4(src);
#pragma unroll
        for (int j = 0; j < 4; j++) {
          pa[j >> 1][j & 1] = __uint_as_float(__shfl_sync(0xffffffffu, v.x, g + 8 * j));
          pb[j >> 1][j & 1] = __uint_as_float(__shfl_sync(0xffffffffu, v.y, g + 8 * j));
        }
        if (warp != 9) STEPT(5);
      }
      const int prow = (int)s_misc[M_SEL0] - rb * 256;
      const float4* cs = (const float4*)(smem + OFF_CS) + q;
      auto finish = [&](int m, int b, float2 c, uint32_t* dst) {
        dst[0] = pack_bf16(acc[m][4 * b] * pa[m][0] - c.x * pb[m][0], acc[m][4 * b + 1] * pa[m][0] - c.y * pb[m][0]);
        dst[1] = pack_bf16(acc[m][4 * b + 2] * pa[m][1] - c.x * pb[m][1], acc[m][4 * b + 3] * pa[m][1] - c.y * pb[m][1]);
      };
      auto grp = [](int n) { return n < 8 ? 4 + ((n >> 1) & 1) * 4 + (n >> 2) * 2 + (n & 1) : n - 8; };
      float4 cq[2] = {cs[grp(0) * 4], cs[grp(1) * 4]};
      auto next = [&](int m, int n, uint32_t* r) {
        if (m == 1 && n % 4 == 0) { last_tile(0, 1 + n / 4); wg_commit(); }
        const float4 c = cq[n & 1];
        cq[n & 1] = cs[grp((n + 2) % 12) * 4];
        finish(m, 2 * grp(n), make_float2(c.x, c.y), r); finish(m, 2 * grp(n) + 1, make_float2(c.z, c.w), r + 2);
      };
#pragma unroll
      for (int m = 1; m >= 0; m--) {
        if (m == 1) {
          wg_wait<1>();
          fence_regs<96>(acc[1]);
          mbar_wait(bar(B_E23), layer);
          if (warp != 9) STEPT(0);
        } else {
          wg_wait<0>();
          fence_regs<96>(acc[0]);
          if (warp != 9) STEPT(1);
          if (lane < 2) mbar_arrive_cluster(bar(B_QDONE), lane);
          if (warp == 9) PROF(2);
        }
        const int qb = wg - 2 + 2 * m;
        const bool patch = prow >> 4 == qb * 4 + wi;
#pragma unroll
        for (int jj = 0; jj < 8; jj++) {
          const int h = jj >> 2;
          uint32_t r[4];
          next(m, jj, r);
          if (m == 0 && jj == 0) named_bar(5, 256);
          stsm_x4(sbase + kv_off(h, 4 + 2 * m) + (wg - 2) * 8192 + ((jj >> 1) & 1) * 4096 + srow * 64 + ((((jj & 1) * 2 + (mi >> 1)) ^ ((srow >> 1) & 3)) << 4),
              r[0], r[1], r[2], r[3]);
        }
        if (patch) {
          mbar_wait(bar(B_CS), 1);
          __syncwarp();
          if (lane < 16)
            *(uint4*)(smem + kv_off(g >> 1, 4 + qb) + (g & 1) * 4096 + (prow & 63) * 64 + ((q ^ ((prow >> 1) & 3)) << 4)) =
              *(const uint4*)(smem + OFF_PATCH + 128 + (g & 1) * 128 + (g >> 1) * 64 + q * 16);
        }
        fence_async_smem();
        __syncwarp();
        mbar_arrive_e(bar(B_KVREADY + 1 - m));
        if (warp != 9) STEPT(3 - m);
        pa[m][0] *= SM_C; pa[m][1] *= SM_C; pb[m][0] *= SM_C; pb[m][1] *= SM_C;
#pragma unroll
        for (int jj = 0; jj < 4; jj++) {
          uint32_t r[4];
          next(m, 8 + jj, r);
          *(uint4*)(smem + qo_off(jj >> 1, 2 * m) + (warp - 8) * 1024 + (jj & 1) * 512 + lane * 16) = make_uint4(r[0], r[1], r[2], r[3]);
        }
        __syncwarp();
        if (patch) {
          *(uint32_t*)(smem + qo_off(lane >> 4, 2 * m) + (warp - 8) * 1024 + (mi & 1) * 512 + ((prow & 7) * 4 + q) * 16 + ((g & 1) * 2 + ((prow >> 3) & 1)) * 4) =
              *(const uint32_t*)(smem + OFF_PATCH + lane * 4);
          __syncwarp();
        }
      }
      if (warp == 9) PROF(3);
      mbar_arrive_e(bar(B_QREADY));
      regs_dec<120>();
    } else {
      if (pass > 0) {
        const unsigned layer = pass - 1;
        PHASE_IDS
        const uint32_t tag = s_misc[M_TAG];
        if (warp == 7) {
          uint32_t* tab = (uint32_t*)(smem + OFF_PATCH);
#pragma unroll
          for (int j = 0; j < 2; j++) { const int w = lane + 32 * j; tab[(w & 3) * 16 + (w >> 2)] = ((const uint32_t*)P.w_r)[nb * 64 + w]; }
          tab[64 + lane] = lane < 16 ? 0x3F803F80u : 0u;
          float tot = 0.f;
#pragma unroll 1
          for (int j = 0; j < 4; j++) {
            const uint4 u = ((const uint4*)P.w_r)[lane + 32 * j];
            tot += bf_lo(u.x) + bf_hi(u.x) + bf_lo(u.y) + bf_hi(u.y) + bf_lo(u.z) + bf_hi(u.z) + bf_lo(u.w) + bf_hi(u.w);
          }
          s_misc[M_WSUM] = __float_as_uint(warp_sum(tot));
        }
        if (layer == 1) {
          const float2 ln = g_rowln[nb][mb * 128 + tid - 128];
          const uint32_t m2 = pack_bf16(ln.x, ln.x);
          uint8_t* row = smem + qo_off(0, wi & 2) + (tid & 63) * 128;
          mbar_wait(bar(B_RES), 1);
#pragma unroll 1
          for (int j = 0; j < 8; j++) {
            uint4* c = (uint4*)(row + (((j + lane) & 7) << 4));
            const uint4 v = c[0], w = c[512];
            c[0] = make_uint4(add_ln_pair(v.x, m2, ln.y), add_ln_pair(v.y, m2, ln.y), add_ln_pair(v.z, m2, ln.y), add_ln_pair(v.w, m2, ln.y));
            c[512] = make_uint4(add_ln_pair(w.x, m2, ln.y), add_ln_pair(w.y, m2, ln.y), add_ln_pair(w.z, m2, ln.y), add_ln_pair(w.w, m2, ln.y));
          }
          const int prow = (int)s_misc[M_SEL0] - mb * 128;
          __syncwarp();
          if (prow >> 5 == wi && lane < 16)
            *(uint4*)(smem + qo_off(0, wi & 2) + (lane >> 3) * 8192 + (prow & 63) * 128 + (((lane ^ prow) & 7) << 4)) = poll4(&g_x2row[(nb * 16 + lane) * 2]);
          PROF(30);
        }
        __syncwarp();
        mbar_arrive_e(bar(B_RST));
        if (warp == 4) {
          named_bar(6, 320);
          spin_cycles(DELAY_S);
          uint4 c, u0 = {}, u1 = {};
          uint32_t u2 = 0, best = 0, spins = 0;
          int src;
#pragma unroll 1
          for (;;) {
            src = (~best & 0x7FFu) >> 7;
            const uint4* xsel = &g_cand[layer][src * 128];
            c = ld_relaxed4(&g_slot[layer][(lane & 15) * 8]);
            if (best) {
              u0 = ld_relaxed4(xsel + rank * 64 + lane); u1 = ld_relaxed4(xsel + rank * 64 + 32 + lane);
              u2 = ld_relaxed((const uint32_t*)(xsel + (bid >> 4) * 16 + q * 4) + (bid & 15));
            }
            const uint32_t prev = best;
            best = __reduce_max_sync(0xffffffffu, c.w == tag ? c.x : 0u);
            if ((__all_sync(0xffffffffu, c.w == tag && valid4(u0) && valid4(u1) && u2 != SENT) && best == prev) || ++spins > SPIN_LIMIT) break;
          }
          const float sel_m = __uint_as_float(__shfl_sync(0xffffffffu, c.y, src)), sel_inv = __uint_as_float(__shfl_sync(0xffffffffu, c.z, src));
          const uint32_t m2 = pack_bf16(sel_m, sel_m);
          uint4* xs = (uint4*)(smem + T_XS) + (lane & 16) + q * 4 + (g & 3);
          xs[0] = make_uint4(ln_pair(u0.x, m2, sel_inv), ln_pair(u0.y, m2, sel_inv), ln_pair(u0.z, m2, sel_inv), ln_pair(u0.w, m2, sel_inv));
          xs[32] = make_uint4(ln_pair(u1.x, m2, sel_inv), ln_pair(u1.y, m2, sel_inv), ln_pair(u1.z, m2, sel_inv), ln_pair(u1.w, m2, sel_inv));
          s_misc[M_KEY] = best; s_misc[M_MEAN] = __float_as_uint(sel_m); s_misc[M_INV] = __float_as_uint(sel_inv);
          s_misc[M_XQ + q] = u2;
          if (layer == 0) s_misc[M_SEL0] = ~best & 0x7FFu;
          PROF(16);
        }
        if (layer == 1) {
          named_bar(7, 512);
          const int sel = SEQ - 1 - (int)(s_misc[M_KEY] & 0x7FFFu), skip = sel >> 7 == mb ? (sel >> 6) & 1 : -1;
          if (warp == 7) store_tile(1, skip, false);
          if (warp == 4) {
            mbar_wait_cluster(bar(B_HX), 1);
            ((bf16*)(smem + OFF_PATCH + 256))[((lane >> 1) & 3) * 8 + (lane >> 3) * 2 + (lane & 1)] = __float2bfloat16_rn(hidden());
            asm volatile("bar.arrive 10, 288;" ::: "memory");
          }
#pragma unroll 1
          for (int c = tid - 128; c < 1024 && skip >= 0; c += 128) {
            const int r = c >> 4;
            if (r != (sel & 63))
              *(uint4*)(P.out + (size_t)(mb * 128 + skip * 64 + r) * DM + nb * 128 + (c & 15) * 8) =
                *(const uint4*)(smem + X_ST + skip * 16384 + ((c >> 3) & 1) * 8192 + r * 128 + (((c ^ r) & 7) << 4));
          }
          __syncwarp();
        } else asm volatile("bar.arrive 7, 512;" ::: "memory");
        if (warp == 5 && layer == 0) {
          named_bar(8, 288);
          if (nb > 0) spin_cycles(X_STAGGER);
          store_tile(0, -1, true);
          set_flag(&g_xflag[mb][nb].v[0], tag);
          PROF(17);
          poll_flag(&g_xflag[2 * rb + (lane & 1)][0].v[0], tag);
          fence_async_global();
          load_a(0, 0, 1);
          PROFL(1, 1);
        }
      }
      named_bar(1 + (fresh_tid() >> 7), 128);
      regs_dec<32>();
#pragma unroll 1
      for (;;) {
        const unsigned pass = __shfl_sync(0xffffffffu, pass_v, 0);
        if (pass > 0) {
          const unsigned layer = pass - 1;
          PHASE_IDS
          const uint32_t tag = s_misc[M_TAG], bkey = s_misc[M_KEY];
          const int sel = SEQ - 1 - (int)(bkey & 0x7FFFu);
          if (warp == 3) {
            if (layer == 1) {
#pragma unroll
              for (int j = 0; j < 3; j++) ((uint4*)g_vw)[bid * 96 + j * 32 + lane] = make_uint4(0, 0, 0, 0);
            }
            if (bid == 0 && lane == 0) g_sel[layer] = sel;
          }
          __syncwarp();
          if (layer == 0) {
            auto load_down = [&](int j) {
              mbar_expect_tx(bar(B_DN + j), 2 * FFN_PIECE);
              bulk_load_h(sbase + SL_F + j * 2 * FFN_PIECE, P.w_d + (size_t)((cl * 56 + rank * 28) + j * 14) * DM, 2 * FFN_PIECE, bar(B_DN + j), policy_evict_first());
            };
            if (warp == 5) {
              load_a(2, 2, 1);
              poll_flag(&g_xflag[2 * rb + (lane & 1)][(lane >> 1) & 7].v[0], tag);
              fence_async_global();
              load_a(4, 4, 1);
            }
            float hv = 0.f;
            if (wg == 1) { mbar_wait_cluster(bar(B_HX), 0); hv = rbf(hidden()); fence_regs<1>(&hv); }
            named_bar(9, 512);
            if (warp == 0) {
              fence_async_smem();
              if (lane < 16) mbar_arrive_cluster(bar(B_QFREE), lane & 1);
              mbar_wait(bar(B_QFREE), 1);
              load_w(4, 4); load_w(5, 5);
              load_down(0);
            } else if (wg == 1) {
              if (warp == 4) { mbar_wait(bar(B_DN), 0); load_down(1); }
              float d[8] = {0.f, 0.f, 0.f, 0.f, 0.f, 0.f, 0.f, 0.f};
              const uint4* wrow = (const uint4*)(smem + SL_F) + tid - 128;
              mbar_wait(bar(B_DN), 0);
              uint4 w0 = wrow[0];
#pragma unroll 1
              for (int j = 0; j < 28; j += 2) {
                const uint4 w1 = wrow[j * 128 + 128];
                fma8(d, w0, __shfl_sync(0xffffffffu, hv, j));
                if (j == 12) mbar_wait(bar(B_DN + 1), 0);
                w0 = wrow[min(j + 2, 27) * 128];
                fma8(d, w1, __shfl_sync(0xffffffffu, hv, j + 1));
              }
              uint4* dst = &g_ypart[0][bid * 256 + (tid - 128) * 2];
              st_relaxed4(dst, make_uint4(__float_as_uint(d[0]), __float_as_uint(d[1]), __float_as_uint(d[2]), __float_as_uint(d[3])));
              st_relaxed4(dst + 1, make_uint4(__float_as_uint(d[4]), __float_as_uint(d[5]), __float_as_uint(d[6]), __float_as_uint(d[7])));
              asm volatile("bar.arrive 11, 160;" ::: "memory");
              PROF(20);
            } else if (warp == 2) {
              named_bar(11, 160);
              fence_async_smem();
              load_ws(WS_PACE);
            }
          } else {
            if (wg == 1) named_bar(9, 384);
            cluster_arrive();
          }
          if (wg == 1) {
            const int t_y = (int)clock();
            const uint32_t xw = s_misc[M_XQ + ((lane & 7) >> 1)];
            const float x = (lane & 1) ? bf_hi(xw) : bf_lo(xw);
            float xn = rbf(rbf(x - __uint_as_float(s_misc[M_MEAN])) * __uint_as_float(s_misc[M_INV]));
            uint32_t u = bkey & 0xFFFF0000u;
            u = (u & 0x80000000u) ? (u & 0x7FFFFFFFu) : (~u & 0xFFFF0000u);
            float sg = rbf(__fdividef(1.f, 1.f + __expf(-__uint_as_float(u))));
            uint32_t* dst = (layer == 0 ? (uint32_t*)&g_x2row[bid * 2] : (uint32_t*)(P.out + (size_t)sel * DM + bid * 8)) + (lane >> 1);
            asm volatile("" : "+f"(xn), "+f"(sg), "+l"(dst));
#pragma unroll 1
            while ((int)clock() - t_y < DELAY_Y) {}
            const uint4* src = &g_ypart[layer][((tid - 128) >> 1) * 256 + bid * 2 + (tid & 1)];
            uint4 v, w;
            uint32_t spins = 0;
#pragma unroll 1
            do { v = ld_relaxed4(src); w = ld_relaxed4(src + 64 * 256); } while (!__all_sync(0xffffffffu, valid4(v) && valid4(w)) && ++spins < SPIN_LIMIT);
            float a[4] = {__uint_as_float(v.x) + __uint_as_float(w.x), __uint_as_float(v.y) + __uint_as_float(w.y),
                  __uint_as_float(v.z) + __uint_as_float(w.z), __uint_as_float(v.w) + __uint_as_float(w.w)};
            const bool b1 = lane & 2, b2 = lane & 4;
            float c0 = (b1 ? a[1] : a[0]) + __shfl_xor_sync(0xffffffffu, b1 ? a[0] : a[1], 2);
            float c1 = (b1 ? a[3] : a[2]) + __shfl_xor_sync(0xffffffffu, b1 ? a[2] : a[3], 2);
            float y = (b2 ? c1 : c0) + __shfl_xor_sync(0xffffffffu, b2 ? c0 : c1, 4);
            y += __shfl_xor_sync(0xffffffffu, y, 8);
            y += __shfl_xor_sync(0xffffffffu, y, 16);
            float* red = (float*)(smem + OFF_PATCH);
            red[wi * 8 + (lane & 1) * 4 + ((lane >> 1) & 3)] = y;
            named_bar(2, 128);
            if (warp == 4) {
              PROF(21);
              y = (red[lane & 7] + red[8 + (lane & 7)]) + (red[16 + (lane & 7)] + red[24 + (lane & 7)]);
              const float res = x + rbf(xn + rbf(rbf(y) * sg));
              const uint32_t pr = pack_bf16(res, __shfl_down_sync(0xffffffffu, res, 1));
              if (lane < 8 && (lane & 1) == 0) st_relaxed(dst, pr);
              PROF(22);
            }
          }
          if (pass == 2) {
            if (bid == 0 && tid == 128) g_epoch = tag;
            bulk_wait_all();
            __syncwarp();
            cluster_wait();
            return;
          }
        }
        const unsigned layer = pass;
        if (__shfl_sync(0xffffffffu, fresh_tid() >> 5, 0) > 1 - (int)layer) {
          PHASE_IDS
          uint4* xrow = (uint4*)(smem + SL_F + 4 * SL_HD);
          if (wg == 1) {
            if (layer == 0) {
              xrow[tid - 128] = make_uint4(0x3F803F80u, 0x3F803F80u, 0x3F803F80u, 0x3F803F80u);
              if (warp == 5) {
                mbar_wait(bar(B_FULL + 5), 0);
                if (lane == 0) {
#pragma unroll 1
                  for (int i = 11; i > 0; i--) prefetch_tmap(&P.mapA[0] + i);
                }
                __syncwarp();
                load_ws(WS_PACE);
              }
            } else xrow[tid - 128] = poll4(&g_x2row[(tid - 128) * 2]);
            PROF(23);
          }
          named_bar(12, 192 + 32 * layer);
          if (warp == 1) {
            float mean = 0.f;
#pragma unroll 1
            for (int pass2 = 0; pass2 < 2; pass2++) {
              float acc = 0.f;
#pragma unroll 1
              for (int j = lane; j < 128; j += 32) {
                const uint4 v = xrow[j];
                const uint32_t w[4] = {v.x, v.y, v.z, v.w};
#pragma unroll
                for (int c = 0; c < 4; c++) {
                  const float d0 = bf_lo(w[c]) - mean, d1 = bf_hi(w[c]) - mean;
                  acc += pass2 ? d0 * d0 + d1 * d1 : d0 + d1;
                }
              }
              acc = warp_sum(acc) * (1.f / DM);
              if (pass2 == 0) mean = acc;
              else { s_misc[M_PMEAN] = __float_as_uint(rbf(mean)); s_misc[M_PINV] = __float_as_uint(ln_inv(acc)); }
            }
          } else {
            mbar_wait(bar(B_WS), layer);
            const uint8_t* wa = smem + SL_F + (g >> 1) * SL_HD + ((warp - 2) >> 1) * 4096 + (g & 1) * 2048;
            const uint32_t* xs = (const uint32_t*)xrow + rb * 64 + g * 8;
            const int ch = (warp & 1) * 4 + q;
            float d[8] = {0.f, 0.f, 0.f, 0.f, 0.f, 0.f, 0.f, 0.f};
            auto wrow = [&](int j) { j = (j ^ ((g & 1) * 4)) & 15; return *(const uint4*)(wa + j * 128 + (((ch ^ j) & 7) << 4)); };
            uint4 w0 = wrow(0);
#pragma unroll 1
            for (int j = 0; j < 16; j += 2) {
              const uint32_t xx = xs[(j >> 1) ^ ((g & 1) * 2)];
              const uint4 w1 = wrow(j + 1);
              fma8(d, w0, bf_lo(xx));
              w0 = wrow(j + 2);
              fma8(d, w1, bf_hi(xx));
            }
#pragma unroll
            for (int c = 0; c < 4; c++) d[c] = ((g & 4) ? d[c + 4] : d[c]) + __shfl_xor_sync(0xffffffffu, (g & 4) ? d[c] : d[c + 4], 16);
#pragma unroll
            for (int c = 0; c < 2; c++) d[c] = ((g & 2) ? d[c + 2] : d[c]) + __shfl_xor_sync(0xffffffffu, (g & 2) ? d[c] : d[c + 2], 8);
            d[0] = ((g & 1) ? d[1] : d[0]) + __shfl_xor_sync(0xffffffffu, (g & 1) ? d[0] : d[1], 4);
            st_relaxed(&g_vw[layer][rb][((warp - 2) >> 1) * DM + hp * 64 + ch * 8 + g], enc(d[0]));
          }
          named_bar(12, 192 + 32 * layer);
          PROF(24);
        }
        PHASE_IDS
        if (wg == 0) {
          if (warp == 0) {
            if (layer == 0) {
#pragma unroll 1
              for (int i = 2; i < 6; i++) { load_w(i, i); if (!(i & 1)) load_a(i, i, 0); }
            }
            int s = 0, u = 0;
#pragma unroll 1
            for (int i = 6; i < 32; i++) {
              if (layer == 1) mbar_arrive_e(bar(B_EMPTY + s));
              mbar_wait(bar(B_EMPTY + s), (u + (s > 1 ? 0 : layer)) & 1);
              if (s & 1) load_a(s - 1, i - 1, layer);
              load_w(s, i);
              if (++s == 6) { s = 0; u++; }
            }
          } else if (warp == 1) {
            if (layer == 0) {
              const uint32_t tag = ld_relaxed(&g_epoch) + 1;
              if (lane < 16) g_rowab[0][rb * 256 + hp * 16 + lane] = make_uint4(0, 0, 0, 0);
              float shift = 0.f, sum = 0.f, sq = 0.f;
              const int r = hp * 16 + (lane >> 1);
#pragma unroll 1
              for (int i = 0; i < 32; i++) {
                mbar_wait(bar(B_FULL + i % 6), (i / 6) & 1);
                const uint8_t* base = smem + ((i % 6) >> 1) * STG + r * 128;
                uint4 v[2];
#pragma unroll
                for (int j = 0; j < 2; j++) v[j] = *(const uint4*)(base + ((((i & 1) * 4 + (lane & 1) * 2 + j) ^ (r & 7)) << 4));
                if (i == 0) shift = __shfl_sync(0xffffffffu, bf_lo(v[0].x), lane & ~1);
#pragma unroll
                for (int j = 0; j < 2; j++) {
                  const uint32_t w[4] = {v[j].x, v[j].y, v[j].z, v[j].w};
#pragma unroll
                  for (int c = 0; c < 4; c++) {
                    const float d0 = bf_lo(w[c]) - shift, d1 = bf_hi(w[c]) - shift;
                    sum += d0 + d1; sq = fmaf(d0, d0, fmaf(d1, d1, sq));
                  }
                }
                fence_async_smem();
                __syncwarp();
                if (i < 26) mbar_arrive_e(bar(B_EMPTY + i % 6));
              }
              sum += __shfl_xor_sync(0xffffffffu, sum, 1); sq += __shfl_xor_sync(0xffffffffu, sq, 1);
              const float dm = sum * (1.f / DM), var = fmaxf(sq * (1.f / DM) - dm * dm, 0.f), mean = shift + dm;
              const float inv = ln_inv(var);
              if ((lane & 1) == 0) st_relaxed4(&g_rowab[0][rb * 256 + r], make_uint4(__float_as_uint(inv), __float_as_uint(rbf(mean) * inv), tag, 0));
            }
            __syncwarp();
            mbar_arrive_e(bar(B_E23));
            if (rb == 0) {
              mbar_wait(bar(B_QDONE), layer);
#pragma unroll 1
              for (int j = lane; j < 512; j += 32) ((uint4*)(smem + kv_off(1, 0)))[j] = make_uint4(0, 0, 0, 0);
              fence_async_smem();
              __syncwarp();
              if (lane < 3) mbar_arrive(bar(B_HALO + lane));
            }
          } else if (warp == 3) {
            if (rb > 0) { mbar_expect_tx(bar(B_HALO), 16384); mbar_expect_tx(bar(B_HALO + 1), 16384); mbar_expect_tx(bar(B_HALO + 2), 32768); }
            fence_async_smem();
            load_gu(0, layer ? GU_PACE1 : GU_PACE);
            PROF(27);
          } else {
            const uint4 sent = make_uint4(SENT, SENT, SENT, SENT), zero = make_uint4(0, 0, 0, 0);
            if (layer == 0) {
              const int f = lane >> 1;
              Flag* fl = f < 2 ? &g_kvflag[rb >> 1][hp][f] : f < 4 ? &g_oflag[rb][f & 1][hp] : &g_xflag[mb][nb];
              if (f < 5 && (f >= 2 || (rank == 1 && rb < 7))) ((uint4*)fl)[lane & 1] = zero;
            }
#pragma unroll 1
            for (int t = lane; t < 128; t += 32) {
              g_ypart[layer][bid * 256 + t] = sent; g_ypart[layer][bid * 256 + 128 + t] = sent;
              g_part[layer][nb * SEQ + mb * 128 + t] = zero;
              if (t < 16) g_cand[layer][mb * 128 + nb * 16 + t] = sent;
              else if (t < 18) { if (nb == 0) g_slot[layer][mb * 8 + t - 16] = zero; }
              else if (t < 20) { if (layer == 0) g_x2row[bid * 2 + t - 18] = sent; }
            }
            __syncwarp();
            mbar_arrive_e(bar(B_CS));
          }
          __syncwarp();
          uint8_t* kvg = g_kv + (size_t)(((rb - 1 + rank) >> 1) * 16 + hp) * 65536;
          if (rank == 0) {
            if (warp == 0) {
              mbar_wait(bar(B_QDONE), layer);
#pragma unroll 1
              for (int j = 0; j < 4; j++) {
                mbar_wait(bar(B_KVREADY + (j >> 1)), layer);
                bulk_push(mapa(sbase + kv_off(j & 1, 2 - (j & 2)), 1), sbase + kv_off(j & 1, 6 - (j & 2)), 16384, mapa(bar(B_HALO + min(j, 2)), 1));
              }
            } else if (warp < 3 && rb > 0) {
              const int p = warp - 1;
              mbar_wait(bar(B_QREADY), layer);
              if (p) spin_cycles(P1_DELAY);
              poll_flag(&g_kvflag[(rb - 1) >> 1][hp][p].v[layer], s_misc[M_TAG]);
              fence_async_global();
#pragma unroll 1
              for (int j = 2 * p; j < 2 * p + 2; j++) bulk_load_h(sbase + kv_off(j & 1, 2 - (j & 2)), kvg + j * 16384, 16384, bar(B_HALO + min(j, 2)), policy_evict_first());
              if (p == 0) PROF(5);
            }
          } else if (warp < 2 && rb < 7) {
            mbar_wait(bar(B_KVREADY + warp), layer);
            if (warp == 1) named_bar(13, 64);
#pragma unroll 1
            for (int j = 2 * warp; j < 2 * warp + 2; j++) bulk_store(kvg + j * 16384, sbase + kv_off(j & 1, 6 - (j & 2)), 16384);
            bulk_commit();
            bulk_wait_all();
            if (warp == 0) asm volatile("bar.arrive 13, 64;" ::: "memory");
            set_flag(&g_kvflag[rb >> 1][hp][warp].v[layer], s_misc[M_TAG]);
            if (warp == 0) PROF(4);
          }
        } else {
          const int t = tid - 128, go = (t >> 5) * DM + hp * 64 + (t & 31) * 2;
          if (layer == 0 && t == 96) { s_misc[M_TAG] = ld_relaxed(&g_epoch) + 1; s_misc[M_SEL0] = 0xFFFFFFFFu; s_misc[M_PROG] = s_misc[M_PROG + 1] = 0; }
          if ((layer == 0 || (int)s_misc[M_SEL0] >> 8 == rb) && warp < 7) {
            spin_cycles(layer ? 300 : 1500);
            uint2 w[8];
            uint32_t spins = 0;
            bool ok;
#pragma unroll 1
            do {
              ok = true;
#pragma unroll
              for (int j = 0; j < 8; j++) w[j] = ld_relaxed2(&g_vw[layer][j][go]);
#pragma unroll
              for (int j = 0; j < 8; j++) ok = ok && w[j].x && w[j].y;
            } while (!__all_sync(0xffffffffu, ok) && ++spins < SPIN_LIMIT);
            float s0 = 0.f, s1 = 0.f;
#pragma unroll
            for (int j = 0; j < 8; j++) { s0 += dec(w[j].x); s1 += dec(w[j].y); }
            float2* csp = (float2*)(smem + OFF_CS) + (t & ~7) + (t & 3) * 2 + ((t >> 2) & 1);
            if (layer == 0) *csp = make_float2(s0, s1);
            else {
              const float2 c = *csp;
              const float a = __uint_as_float(s_misc[M_PINV]) * (warp == 4 ? SM_C : 1.f), b = __uint_as_float(s_misc[M_PMEAN]) * a;
              ((uint32_t*)(smem + OFF_PATCH))[t] = pack_bf16(s0 * a - c.x * b, s1 * a - c.y * b);
            }
            PROF(25);
          }
          __syncwarp();
          mbar_arrive_e(bar(B_CS));
        }
        __syncwarp();
        if (wi == 0) mbar_wait(bar(B_QREADY), layer);
        named_bar(1 + (fresh_tid() >> 7), 128);
        if (__shfl_sync(0xffffffffu, fresh_tid() >> 7, 0) == 0) {
          regs_inc<152>();
          uint32_t gu[112];
          {
            PHASE_IDS
            const uint32_t tag = s_misc[M_TAG];
            mbar_wait(bar(B_GU), layer);
#pragma unroll
            for (int j = 0; j < 28; j++) fetch_gu(gu + 4 * j, warp * 4 + (j & 3), j >> 2);
            fence_async_smem();
            named_bar(1, 128);
            if (warp == 0) {
              mbar_wait(bar(B_ADONE), layer);
#pragma unroll 1
              for (int k = 2; k < 16; k++) {
#pragma unroll 1
                for (uint32_t spins = 0; (int)s_misc[M_PROG + (k >> 3)] <= (k & 7) + 16 * (int)layer && spins < SPIN_LIMIT; spins++) {}
                if (k >= 4) mbar_wait(bar(B_WEMPTY + (k & 3)), ((k >> 2) - 1 + ((k & 2) ? layer : 0)) & 1);
                load_o(k); load_wo(k);
                STEPT(16 + k);
                if (k == RES_K) { mbar_wait(bar(B_OST + 1), layer); load_res(1, layer); }
              }
              if (layer == 1) {
                mbar_wait(bar(B_WEMPTY + 1), 1);
                mbar_expect_tx(bar(B_DN), 4 * FFN_PIECE);
                tma_load3_h(sbase + wo_off(0), &P.mapD, 0, (cl * 56 + rank * 28), 0, bar(B_DN), policy_evict_first());
              }
              named_bar(6, 320);
              if (layer == 0) {
                mbar_wait(bar(B_QFREE), 0);
#pragma unroll 1
                for (int i = 0; i < 4; i++) load_w(i, i);
              } else tma_load3_h(sbase + wo_off(0) + 2 * FFN_PIECE, &P.mapD, 0, (cl * 56 + rank * 28), 8, bar(B_DN), policy_evict_first());
            } else if (warp < 3) {
              const int h = warp - 1;
#pragma unroll 1
              for (int qb = 3; qb >= 0; qb--) {
                mbar_wait(bar(B_UNIT + h * 4 + 3 - qb), layer);
                bulk_store(g_o + (size_t)((((rb * 2 + (qb >> 1)) * 2 + h) * 16 + hp) * 2 + (qb & 1)) * 4096, sbase + qo_off(h, qb), 4096);
              }
              bulk_commit();
              if (h == 0 && lane < 2) mbar_arrive_cluster(bar(B_OST), lane);
              bulk_wait_all();
              if (h == 1) mbar_arrive_e(bar(B_OST + 1));
              set_flag(&g_oflag[rb][h][hp].v[layer], tag);
              PROF(28 + 3 * h);
              if (h == 0) { load_res(0, layer); mbar_wait(bar(B_OST), layer); load_wo(0); load_wo(1); }
              int n = 0, first = h;
#pragma unroll 1
              for (uint32_t spins = 0; n < 8 && spins < SPIN_LIMIT; spins++) {
                n = (__ffs(__ballot_sync(0xffffffffu, ld_relaxed(&g_oflag[rb][h][lane & 15].v[layer]) != tag || lane == 16)) - 1) >> 1;
                asm volatile("fence.acquire.gpu;" ::: "memory");
                fence_async_global();
                if (!first && n >= 2) {
                  first = 1;
                  load_o(0); load_o(1);
                  PROF(15);
                }
                s_misc[M_PROG + h] = n + 16 * layer;
              }
              if (h) PROF(26);
            } else {
              mbar_expect_tx(bar(B_HX), 2240);
              mbar_wait(bar(B_HALO + 2), layer);
              if (rb == 0) spin_cycles(2000);
              PROF(6);
              load_gu(1, GUB_PACE);
            }
          }
          PHASE_IDS
          uint4 xa = {}, xb = {};
          named_bar(7, 512);
          if (g == 0) { xa = ((const uint4*)(smem + T_XS))[warp * 8 + q]; xb = ((const uint4*)(smem + T_XS))[warp * 8 + 4 + q]; }
          __syncwarp();
          float d[7][4] = {};
#pragma unroll
          for (int j = 0; j < 28; j++) {
            const int ks = j / 7, ct = j % 7;
            const uint32_t* a = gu + ct * 16 + ks * 4;
            mma_16816(d[ct], a[0], a[1], a[2], a[3], ks == 0 ? xa.x : ks == 1 ? xa.z : ks == 2 ? xb.x : xb.z, ks == 0 ? xa.y : ks == 1 ? xa.w : ks == 2 ? xb.y : xb.w);
          }
#pragma unroll
          for (int ct = 0; ct < 7; ct++) send_gu(d[ct][0], d[ct][2], ct, warp);
          __syncwarp();
          if (warp == 2) PROF(18);
          regs_dec<32>();
          pass_v = pass + 1;
          continue;
        }
        break;
      }
      regs_inc<120>();
    }
    const unsigned layer = pass;
    {
      PHASE_IDS
      mbar_wait(bar(B_QREADY), layer);
      if (warp != 9) STEPT(7);
      const int bmin = rb == 0 ? 4 : 0;
      auto kdesc = [&](int h, int b) { const uint32_t v = dlo(SOFF, 16) + (kv_off(h, b) >> 4); return b < bmin ? dlo(SOFF + kv_off(1, 0), 16) : v; };
      auto vdesc = [&](int h, int b) {
        const uint32_t v = dlo(SOFF + 4096, OFF_ONES - 4096) + (kv_off(h, b) >> 10) * VSTEP;
        return b < bmin ? dlo(SOFF + kv_off(1, 0), 4096) : v;
      };
      const int units = wg == 3 ? 0x8630 : (wg == 2 ? 0x8721 : 0x854);
      auto need = [&](int h, int b) { if (b == 3 || b == 1) mbar_wait(bar(B_HALO + (b == 1 ? 2 : h)), layer); };
      auto load_q = [&](uint32_t* qf, int u) {
        *(uint4*)&qf[0] = *(const uint4*)(smem + qo_off(u >> 2, ~u & 3) + wi * 1024 + lane * 16);
        *(uint4*)&qf[4] = *(const uint4*)(smem + qo_off(u >> 2, ~u & 3) + wi * 1024 + 512 + lane * 16);
      };
      auto store_o = [&](const float* o, int u) {
        const float i0 = rcp(o[16]), i1 = rcp(o[18]);
        if (u >= 4 && lane < 2) mbar_arrive_cluster(bar(B_ADONE), lane);
#pragma unroll
        for (int j = 0; j < 2; j++)
          stsm_x4(sbase + qo_off(u >> 2, ~u & 3) + srow * 64 + (((2 * j + (mi >> 1)) ^ ((srow >> 1) & 3)) << 4),
            pack_bf16(o[8 * j] * i0, o[8 * j + 1] * i0), pack_bf16(o[8 * j + 2] * i1, o[8 * j + 3] * i1),
            pack_bf16(o[8 * j + 4] * i0, o[8 * j + 5] * i0), pack_bf16(o[8 * j + 6] * i1, o[8 * j + 7] * i1));
        fence_async_smem();
        __syncwarp();
        mbar_arrive_e(bar(B_UNIT + u));
      };
      int redo = 0;
      {
        const int dl = g - 2 * q;
        const uint32_t mt = shl_clamp(0xFFFFFFFFu, max(16 * dl + 16, 0));
        uint32_t qf[8];
        float s[32];
        load_q(qf, units & 7);
        wg_fence();
        qk64(s, qf, kdesc((units >> 2) & 1, 6 - (units & 3)));
        wg_commit();
        wg_wait<0>();
        fence_regs<32>(s);
#pragma unroll 1
        for (int ul = units; ul != 8; ul >>= 4) {
          const int u = ul & 7, h = u >> 2, qb = 3 - (u & 3);
          float o[20];
          uint32_t p1[16], p2[16], p3[16], p4[16], p5[16];
          if (warp != 9) STEPT(8 + nu * 8);
          exp_pack<8>(s, p1);
          fence_regs_u<16>(p1);
          need(h, qb + 2);
          {
            float s2[32];
            const uint32_t vd = vdesc(h, qb + 3);
            wg_fence();
            qk64(s2, qf, kdesc(h, qb + 2));
            wg_commit();
            wg_rs40t_z<H64>(o, p1[0], p1[1], p1[2], p1[3], vd);
            wg_rs40t<H64>(o, p1[4], p1[5], p1[6], p1[7], vd + VSTEP, 1);
            pv32(o, p1 + 8, vd + 2 * VSTEP);
            wg_commit();
            wg_wait<1>();
            fence_regs<32>(s2);
            if (warp != 9) STEPT(9 + nu * 8);
            exp_pack<8>(s2, p2);
            fence_regs_u<16>(p2);
            wg_wait<0>();
            fence_regs<20>(o);
          }
          need(h, qb + 1);
          {
            float s3[32];
            wg_fence();
            qk64(s3, qf, kdesc(h, qb + 1));
            wg_commit();
            pv32(o, p2, vdesc(h, qb + 2)); pv32(o, p2 + 8, vdesc(h, qb + 2) + 2 * VSTEP);
            wg_commit();
            wg_wait<1>();
            fence_regs<32>(s3);
            if (warp != 9) STEPT(10 + nu * 8);
            exp_pack<8>(s3, p3);
            fence_regs_u<16>(p3);
            wg_wait<0>();
            fence_regs<20>(o);
          }
          need(h, qb);
          const uint32_t kd = kdesc(h, qb + 4), kt = kdesc(h, qb), vd = vdesc(h, qb + 4), vt = vdesc(h, qb);
          {
            float sd[16], st[16];
            wg_fence();
            qk32x2(sd, st, qf, kd, kt);
            wg_commit();
            pv32(o, p3, vdesc(h, qb + 1)); pv32(o, p3 + 8, vdesc(h, qb + 1) + 2 * VSTEP);
            wg_commit();
            wg_wait<1>();
            fence_regs<16>(sd); fence_regs<16>(st);
            if (warp != 9) STEPT(11 + nu * 8);
            edge32(sd, st, p4, p4 + 8, wi, dl, mt);
            fence_regs_u<16>(p4);
            wg_wait<0>();
            fence_regs<20>(o);
          }
          const int un = (ul >> 4) == 8 ? 4 : (ul >> 4) & 7;
          {
            float sd[16], st[16];
            wg_fence();
            qk32x2(sd, st, qf, kd + 128, kt + 128);
            wg_commit();
            pv32(o, p4, vd); pv32(o, p4 + 8, vt);
            wg_commit();
            wg_wait<1>();
            fence_regs<16>(sd); fence_regs<16>(st);
            load_q(qf, un);
            edge32(sd, st, p5, p5 + 8, wi - 2, dl, mt);
            fence_regs_u<16>(p5);
          }
          need(un >> 2, 6 - (un & 3));
          wg_fence();
          pv32(o, p5, vd + 2 * VSTEP); pv32(o, p5 + 8, vt + 2 * VSTEP);
          wg_commit();
          qk64(s, qf, kdesc(un >> 2, 6 - (un & 3)));
          wg_commit();
          wg_wait<1>();
          fence_regs<20>(o);
          if (warp != 9) STEPT(12 + nu * 8);
          const bool unsafe = !(o[16] >= LSUM_MIN && o[16] <= LSUM_MAX && o[18] >= LSUM_MIN && o[18] <= LSUM_MAX);
          if (__any_sync(0xffffffffu, unsafe)) redo |= 1 << u;
          else store_o(o, u);
          wg_wait<0>();
          fence_regs<32>(s);
        }
      }
      if (warp != 9) STEPT(31);
      if (bar_red_or(1 + wg, 128, redo)) {
#pragma unroll 1
        for (int ul = units; ul != 8; ul >>= 4) {
          const int u = ul & 7;
          if (!bar_red_or(1 + wg, 128, redo >> u & 1)) continue;
          const int h = u >> 2, qb = 3 - (u & 3);
          uint32_t qf[8], p[16];
          float o[20], m0 = -INFINITY, m1 = -INFINITY;
          load_q(qf, u);
#pragma unroll
          for (int i = 0; i < 20; i++) o[i] = 0.f;
#pragma unroll 1
          for (int j = 0; j <= (rb == 0 ? qb : 4); j++) {
            const int b = qb + 4 - j;
            float s[32];
            wg_fence();
            qk64(s, qf, kdesc(h, b));
            wg_commit();
            wg_wait<0>();
            fence_regs<32>(s);
            float mx0 = m0, mx1 = m1;
#pragma unroll
            for (int c = 0; c < 8; c++) {
#pragma unroll
              for (int i = 0; i < 4; i++) {
                const int diff = j * 64 + (16 * wi + g + (i >> 1) * 8) - (8 * c + 2 * q + (i & 1));
                if (diff < 0 || diff > 255) s[4 * c + i] = -INFINITY;
              }
              mx0 = fmaxf(mx0, fmaxf(s[4 * c], s[4 * c + 1]));
              mx1 = fmaxf(mx1, fmaxf(s[4 * c + 2], s[4 * c + 3]));
            }
            mx0 = fmaxf(mx0, __shfl_xor_sync(0xffffffffu, mx0, 1)); mx1 = fmaxf(mx1, __shfl_xor_sync(0xffffffffu, mx1, 1));
            mx0 = fmaxf(mx0, __shfl_xor_sync(0xffffffffu, mx0, 2)); mx1 = fmaxf(mx1, __shfl_xor_sync(0xffffffffu, mx1, 2));
            const float r0 = j == 0 ? 0.f : ex2(m0 - mx0), r1 = j == 0 ? 0.f : ex2(m1 - mx1);
            m0 = mx0; m1 = mx1;
#pragma unroll
            for (int i = 0; i < 5; i++) { o[4 * i] *= r0; o[4 * i + 1] *= r0; o[4 * i + 2] *= r1; o[4 * i + 3] *= r1; }
#pragma unroll
            for (int c = 0; c < 8; c++) { s[4 * c] -= m0; s[4 * c + 1] -= m0; s[4 * c + 2] -= m1; s[4 * c + 3] -= m1; }
            exp_pack<8>(s, p);
            fence_regs<20>(o); fence_regs_u<16>(p);
            wg_fence();
            pv32(o, p, vdesc(h, b)); pv32(o, p + 8, vdesc(h, b) + 2 * VSTEP);
            wg_commit();
            wg_wait<0>();
            fence_regs<20>(o);
          }
          named_bar(1 + wg, 128);
          if (redo >> u & 1) store_o(o, u);
          __syncwarp();
        }
      }
      if (wi == 0) PROF(6 + wg);
    }
    pass_v = pass + 1;
  }
}

}

typedef CUresult (*EncodeFn)(CUtensorMap*, CUtensorMapDataType, cuuint32_t, void*, const cuuint64_t*, const cuuint64_t*,
                             const cuuint32_t*, const cuuint32_t*, CUtensorMapInterleave, CUtensorMapSwizzle,
                             CUtensorMapL2promotion, CUtensorMapFloatOOBfill);
static EncodeFn g_encode = nullptr;
struct Dim { uint64_t size, stride; uint32_t box; };
template <int N> static CUtensorMap make_map(const void* ptr, const Dim (&d)[N], int swizzle) {
  CUtensorMap m;
  cuuint64_t dims[N], strides[N];
  cuuint32_t box[N], es[N];
  for (int i = 0; i < N; i++) { dims[i] = d[i].size; strides[i] = d[i].stride; box[i] = d[i].box; es[i] = 1; }
  g_encode(&m, CU_TENSOR_MAP_DATA_TYPE_BFLOAT16, N, const_cast<void*>(ptr), dims, strides + 1, box, es, CU_TENSOR_MAP_INTERLEAVE_NONE,
           swizzle == 128 ? CU_TENSOR_MAP_SWIZZLE_128B : (swizzle == 64 ? CU_TENSOR_MAP_SWIZZLE_64B : CU_TENSOR_MAP_SWIZZLE_NONE),
           swizzle ? CU_TENSOR_MAP_L2_PROMOTION_L2_256B : CU_TENSOR_MAP_L2_PROMOTION_L2_128B, CU_TENSOR_MAP_FLOAT_OOB_FILL_NONE);
  return m;
}
static CUtensorMap map2(const void* ptr, uint64_t inner, uint64_t outer, uint32_t bi, uint32_t bo, int swizzle) {
  const Dim d[2] = {{inner, 0, bi}, {outer, inner * 2, bo}};
  return make_map(ptr, d, swizzle);
}
template <class T> static void* sym_addr(T& sym) { void* p = nullptr; cudaGetSymbolAddress(&p, sym); return p; }

static Params h_p;
static const void* h_key[9];

static cudaLaunchConfig_t launch_cfg(int grid, cudaLaunchAttribute* at) {
  cudaLaunchConfig_t cfg = {};
  cfg.gridDim = dim3(grid); cfg.blockDim = dim3(512); cfg.dynamicSmemBytes = SMEM_BYTES; cfg.stream = cudaStreamPerThread;
  at[0].id = cudaLaunchAttributeClusterDimension;
  at[0].val.clusterDim.x = 2; at[0].val.clusterDim.y = 1; at[0].val.clusterDim.z = 1;
  cfg.attrs = at; cfg.numAttrs = 1;
  return cfg;
}

extern "C" void kernel_launch(void* const* d_in, const int* in_sizes, int n_in, void* d_out, int out_size) {
  const bf16* x = (const bf16*)d_in[0];
  const bf16* wqkv = (const bf16*)d_in[1];
  const bf16* wo = (const bf16*)d_in[2];
  cudaLaunchAttribute at[1];
  bool fresh = g_encode != nullptr && h_key[8] == d_out;
  for (int i = 0; i < 8; i++) fresh = fresh && h_key[i] == d_in[i];
  if (!fresh) {
    if (!g_encode) {
      void* fn = nullptr;
      cudaDriverEntryPointQueryResult st;
      cudaGetDriverEntryPoint("cuTensorMapEncodeTiled", &fn, cudaEnableDefault, &st);
      g_encode = (EncodeFn)fn;
      cudaFuncSetAttribute(mega_kernel, cudaFuncAttributeMaxDynamicSharedMemorySize, SMEM_BYTES);
    }
    bf16* x1 = (bf16*)sym_addr(g_x1);
    Params& p = h_p;
    p.w_r = (const bf16*)d_in[4]; p.w_d = (const bf16*)d_in[7];
    p.out = (bf16*)d_out;
    p.mapA[0] = map2(x, DM, SEQ, 64, 256, 128);
    p.mapA[1] = map2(x1, DM, SEQ, 64, 256, 128);
    { const Dim d[3] = {{DM, 0, 64}, {DM, 3 * DM * 2, 16}, {3, DM * 2, 3}}; p.mapW = make_map(wqkv, d, 128); }
    { const Dim d[3] = {{DM, 0, 64}, {DM, 3 * DM * 2, 32}, {3, DM * 2, 3}}; p.mapWs = make_map(wqkv, d, 128); }
    { const Dim d[3] = {{DM, 0, 64}, {64, DM * 2, 32}, {16, 64 * DM * 2, 2}}; p.mapWo = make_map(wo, d, 128); }
    p.mapRes[0] = map2(x, DM, SEQ, 64, 64, 128);
    p.mapRes[1] = p.mapXst[0] = map2(x1, DM, SEQ, 64, 64, 128);
    p.mapXst[1] = map2(d_out, DM, SEQ, 64, 64, 128);
    p.mapG = map2(d_in[5], FF, DM, 56, 128, 0);
    p.mapU = map2(d_in[6], FF, DM, 56, 128, 0);
    { const Dim d[3] = {{64, 0, 64}, {FF, DM * 2, 28}, {DM / 64, 128, 8}}; p.mapD = make_map(p.w_d, d, 128); }
    for (int b = 0; b < 128; b++) {
      static const int perm[8] = {0, 6, 4, 5, 1, 2, 3, 7};
      const int c = b >> 1, col = c < 4 ? 0 : (c < 36 ? (c - 4) & 7 : (c - 36) % 7 + 1), j = c < 4 ? 4 + c : (c < 36 ? (c - 4) >> 3 : 4 + (c - 36) / 7);
      p.role[b] = (b & 1) | (perm[col] >> 1) << 1 | j << 3 | (perm[col] & 1) << 6;
    }
    for (int i = 0; i < 8; i++) h_key[i] = d_in[i];
    h_key[8] = d_out;
  }
  void* a0[] = {&h_p};
  cudaLaunchConfig_t cfg = launch_cfg(128, at);
  cudaLaunchKernelExC(&cfg, (const void*)mega_kernel, a0);
}
```

```cpp
#include <cuda_runtime.h>
#include <cuda_bf16.h>
#include <cuda.h>
#include <stdint.h>
#pragma nv_diag_suppress 550

namespace {

constexpr int SEQ = 2048, DM = 1024, FF = 3584;
constexpr float LN_EPS = 1e-5f;
typedef __nv_bfloat16 bf16;

__device__ __align__(1024) uint8_t g_kv[3 * 16 * 65536];
__device__ __align__(1024) uint8_t g_o[SEQ * DM * 2];
__device__ __align__(1024) bf16 g_x1[SEQ * DM];
__device__ unsigned g_epoch;
struct __align__(128) Flag { unsigned v[32]; };
__device__ Flag g_kvflag[3][16][2], g_oflag[8][2][16], g_xflag[16][8];
__device__ uint4 g_rowab[2][SEQ];
__device__ __align__(16) uint32_t g_vw[2][8][3 * DM];
constexpr uint32_t SENT = 0xFFFFFFFFu;
__device__ uint4 g_part[2][8 * SEQ];
__device__ uint4 g_slot[2][16 * 8];
__device__ uint4 g_cand[2][16 * 128];
__device__ uint4 g_ypart[2][128 * DM / 4];
__device__ uint4 g_x2row[128 * 2];
__device__ float2 g_rowln[8][SEQ];
__device__ int g_sel[2];

#define PROFL(l, e)
#define PROF(e) PROFL(layer, e)
#define STEPT(i)
#define SPIN_LIMIT 4000000u
__device__ __forceinline__ uint32_t smem_u32(const void* p) { return (uint32_t)__cvta_generic_to_shared(p); }
__device__ __forceinline__ void mbar_init(uint32_t bar, uint32_t cnt) {
  asm volatile("mbarrier.init.shared::cta.b64 [%0], %1;" ::"r"(bar), "r"(cnt) : "memory");
}
#define ELECT "{\n.reg .pred e;\nelect.sync _|e, 0xffffffff;\n@e "
__device__ __forceinline__ void mbar_expect_tx(uint32_t bar, uint32_t bytes) {
  asm volatile(ELECT "mbarrier.arrive.expect_tx.shared::cta.b64 _, [%0], %1;\n}" ::"r"(bar), "r"(bytes) : "memory");
}
__device__ __forceinline__ void mbar_arrive(uint32_t bar) {
  asm volatile("mbarrier.arrive.shared::cta.b64 _, [%0];" ::"r"(bar) : "memory");
}
__device__ __forceinline__ void mbar_arrive_e(uint32_t bar) {
  asm volatile(ELECT "mbarrier.arrive.shared::cta.b64 _, [%0];\n}" ::"r"(bar) : "memory");
}
__device__ __forceinline__ uint32_t mapa(uint32_t addr, uint32_t cta) {
  uint32_t r; asm("mapa.shared::cluster.u32 %0, %1, %2;" : "=r"(r) : "r"(addr), "r"(cta)); return r;
}
__device__ __forceinline__ void mbar_arrive_cluster(uint32_t bar, uint32_t cta) {
  asm volatile("mbarrier.arrive.shared::cluster.b64 _, [%0];" ::"r"(mapa(bar, cta)) : "memory");
}
#define MBAR_WAIT_ASM(QUAL)                                                                                                \
  asm volatile("{\n.reg .pred p;\nWAIT_LOOP:\n.pragma \"nounroll\";\nmbarrier.try_wait.parity" QUAL ".shared::cta.b64 p, [%0], %1;\n" \
               "@!p bra WAIT_LOOP;\n}" ::"r"(bar), "r"(parity) : "memory")
__device__ __forceinline__ void mbar_wait(uint32_t bar, uint32_t parity) { MBAR_WAIT_ASM(""); }
__device__ __forceinline__ void mbar_wait_cluster(uint32_t bar, uint32_t parity) { MBAR_WAIT_ASM(".acquire.cluster"); }
__device__ __forceinline__ void st_async2(uint32_t addr, float a, float b, uint32_t bar) {
  asm volatile("st.async.weak.shared::cluster.mbarrier::complete_tx::bytes.v2.f32 [%0], {%1, %2}, [%3];"
               ::"r"(addr), "f"(a), "f"(b), "r"(bar) : "memory");
}
__device__ __forceinline__ uint64_t policy_evict_first() {
  uint64_t p; asm volatile("createpolicy.fractional.L2::evict_first.b64 %0, 1.0;" : "=l"(p)); return p;
}
__device__ __forceinline__ void tma_load2(uint32_t dst, const CUtensorMap* m, int c0, int c1, uint32_t bar) {
  asm volatile(ELECT "cp.async.bulk.tensor.2d.shared::cluster.global.mbarrier::complete_tx::bytes [%0], [%1, {%3, %4}], [%2];\n}"
               ::"r"(dst), "l"(m), "r"(bar), "r"(c0), "r"(c1) : "memory");
}
__device__ __forceinline__ void tma_load2_h(uint32_t dst, const CUtensorMap* m, int c0, int c1, uint32_t bar, uint64_t pol) {
  asm volatile(ELECT "cp.async.bulk.tensor.2d.shared::cluster.global.mbarrier::complete_tx::bytes.L2::cache_hint [%0], [%1, {%3, %4}], [%2], %5;\n}"
               ::"r"(dst), "l"(m), "r"(bar), "r"(c0), "r"(c1), "l"(pol) : "memory");
}
__device__ __forceinline__ void tma_load3(uint32_t dst, const CUtensorMap* m, int c0, int c1, int c2, uint32_t bar) {
  asm volatile(ELECT "cp.async.bulk.tensor.3d.shared::cluster.global.mbarrier::complete_tx::bytes [%0], [%1, {%3, %4, %5}], [%2];\n}"
               ::"r"(dst), "l"(m), "r"(bar), "r"(c0), "r"(c1), "r"(c2) : "memory");
}
__device__ __forceinline__ void tma_load3_h(uint32_t dst, const CUtensorMap* m, int c0, int c1, int c2, uint32_t bar, uint64_t pol) {
  asm volatile(ELECT "cp.async.bulk.tensor.3d.shared::cluster.global.mbarrier::complete_tx::bytes.L2::cache_hint [%0], [%1, {%3, %4, %5}], [%2], %6;\n}"
               ::"r"(dst), "l"(m), "r"(bar), "r"(c0), "r"(c1), "r"(c2), "l"(pol) : "memory");
}
__device__ __forceinline__ void tma_load3_mc(uint32_t dst, const CUtensorMap* m, int c0, int c1, int c2, uint32_t bar) {
  asm volatile(ELECT "cp.async.bulk.tensor.3d.shared::cluster.global.mbarrier::complete_tx::bytes.multicast::cluster [%0], [%1, {%3, %4, %5}], [%2], %6;\n}"
               ::"r"(dst), "l"(m), "r"(bar), "r"(c0), "r"(c1), "r"(c2), "h"((uint16_t)3) : "memory");
}
__device__ __forceinline__ void bulk_push(uint32_t dst, uint32_t src, uint32_t bytes, uint32_t bar) {
  asm volatile(ELECT "cp.async.bulk.shared::cluster.shared::cta.mbarrier::complete_tx::bytes [%0], [%1], %2, [%3];\n}"
               ::"r"(dst), "r"(src), "r"(bytes), "r"(bar) : "memory");
}
template <int N> __device__ __forceinline__ void regs_inc() { asm volatile("setmaxnreg.inc.sync.aligned.u32 %0;" ::"n"(N)); }
template <int N> __device__ __forceinline__ void regs_dec() { asm volatile("setmaxnreg.dec.sync.aligned.u32 %0;" ::"n"(N)); }
__device__ __forceinline__ void tma_store(const CUtensorMap* m, uint32_t src, int c0, int c1) {
  asm volatile(ELECT "cp.async.bulk.tensor.2d.global.shared::cta.bulk_group [%0, {%2, %3}], [%1];\n}"
               ::"l"(m), "r"(src), "r"(c0), "r"(c1) : "memory");
}
__device__ __forceinline__ void bulk_load_h(uint32_t dst, const void* src, uint32_t bytes, uint32_t bar, uint64_t pol) {
  asm volatile(ELECT "cp.async.bulk.shared::cluster.global.mbarrier::complete_tx::bytes.L2::cache_hint [%0], [%1], %2, [%3], %4;\n}"
               ::"r"(dst), "l"(src), "r"(bytes), "r"(bar), "l"(pol) : "memory");
}
__device__ __forceinline__ void bulk_store(void* dst, uint32_t src, uint32_t bytes) {
  asm volatile(ELECT "cp.async.bulk.global.shared::cta.bulk_group [%0], [%1], %2;\n}" ::"l"(dst), "r"(src), "r"(bytes) : "memory");
}
__device__ __forceinline__ void bulk_commit() { asm volatile("cp.async.bulk.commit_group;" ::: "memory"); }
__device__ __forceinline__ void bulk_wait_all() { asm volatile("cp.async.bulk.wait_group 0;" ::: "memory"); }
__device__ __forceinline__ void fence_async_smem() { asm volatile("fence.proxy.async.shared::cta;" ::: "memory"); }
__device__ __forceinline__ void fence_async_global() { asm volatile("fence.proxy.async.global;" ::: "memory"); }
__device__ __forceinline__ void prefetch_tmap(const CUtensorMap* m) { asm volatile("prefetch.tensormap [%0];" ::"l"(m) : "memory"); }
__device__ __forceinline__ void named_bar(int id, int n) { asm volatile("bar.sync %0, %1;" ::"r"(id), "r"(n) : "memory"); }
__device__ __forceinline__ bool bar_red_or(int id, int n, bool v) {
  uint32_t r;
  asm volatile("{\n.reg .pred p, q;\nsetp.ne.u32 q, %3, 0;\nbarrier.cta.red.or.pred p, %1, %2, q;\nselp.u32 %0, 1, 0, p;\n}"
               : "=r"(r) : "r"(id), "r"(n), "r"((uint32_t)v) : "memory");
  return r != 0;
}
__device__ __forceinline__ void cluster_arrive() { asm volatile("barrier.cluster.arrive.relaxed.aligned;" ::: "memory"); }
__device__ __forceinline__ void cluster_wait() { asm volatile("barrier.cluster.wait.aligned;" ::: "memory"); }
__device__ __forceinline__ unsigned ld_relaxed(const unsigned* p) {
  unsigned v; asm volatile("ld.relaxed.gpu.global.u32 %0, [%1];" : "=r"(v) : "l"(p) : "memory"); return v;
}
__device__ __forceinline__ uint4 ld_relaxed4(const uint4* p) {
  uint4 v; asm volatile("ld.relaxed.gpu.global.v4.u32 {%0, %1, %2, %3}, [%4];" : "=r"(v.x), "=r"(v.y), "=r"(v.z), "=r"(v.w) : "l"(p) : "memory"); return v;
}
__device__ __forceinline__ void st_relaxed(unsigned* p, unsigned v) {
  asm volatile("st.relaxed.gpu.global.u32 [%0], %1;" ::"l"(p), "r"(v) : "memory");
}
__device__ __forceinline__ uint2 ld_relaxed2(const void* p) {
  uint2 v; asm volatile("ld.relaxed.gpu.global.v2.u32 {%0, %1}, [%2];" : "=r"(v.x), "=r"(v.y) : "l"(p) : "memory"); return v;
}
__device__ __forceinline__ void st_relaxed4(uint4* p, uint4 v) {
  asm volatile("st.relaxed.gpu.global.v4.u32 [%0], {%1, %2, %3, %4};" ::"l"(p), "r"(v.x), "r"(v.y), "r"(v.z), "r"(v.w) : "memory");
}
__device__ __forceinline__ bool valid4(uint4 v) { return v.x != SENT && v.y != SENT && v.z != SENT && v.w != SENT; }
__device__ __forceinline__ uint4 poll4(const uint4* p) {
  uint4 v;
  uint32_t spins = 0;
#pragma unroll 1
  do { v = ld_relaxed4(p); } while (!valid4(v) && ++spins < SPIN_LIMIT);
  return v;
}
__device__ __forceinline__ void set_flag(unsigned* p, unsigned tag) {
  asm volatile(ELECT "st.release.gpu.global.u32 [%0], %1;\n}" ::"l"(p), "r"(tag) : "memory");
}
__device__ __forceinline__ void poll_flag(const unsigned* p, unsigned tag) {
#pragma unroll 1
  for (uint32_t spins = 0; !__all_sync(0xffffffffu, ld_relaxed(p) == tag) && spins < SPIN_LIMIT; spins++) {}
  asm volatile("fence.acquire.gpu;" ::: "memory");
}
__device__ __forceinline__ uint32_t enc(float x) { return __float_as_uint(x + 0.0f) ^ 0x80000000u; }
__device__ __forceinline__ float dec(uint32_t u) { return __uint_as_float(u ^ 0x80000000u); }
__device__ __forceinline__ uint32_t hadd_bf2(uint32_t a, uint32_t b) {
  uint32_t r; asm("add.rn.bf16x2 %0, %1, %2;" : "=r"(r) : "r"(a), "r"(b)); return r;
}
__device__ __forceinline__ uint32_t hsub_bf2(uint32_t a, uint32_t b) {
  uint32_t r; asm("sub.rn.bf16x2 %0, %1, %2;" : "=r"(r) : "r"(a), "r"(b)); return r;
}
__device__ __forceinline__ void wg_fence() { asm volatile("wgmma.fence.sync.aligned;" ::: "memory"); }
__device__ __forceinline__ void wg_commit() { asm volatile("wgmma.commit_group.sync.aligned;" ::: "memory"); }
template <int N> __device__ __forceinline__ void wg_wait() { asm volatile("wgmma.wait_group.sync.aligned %0;" ::"n"(N) : "memory"); }
template <int R> __device__ __forceinline__ void fence_regs(float* d) {
#pragma unroll
  for (int i = 0; i < R; i++) asm volatile("" : "+f"(d[i])::"memory");
}
template <int R> __device__ __forceinline__ void fence_regs_u(uint32_t* d) {
#pragma unroll
  for (int i = 0; i < R; i++) asm volatile("" : "+r"(d[i])::"memory");
}
__host__ __device__ constexpr uint32_t dlo(uint32_t addr, uint32_t lbo) { return ((addr & 0x3FFFF) >> 4) | ((lbo >> 4) << 16); }
constexpr uint32_t H128 = 0x40000040u, H64 = 0x80000020u;
__device__ __forceinline__ void stsm_x4(uint32_t addr, uint32_t r0, uint32_t r1, uint32_t r2, uint32_t r3) {
  asm volatile("stmatrix.sync.aligned.m8n8.x4.shared.b16 [%0], {%1, %2, %3, %4};"
               ::"r"(addr), "r"(r0), "r"(r1), "r"(r2), "r"(r3) : "memory");
}
__device__ __forceinline__ void ldsm_x4(uint32_t addr, uint32_t& r0, uint32_t& r1, uint32_t& r2, uint32_t& r3) {
  asm volatile("ldmatrix.sync.aligned.m8n8.x4.shared.b16 {%0, %1, %2, %3}, [%4];"
               : "=r"(r0), "=r"(r1), "=r"(r2), "=r"(r3) : "r"(addr) : "memory");
}
__device__ __forceinline__ void ldsm_x4_t(uint32_t addr, uint32_t& r0, uint32_t& r1, uint32_t& r2, uint32_t& r3) {
  asm volatile("ldmatrix.sync.aligned.m8n8.x4.trans.shared.b16 {%0, %1, %2, %3}, [%4];"
               : "=r"(r0), "=r"(r1), "=r"(r2), "=r"(r3) : "r"(addr) : "memory");
}
__device__ __forceinline__ void mma_16816(float* d, uint32_t a0, uint32_t a1, uint32_t a2, uint32_t a3, uint32_t b0, uint32_t b1) {
  asm volatile("mma.sync.aligned.m16n8k16.row.col.f32.bf16.bf16.f32 {%0, %1, %2, %3}, {%4, %5, %6, %7}, {%8, %9}, {%0, %1, %2, %3};"
               : "+f"(d[0]), "+f"(d[1]), "+f"(d[2]), "+f"(d[3]) : "r"(a0), "r"(a1), "r"(a2), "r"(a3), "r"(b0), "r"(b1));
}
__device__ __forceinline__ void spin_cycles(int n) {
  const int t0 = (int)clock();
#pragma unroll 1
  while ((int)clock() - t0 < n) {}
}
__device__ __forceinline__ uint32_t pack_bf16(float lo, float hi) {
  uint32_t r; asm("cvt.rn.bf16x2.f32 %0, %1, %2;" : "=r"(r) : "f"(hi), "f"(lo)); return r;
}
__device__ __forceinline__ float bf_lo(uint32_t v) { return __uint_as_float(v << 16); }
__device__ __forceinline__ float bf_hi(uint32_t v) { return __uint_as_float(v & 0xffff0000u); }
__device__ __forceinline__ float rbf(float x) { return __bfloat162float(__float2bfloat16_rn(x)); }
__device__ __forceinline__ float ex2(float x) { float y; asm("ex2.approx.ftz.f32 %0, %1;" : "=f"(y) : "f"(x)); return y; }
__device__ __forceinline__ float rcp(float x) { float y; asm("rcp.approx.ftz.f32 %0, %1;" : "=f"(y) : "f"(x)); return y; }
__device__ __forceinline__ uint32_t shl_clamp(uint32_t v, uint32_t n) {
  uint32_t r; asm("shl.b32 %0, %1, %2;" : "=r"(r) : "r"(v), "r"(n)); return r;
}
__device__ __forceinline__ float warp_sum(float v) {
#pragma unroll
  for (int o = 16; o > 0; o >>= 1) v += __shfl_xor_sync(0xffffffffu, v, o);
  return v;
}
__device__ __forceinline__ float ln_inv(float var) {
  float r;
  asm("sqrt.approx.ftz.f32 %0, %1;" : "=f"(r) : "f"(rbf(rbf(var) + LN_EPS)));
  asm("rcp.approx.ftz.f32 %0, %1;" : "=f"(r) : "f"(rbf(r)));
  return r;
}
__device__ __forceinline__ uint32_t ln_pair(uint32_t x, uint32_t mean2, float inv) {
  const uint32_t d = hsub_bf2(x, mean2);
  return pack_bf16(bf_lo(d) * inv, bf_hi(d) * inv);
}
__device__ __forceinline__ uint32_t add_ln_pair(uint32_t x, uint32_t mean2, float inv) { return hadd_bf2(x, ln_pair(x, mean2, inv)); }
__device__ __forceinline__ uint32_t router_key(float r_bf, int row) {
  uint32_t u = __float_as_uint(r_bf);
  u = (u & 0x80000000u) ? ~u : (u | 0x80000000u);
  return (u & 0xFFFF0000u) | 0x8000u | (uint32_t)(SEQ - 1 - row);
}

template <uint32_t HA = 0x40000040u, uint32_t HB = 0x40000040u>
__device__ __forceinline__ void wg_ss192t(float* d, uint32_t da, uint32_t db, int scale_d) {
  asm volatile("{\n.reg .pred p;\n.reg .b64 dA, dB;\nmov.b64 dA, {%96, %99};\nmov.b64 dB, {%97, %100};\nsetp.ne.b32 p, %98, 0;\n"
    "wgmma.mma_async.sync.aligned.m64n192k16.f32.bf16.bf16 "
    "{%0, %1, %2, %3, %4, %5, %6, %7, %8, %9, %10, %11, %12, %13, %14, %15, "
    "%16, %17, %18, %19, %20, %21, %22, %23, %24, %25, %26, %27, %28, %29, %30, %31, "
    "%32, %33, %34, %35, %36, %37, %38, %39, %40, %41, %42, %43, %44, %45, %46, %47, "
    "%48, %49, %50, %51, %52, %53, %54, %55, %56, %57, %58, %59, %60, %61, %62, %63, "
    "%64, %65, %66, %67, %68, %69, %70, %71, %72, %73, %74, %75, %76, %77, %78, %79, "
    "%80, %81, %82, %83, %84, %85, %86, %87, %88, %89, %90, %91, %92, %93, %94, %95}, "
    "dA, dB, p, 1, 1, 0, 1;\n}\n"
    : "+f"(d[0]), "+f"(d[1]), "+f"(d[2]), "+f"(d[3]), "+f"(d[4]), "+f"(d[5]), "+f"(d[6]), "+f"(d[7]),
      "+f"(d[8]), "+f"(d[9]), "+f"(d[10]), "+f"(d[11]), "+f"(d[12]), "+f"(d[13]), "+f"(d[14]), "+f"(d[15]),
      "+f"(d[16]), "+f"(d[17]), "+f"(d[18]), "+f"(d[19]), "+f"(d[20]), "+f"(d[21]), "+f"(d[22]), "+f"(d[23]),
      "+f"(d[24]), "+f"(d[25]), "+f"(d[26]), "+f"(d[27]), "+f"(d[28]), "+f"(d[29]), "+f"(d[30]), "+f"(d[31]),
      "+f"(d[32]), "+f"(d[33]), "+f"(d[34]), "+f"(d[35]), "+f"(d[36]), "+f"(d[37]), "+f"(d[38]), "+f"(d[39]),
      "+f"(d[40]), "+f"(d[41]), "+f"(d[42]), "+f"(d[43]), "+f"(d[44]), "+f"(d[45]), "+f"(d[46]), "+f"(d[47]),
      "+f"(d[48]), "+f"(d[49]), "+f"(d[50]), "+f"(d[51]), "+f"(d[52]), "+f"(d[53]), "+f"(d[54]), "+f"(d[55]),
      "+f"(d[56]), "+f"(d[57]), "+f"(d[58]), "+f"(d[59]), "+f"(d[60]), "+f"(d[61]), "+f"(d[62]), "+f"(d[63]),
      "+f"(d[64]), "+f"(d[65]), "+f"(d[66]), "+f"(d[67]), "+f"(d[68]), "+f"(d[69]), "+f"(d[70]), "+f"(d[71]),
      "+f"(d[72]), "+f"(d[73]), "+f"(d[74]), "+f"(d[75]), "+f"(d[76]), "+f"(d[77]), "+f"(d[78]), "+f"(d[79]),
      "+f"(d[80]), "+f"(d[81]), "+f"(d[82]), "+f"(d[83]), "+f"(d[84]), "+f"(d[85]), "+f"(d[86]), "+f"(d[87]),
      "+f"(d[88]), "+f"(d[89]), "+f"(d[90]), "+f"(d[91]), "+f"(d[92]), "+f"(d[93]), "+f"(d[94]), "+f"(d[95])
    : "r"(da), "r"(db), "r"(scale_d), "n"(HA), "n"(HB));
}
template <uint32_t HA = 0x40000040u, uint32_t HB = 0x40000040u>
__device__ __forceinline__ void wg_ss192t_z(float* d, uint32_t da, uint32_t db) {
  asm volatile("{\n.reg .pred p;\n.reg .b64 dA, dB;\nmov.b64 dA, {%96, %98};\nmov.b64 dB, {%97, %99};\nsetp.ne.b32 p, 0, 0;\n"
    "wgmma.mma_async.sync.aligned.m64n192k16.f32.bf16.bf16 "
    "{%0, %1, %2, %3, %4, %5, %6, %7, %8, %9, %10, %11, %12, %13, %14, %15, "
    "%16, %17, %18, %19, %20, %21, %22, %23, %24, %25, %26, %27, %28, %29, %30, %31, "
    "%32, %33, %34, %35, %36, %37, %38, %39, %40, %41, %42, %43, %44, %45, %46, %47, "
    "%48, %49, %50, %51, %52, %53, %54, %55, %56, %57, %58, %59, %60, %61, %62, %63, "
    "%64, %65, %66, %67, %68, %69, %70, %71, %72, %73, %74, %75, %76, %77, %78, %79, "
    "%80, %81, %82, %83, %84, %85, %86, %87, %88, %89, %90, %91, %92, %93, %94, %95}, "
    "dA, dB, p, 1, 1, 0, 1;\n}\n"
    : "=f"(d[0]), "=f"(d[1]), "=f"(d[2]), "=f"(d[3]), "=f"(d[4]), "=f"(d[5]), "=f"(d[6]), "=f"(d[7]),
      "=f"(d[8]), "=f"(d[9]), "=f"(d[10]), "=f"(d[11]), "=f"(d[12]), "=f"(d[13]), "=f"(d[14]), "=f"(d[15]),
      "=f"(d[16]), "=f"(d[17]), "=f"(d[18]), "=f"(d[19]), "=f"(d[20]), "=f"(d[21]), "=f"(d[22]), "=f"(d[23]),
      "=f"(d[24]), "=f"(d[25]), "=f"(d[26]), "=f"(d[27]), "=f"(d[28]), "=f"(d[29]), "=f"(d[30]), "=f"(d[31]),
      "=f"(d[32]), "=f"(d[33]), "=f"(d[34]), "=f"(d[35]), "=f"(d[36]), "=f"(d[37]), "=f"(d[38]), "=f"(d[39]),
      "=f"(d[40]), "=f"(d[41]), "=f"(d[42]), "=f"(d[43]), "=f"(d[44]), "=f"(d[45]), "=f"(d[46]), "=f"(d[47]),
      "=f"(d[48]), "=f"(d[49]), "=f"(d[50]), "=f"(d[51]), "=f"(d[52]), "=f"(d[53]), "=f"(d[54]), "=f"(d[55]),
      "=f"(d[56]), "=f"(d[57]), "=f"(d[58]), "=f"(d[59]), "=f"(d[60]), "=f"(d[61]), "=f"(d[62]), "=f"(d[63]),
      "=f"(d[64]), "=f"(d[65]), "=f"(d[66]), "=f"(d[67]), "=f"(d[68]), "=f"(d[69]), "=f"(d[70]), "=f"(d[71]),
      "=f"(d[72]), "=f"(d[73]), "=f"(d[74]), "=f"(d[75]), "=f"(d[76]), "=f"(d[77]), "=f"(d[78]), "=f"(d[79]),
      "=f"(d[80]), "=f"(d[81]), "=f"(d[82]), "=f"(d[83]), "=f"(d[84]), "=f"(d[85]), "=f"(d[86]), "=f"(d[87]),
      "=f"(d[88]), "=f"(d[89]), "=f"(d[90]), "=f"(d[91]), "=f"(d[92]), "=f"(d[93]), "=f"(d[94]), "=f"(d[95])
    : "r"(da), "r"(db), "n"(HA), "n"(HB));
}
template <uint32_t HA = 0x40000040u, uint32_t HB = 0x40000040u>
__device__ __forceinline__ void wg_ss128t(float* d, uint32_t da, uint32_t db, int scale_d) {
  asm volatile("{\n.reg .pred p;\n.reg .b64 dA, dB;\nmov.b64 dA, {%64, %67};\nmov.b64 dB, {%65, %68};\nsetp.ne.b32 p, %66, 0;\n"
    "wgmma.mma_async.sync.aligned.m64n128k16.f32.bf16.bf16 "
    "{%0, %1, %2, %3, %4, %5, %6, %7, %8, %9, %10, %11, %12, %13, %14, %15, "
    "%16, %17, %18, %19, %20, %21, %22, %23, %24, %25, %26, %27, %28, %29, %30, %31, "
    "%32, %33, %34, %35, %36, %37, %38, %39, %40, %41, %42, %43, %44, %45, %46, %47, "
    "%48, %49, %50, %51, %52, %53, %54, %55, %56, %57, %58, %59, %60, %61, %62, %63}, "
    "dA, dB, p, 1, 1, 0, 1;\n}\n"
    : "+f"(d[0]), "+f"(d[1]), "+f"(d[2]), "+f"(d[3]), "+f"(d[4]), "+f"(d[5]), "+f"(d[6]), "+f"(d[7]),
      "+f"(d[8]), "+f"(d[9]), "+f"(d[10]), "+f"(d[11]), "+f"(d[12]), "+f"(d[13]), "+f"(d[14]), "+f"(d[15]),
      "+f"(d[16]), "+f"(d[17]), "+f"(d[18]), "+f"(d[19]), "+f"(d[20]), "+f"(d[21]), "+f"(d[22]), "+f"(d[23]),
      "+f"(d[24]), "+f"(d[25]), "+f"(d[26]), "+f"(d[27]), "+f"(d[28]), "+f"(d[29]), "+f"(d[30]), "+f"(d[31]),
      "+f"(d[32]), "+f"(d[33]), "+f"(d[34]), "+f"(d[35]), "+f"(d[36]), "+f"(d[37]), "+f"(d[38]), "+f"(d[39]),
      "+f"(d[40]), "+f"(d[41]), "+f"(d[42]), "+f"(d[43]), "+f"(d[44]), "+f"(d[45]), "+f"(d[46]), "+f"(d[47]),
      "+f"(d[48]), "+f"(d[49]), "+f"(d[50]), "+f"(d[51]), "+f"(d[52]), "+f"(d[53]), "+f"(d[54]), "+f"(d[55]),
      "+f"(d[56]), "+f"(d[57]), "+f"(d[58]), "+f"(d[59]), "+f"(d[60]), "+f"(d[61]), "+f"(d[62]), "+f"(d[63])
    : "r"(da), "r"(db), "r"(scale_d), "n"(HA), "n"(HB));
}
template <uint32_t HB = 0x40000040u>
__device__ __forceinline__ void wg_rs64(float* d, uint32_t a0, uint32_t a1, uint32_t a2, uint32_t a3, uint32_t db, int scale_d) {
  asm volatile("{\n.reg .pred p;\n.reg .b64 dB;\nmov.b64 dB, {%36, %38};\nsetp.ne.b32 p, %37, 0;\n"
    "wgmma.mma_async.sync.aligned.m64n64k16.f32.bf16.bf16 "
    "{%0, %1, %2, %3, %4, %5, %6, %7, %8, %9, %10, %11, %12, %13, %14, %15, "
    "%16, %17, %18, %19, %20, %21, %22, %23, %24, %25, %26, %27, %28, %29, %30, %31}, "
    "{%32, %33, %34, %35}, dB, p, 1, 1, 0;\n}\n"
    : "+f"(d[0]), "+f"(d[1]), "+f"(d[2]), "+f"(d[3]), "+f"(d[4]), "+f"(d[5]), "+f"(d[6]), "+f"(d[7]),
      "+f"(d[8]), "+f"(d[9]), "+f"(d[10]), "+f"(d[11]), "+f"(d[12]), "+f"(d[13]), "+f"(d[14]), "+f"(d[15]),
      "+f"(d[16]), "+f"(d[17]), "+f"(d[18]), "+f"(d[19]), "+f"(d[20]), "+f"(d[21]), "+f"(d[22]), "+f"(d[23]),
      "+f"(d[24]), "+f"(d[25]), "+f"(d[26]), "+f"(d[27]), "+f"(d[28]), "+f"(d[29]), "+f"(d[30]), "+f"(d[31])
    : "r"(a0), "r"(a1), "r"(a2), "r"(a3), "r"(db), "r"(scale_d), "n"(HB));
}
template <uint32_t HB = 0x40000040u>
__device__ __forceinline__ void wg_rs64_z(float* d, uint32_t a0, uint32_t a1, uint32_t a2, uint32_t a3, uint32_t db) {
  asm volatile("{\n.reg .pred p;\n.reg .b64 dB;\nmov.b64 dB, {%36, %37};\nsetp.ne.b32 p, 0, 0;\n"
    "wgmma.mma_async.sync.aligned.m64n64k16.f32.bf16.bf16 "
    "{%0, %1, %2, %3, %4, %5, %6, %7, %8, %9, %10, %11, %12, %13, %14, %15, "
    "%16, %17, %18, %19, %20, %21, %22, %23, %24, %25, %26, %27, %28, %29, %30, %31}, "
    "{%32, %33, %34, %35}, dB, p, 1, 1, 0;\n}\n"
    : "=f"(d[0]), "=f"(d[1]), "=f"(d[2]), "=f"(d[3]), "=f"(d[4]), "=f"(d[5]), "=f"(d[6]), "=f"(d[7]),
      "=f"(d[8]), "=f"(d[9]), "=f"(d[10]), "=f"(d[11]), "=f"(d[12]), "=f"(d[13]), "=f"(d[14]), "=f"(d[15]),
      "=f"(d[16]), "=f"(d[17]), "=f"(d[18]), "=f"(d[19]), "=f"(d[20]), "=f"(d[21]), "=f"(d[22]), "=f"(d[23]),
      "=f"(d[24]), "=f"(d[25]), "=f"(d[26]), "=f"(d[27]), "=f"(d[28]), "=f"(d[29]), "=f"(d[30]), "=f"(d[31])
    : "r"(a0), "r"(a1), "r"(a2), "r"(a3), "r"(db), "n"(HB));
}
template <uint32_t HB = 0x40000040u>
__device__ __forceinline__ void wg_rs32(float* d, uint32_t a0, uint32_t a1, uint32_t a2, uint32_t a3, uint32_t db, int scale_d) {
  asm volatile("{\n.reg .pred p;\n.reg .b64 dB;\nmov.b64 dB, {%20, %22};\nsetp.ne.b32 p, %21, 0;\n"
    "wgmma.mma_async.sync.aligned.m64n32k16.f32.bf16.bf16 "
    "{%0, %1, %2, %3, %4, %5, %6, %7, %8, %9, %10, %11, %12, %13, %14, %15}, "
    "{%16, %17, %18, %19}, dB, p, 1, 1, 0;\n}\n"
    : "+f"(d[0]), "+f"(d[1]), "+f"(d[2]), "+f"(d[3]), "+f"(d[4]), "+f"(d[5]), "+f"(d[6]), "+f"(d[7]),
      "+f"(d[8]), "+f"(d[9]), "+f"(d[10]), "+f"(d[11]), "+f"(d[12]), "+f"(d[13]), "+f"(d[14]), "+f"(d[15])
    : "r"(a0), "r"(a1), "r"(a2), "r"(a3), "r"(db), "r"(scale_d), "n"(HB));
}
template <uint32_t HB = 0x40000040u>
__device__ __forceinline__ void wg_rs32_z(float* d, uint32_t a0, uint32_t a1, uint32_t a2, uint32_t a3, uint32_t db) {
  asm volatile("{\n.reg .pred p;\n.reg .b64 dB;\nmov.b64 dB, {%20, %21};\nsetp.ne.b32 p, 0, 0;\n"
    "wgmma.mma_async.sync.aligned.m64n32k16.f32.bf16.bf16 "
    "{%0, %1, %2, %3, %4, %5, %6, %7, %8, %9, %10, %11, %12, %13, %14, %15}, "
    "{%16, %17, %18, %19}, dB, p, 1, 1, 0;\n}\n"
    : "=f"(d[0]), "=f"(d[1]), "=f"(d[2]), "=f"(d[3]), "=f"(d[4]), "=f"(d[5]), "=f"(d[6]), "=f"(d[7]),
      "=f"(d[8]), "=f"(d[9]), "=f"(d[10]), "=f"(d[11]), "=f"(d[12]), "=f"(d[13]), "=f"(d[14]), "=f"(d[15])
    : "r"(a0), "r"(a1), "r"(a2), "r"(a3), "r"(db), "n"(HB));
}
template <uint32_t HB = 0x40000040u>
__device__ __forceinline__ void wg_rs40t(float* d, uint32_t a0, uint32_t a1, uint32_t a2, uint32_t a3, uint32_t db, int scale_d) {
  asm volatile("{\n.reg .pred p;\n.reg .b64 dB;\nmov.b64 dB, {%24, %26};\nsetp.ne.b32 p, %25, 0;\n"
    "wgmma.mma_async.sync.aligned.m64n40k16.f32.bf16.bf16 "
    "{%0, %1, %2, %3, %4, %5, %6, %7, %8, %9, %10, %11, %12, %13, %14, %15, "
    "%16, %17, %18, %19}, "
    "{%20, %21, %22, %23}, dB, p, 1, 1, 1;\n}\n"
    : "+f"(d[0]), "+f"(d[1]), "+f"(d[2]), "+f"(d[3]), "+f"(d[4]), "+f"(d[5]), "+f"(d[6]), "+f"(d[7]),
      "+f"(d[8]), "+f"(d[9]), "+f"(d[10]), "+f"(d[11]), "+f"(d[12]), "+f"(d[13]), "+f"(d[14]), "+f"(d[15]),
      "+f"(d[16]), "+f"(d[17]), "+f"(d[18]), "+f"(d[19])
    : "r"(a0), "r"(a1), "r"(a2), "r"(a3), "r"(db), "r"(scale_d), "n"(HB));
}
template <uint32_t HB = 0x40000040u>
__device__ __forceinline__ void wg_rs40t_z(float* d, uint32_t a0, uint32_t a1, uint32_t a2, uint32_t a3, uint32_t db) {
  asm volatile("{\n.reg .pred p;\n.reg .b64 dB;\nmov.b64 dB, {%24, %25};\nsetp.ne.b32 p, 0, 0;\n"
    "wgmma.mma_async.sync.aligned.m64n40k16.f32.bf16.bf16 "
    "{%0, %1, %2, %3, %4, %5, %6, %7, %8, %9, %10, %11, %12, %13, %14, %15, "
    "%16, %17, %18, %19}, "
    "{%20, %21, %22, %23}, dB, p, 1, 1, 1;\n}\n"
    : "=f"(d[0]), "=f"(d[1]), "=f"(d[2]), "=f"(d[3]), "=f"(d[4]), "=f"(d[5]), "=f"(d[6]), "=f"(d[7]),
      "=f"(d[8]), "=f"(d[9]), "=f"(d[10]), "=f"(d[11]), "=f"(d[12]), "=f"(d[13]), "=f"(d[14]), "=f"(d[15]),
      "=f"(d[16]), "=f"(d[17]), "=f"(d[18]), "=f"(d[19])
    : "r"(a0), "r"(a1), "r"(a2), "r"(a3), "r"(db), "n"(HB));
}

constexpr uint32_t SOFF = 1024;
constexpr int STG = 57344, SL_W = 32768, SL_HD = 12288, SL_F = 3 * STG, X_ST = 131072;
__host__ __device__ constexpr int kv_off(int h, int b) { return 16384 + h * 81920 + (b ^ (6 * h)) * 8192; }
__host__ __device__ constexpr int qo_off(int h, int qb) { return (qb >> 1) * 81920 + h * 8192 + (qb & 1) * 4096; }
__host__ __device__ constexpr int wo_off(int st) { return 16384 + st * 32768 + (st >> 1) * 16384; }
constexpr int OFF_ONES = 4 * STG;
constexpr int OFF_PATCH = OFF_ONES + 1024;
constexpr int OFF_CS = OFF_PATCH + 768;
constexpr int OFF_BAR = OFF_CS + 768;
constexpr int OFF_MISC = OFF_BAR + 416;
constexpr int SMEM_BYTES = OFF_MISC + 96;
enum { B_FULL = 0, B_EMPTY = 6, B_HALO = 12, B_CS = 15, B_KVREADY, B_QDONE = B_KVREADY + 2, B_QREADY, B_OST, B_ADONE = B_OST + 2,
       B_QFREE, B_WS, B_WFULL, B_WEMPTY = B_WFULL + 4, B_GU = B_WEMPTY + 4, B_RES = B_GU + 2, B_DN,
       B_HX = B_DN + 2, B_RST, B_E23, B_UNIT, B_COUNT = B_UNIT + 8 };
static_assert(B_COUNT <= 52, "barrier area");
__host__ __device__ constexpr int bar_count(int i) {
  return i >= B_EMPTY && i < B_HALO ? 17 : i == B_CS ? 5 : i == B_QFREE ? 16
       : i == B_KVREADY || i == B_KVREADY + 1 || i == B_QREADY ? 8 : i == B_E23 ? 9 : i == B_ADONE ? 32 : i == B_OST ? 2 : i >= B_UNIT ? 4
       : i == B_QDONE || (i >= B_WEMPTY && i < B_GU) ? 16 : i == B_RST ? 4 : i == B_RES ? 2 : 1;
}
enum { M_KEY = 0, M_MEAN, M_INV, M_WSUM, M_TAG, M_SEL0, M_PMEAN, M_PINV, M_XQ = 8, M_KEYS = 12, M_PROG = 20 };
constexpr int FFN_PIECE = 14336;
constexpr int T_XS = 163840, T_HP = T_XS + 1024;
constexpr float LSUM_MIN = 5.421010862427522e-20f, LSUM_MAX = 1.8446744073709552e19f;
constexpr float SM_C = 0.17677669529663687f * 1.4426950408889634f;
constexpr uint32_t VSTEP = 64u - (64u << 16);
constexpr int DELAY_P = 600, DELAY_S = 2000, DELAY_Y = 500, X_STAGGER = 500;
constexpr int GU_PACE = 2000, GU_PACE1 = 1700, GUB_PACE = 900, WS_PACE = 500;
constexpr int RES_K = 4;

struct Params {
  CUtensorMap mapA[2], mapW, mapWo, mapRes[2], mapXst[2], mapG, mapU, mapD, mapWs;
  const bf16 *w_r, *w_d;
  bf16* out;
  int role[128];
};

template <int N> __device__ __forceinline__ void exp_pack(const float* s, uint32_t* p) {
#pragma unroll
  for (int b = 0; b < N; b++) {
    p[2 * b] = pack_bf16(ex2(s[4 * b]), ex2(s[4 * b + 1]));
    p[2 * b + 1] = pack_bf16(ex2(s[4 * b + 2]), ex2(s[4 * b + 3]));
  }
}
template <int KIND> __device__ __forceinline__ void edge16(const float* sd, const float* st, uint32_t* pd, uint32_t* pt, int dl, uint32_t mt) {
  if (KIND == 0) { exp_pack<2>(sd, pd); pt[0] = pt[1] = pt[2] = pt[3] = 0; }
  else if (KIND == 1) { exp_pack<2>(st, pt); pd[0] = pd[1] = pd[2] = pd[3] = 0; }
  else {
    const uint32_t a = pack_bf16(ex2(dl >= 0 ? sd[0] : st[0]), ex2(dl >= 1 ? sd[1] : st[1]));
    const uint32_t c = pack_bf16(ex2(dl >= 0 ? sd[6] : st[6]), ex2(dl >= 1 ? sd[7] : st[7]));
    pd[0] = a & ~mt; pt[0] = a & mt; pd[3] = c & ~mt; pt[3] = c & mt;
    pd[1] = pack_bf16(ex2(sd[2]), ex2(sd[3])); pt[1] = 0;
    pt[2] = pack_bf16(ex2(st[4]), ex2(st[5])); pd[2] = 0;
  }
}
__device__ __forceinline__ void edge32(const float* sd, const float* st, uint32_t* pd, uint32_t* pt, int rel, int dl, uint32_t mt) {
  if (rel > 1) { edge16<0>(sd, st, pd, pt, dl, mt); edge16<0>(sd + 8, st + 8, pd + 4, pt + 4, dl, mt); }
  else if (rel == 1) { edge16<0>(sd, st, pd, pt, dl, mt); edge16<2>(sd + 8, st + 8, pd + 4, pt + 4, dl, mt); }
  else if (rel == 0) { edge16<2>(sd, st, pd, pt, dl, mt); edge16<1>(sd + 8, st + 8, pd + 4, pt + 4, dl, mt); }
  else { edge16<1>(sd, st, pd, pt, dl, mt); edge16<1>(sd + 8, st + 8, pd + 4, pt + 4, dl, mt); }
}
__device__ __forceinline__ void qk64(float* s, const uint32_t* qf, uint32_t kd) {
  wg_rs64_z<H64>(s, qf[0], qf[1], qf[2], qf[3], kd);
  wg_rs64<H64>(s, qf[4], qf[5], qf[6], qf[7], kd + 2, 1);
}
__device__ __forceinline__ void qk32x2(float* a, float* b, const uint32_t* qf, uint32_t ka, uint32_t kb) {
  wg_rs32_z<H64>(a, qf[0], qf[1], qf[2], qf[3], ka); wg_rs32_z<H64>(b, qf[0], qf[1], qf[2], qf[3], kb);
  wg_rs32<H64>(a, qf[4], qf[5], qf[6], qf[7], ka + 2, 1); wg_rs32<H64>(b, qf[4], qf[5], qf[6], qf[7], kb + 2, 1);
}
__device__ __forceinline__ void pv32(float* o, const uint32_t* p, uint32_t vd) {
  wg_rs40t<H64>(o, p[0], p[1], p[2], p[3], vd, 1);
  wg_rs40t<H64>(o, p[4], p[5], p[6], p[7], vd + VSTEP, 1);
}

__device__ __forceinline__ void fma8(float* d, uint4 w, float x) {
  d[0] += x * bf_lo(w.x); d[1] += x * bf_hi(w.x); d[2] += x * bf_lo(w.y); d[3] += x * bf_hi(w.y);
  d[4] += x * bf_lo(w.z); d[5] += x * bf_hi(w.z); d[6] += x * bf_lo(w.w); d[7] += x * bf_hi(w.w);
}

__device__ __forceinline__ int fresh_tid() { int r; asm volatile("mov.u32 %0, %%tid.x;" : "=r"(r)); return r; }
__device__ __forceinline__ int fresh_bid() { int r; asm volatile("mov.u32 %0, %%ctaid.x;" : "=r"(r)); return r; }
#define PHASE_IDS                                                                                                              \
  const uint32_t sbase = smem_u32(smem);                                                                                       \
  const int tid = fresh_tid(), bid = P.role[fresh_bid()];                                                                      \
  const int warp = __shfl_sync(0xffffffffu, tid >> 5, 0), lane = tid & 31;                                                     \
  const int rank = bid & 1, rb = bid & 7, hp = bid >> 3, cl = (rb >> 1) * 16 + hp;                  \
  const int mb = 2 * rb + (hp >> 3), nb = hp & 7;                                            \
  const int wg = warp >> 2, wi = warp & 3, g = lane >> 2, q = lane & 3;                                                        \
  const int mi = lane >> 3, srow = wi * 16 + (mi & 1) * 8 + (lane & 7);      \
  auto bar = [&](int i) { return sbase + OFF_BAR + 8 * i; };                                                                   \
  volatile uint32_t* s_misc = (volatile uint32_t*)(smem + OFF_MISC);                                                           \
  auto load_w = [&](int s, int kt) {                           \
    mbar_expect_tx(bar(B_FULL + s), (s & 1) ? SL_HD : SL_HD + 32768);                        \
    tma_load3_mc(sbase + (s >> 1) * STG + SL_W + (s & 1) * SL_HD + rank * 6144, &P.mapW, hp * 64, kt * 32 + rank * 16, 0, bar(B_FULL + s));              \
  };                                                                                                                           \
  auto load_a = [&](int s, int kt, int layer) { tma_load2(sbase + (s >> 1) * STG, &P.mapA[layer], kt * 32, rb * 256, bar(B_FULL + s)); }; \
  auto load_wo = [&](int k) {                                                 \
    mbar_expect_tx(bar(B_WFULL + (k & 3)), 32768);                                                                             \
    tma_load3_mc(sbase + wo_off(k & 3) + 16384 + rank * 8192, &P.mapWo, nb * 128 + rank * 64, (k >> 3) * 32, (k & 7) * 2, bar(B_WFULL + (k & 3))); \
  };                                                                                                                           \
  auto load_o = [&](int k) {                                                            \
    bulk_load_h(sbase + wo_off(k & 3), g_o + (size_t)(mb * 16 + k) * 16384, 16384, bar(B_WFULL + (k & 3)), policy_evict_first());                    \
  };                                                                                                                           \
  auto export_halo = [&](int p) {                                                        \
    _Pragma("unroll 1")                                                                                                        \
    for (int h = 0; h < 2; h++) {                                                                                              \
      if (rank == 0) bulk_push(mapa(sbase + kv_off(h, 2 - 2 * p), 1), sbase + kv_off(h, 6 - 2 * p), 16384, mapa(bar(B_HALO + (p ? 2 : h)), 1)); \
      else if (rb < 7) bulk_store(g_kv + (size_t)(cl * 4 + p * 2 + h) * 16384, sbase + kv_off(h, 6 - 2 * p), 16384);           \
    }                                                                                                                          \
    bulk_commit();                                                                                                             \
  };                                                                                                                           \
  auto load_res = [&](int half, int layer) {      \
    mbar_expect_tx(bar(B_RES), 16384);                                                                                         \
    tma_load2_h(sbase + qo_off(half, 0), &P.mapRes[layer], nb * 128 + half * 64, mb * 128, bar(B_RES), policy_evict_first());  \
    tma_load2_h(sbase + qo_off(half, 2), &P.mapRes[layer], nb * 128 + half * 64, mb * 128 + 64, bar(B_RES), policy_evict_first()); \
  };                                                                                                                           \
  auto store_tile = [&](int layer, int skip, bool wait) {                                           \
    _Pragma("unroll 1")                                                                                                        \
    for (int j = 0; j < 4; j++)                                                                                                \
      if ((j & 1) != skip) tma_store(&P.mapXst[layer], sbase + X_ST + (j & 1) * 16384 + (j >> 1) * 8192, nb * 128 + (j >> 1) * 64, mb * 128 + (j & 1) * 64); \
    bulk_commit();                                                                                                             \
    if (wait) bulk_wait_all();                                                                                                 \
  };                                                                                                                           \
  auto load_ws = [&](int pace) {                                    \
    mbar_expect_tx(bar(B_WS), 4 * SL_HD);                                                                                      \
    _Pragma("unroll 1")                                                                                                        \
    for (int j = 0; j < 4; j++) {                                                                                              \
      tma_load3(sbase + SL_F + j * SL_HD, &P.mapWs, hp * 64, rb * 128 + j * 32, 0, bar(B_WS));                                 \
      if (pace) spin_cycles(pace);                                                                                             \
    }                                                                                                                          \
  };                                                                                                                           \
  auto load_gu = [&](int half, int pace, int j0, int j1) {                             \
    if (j0 == 0) mbar_expect_tx(bar(B_GU + half), 4 * FFN_PIECE);                                                                         \
    _Pragma("unroll 1")                                                                                                        \
    for (int j = j0; j < j1; j++) {                                                                                            \
      tma_load2_h(sbase + SL_F + j * FFN_PIECE, &P.mapG + (j >> 1), cl * 56, rank * 512 + half * 256 + (j & 1) * 128, bar(B_GU + half), policy_evict_first()); \
      if (j < j1 - 1) spin_cycles(pace);                                                                                       \
    }                                                                                                                          \
  };                                                                                                                           \
  auto fetch_gu = [&](uint32_t* a, int ks, int ct) {                 \
    ldsm_x4_t(sbase + SL_F + (mi & 1) * 2 * FFN_PIECE + (ks * 16 + (mi >> 1) * 8 + (lane & 7)) * 112 + ct * 16, a[0], a[1], a[2], a[3]); \
  };                                                                                                                           \
  auto send_gu = [&](float gate, float up, int ct, int part) {        \
    const int u = 8 * ct + g, own = u >= 28;                                                                                   \
    if (q == 0) st_async2(mapa(sbase + T_HP + ((rank * 5 + part) * 28 + u - 28 * own) * 8, own), gate, up, mapa(bar(B_HX), own)); \
  };                                                                                                                           \
  auto hidden = [&]() {                                     \
    const float2* hpart = (const float2*)(smem + T_HP) + min(lane, 27);                                                        \
    float gs[2] = {0.f, 0.f}, us[2] = {0.f, 0.f};                                                                              \
    _Pragma("unroll")                                                                                                          \
    for (int j = 0; j < 10; j++) { const float2 v = hpart[j * 28]; gs[j & 1] += v.x; us[j & 1] += v.y; }                       \
    const float gb = rbf(gs[0] + gs[1]), ub = rbf(us[0] + us[1]);                                                              \
    return lane < 28 ? rbf(__fdividef(gb, 1.f + __expf(-gb))) * ub : 0.f;                                                      \
  };                                                                                                                           \
  (void)load_wo; (void)load_o; (void)export_halo; (void)load_res; (void)store_tile; (void)fetch_gu; (void)load_ws; (void)load_gu; (void)send_gu; (void)hidden; (void)cl; (void)mb; (void)nb; (void)wg; (void)g; (void)q; (void)srow; (void)s_misc; (void)load_w; (void)load_a;

__global__ void __launch_bounds__(512, 1) mega_kernel(const __grid_constant__ Params P) {
  extern __shared__ __align__(1024) uint8_t smem[];
  {
    PHASE_IDS
    if (warp == 0) {
      if (lane == 0) {
        prefetch_tmap(&P.mapA[0]); prefetch_tmap(&P.mapW);
#pragma unroll
        for (int i = 0; i < 6; i++) mbar_init(bar(B_FULL + i), 1);
        asm volatile("fence.mbarrier_init.release.cluster;" ::: "memory");
      }
      __syncwarp();
      mbar_expect_tx(bar(B_FULL), SL_HD + 32768);
      tma_load3(sbase + SL_W, &P.mapW, hp * 64, 0, 0, bar(B_FULL));
      tma_load3(sbase + SL_W + 6144, &P.mapW, hp * 64, 16, 0, bar(B_FULL));
      load_a(0, 0, 0);
    } else if (tid == 32) {
#pragma unroll
      for (int i = 6; i < B_COUNT; i++) mbar_init(bar(i), bar_count(i));
      asm volatile("fence.mbarrier_init.release.cluster;" ::: "memory");
    } else if (warp == 8) {
      ((uint4*)(smem + OFF_ONES))[lane] = make_uint4(0x3F803F80u, 0x3F803F80u, 0x3F803F80u, 0x3F803F80u);
      ((uint4*)(smem + OFF_ONES))[lane + 32] = make_uint4(0x3F803F80u, 0x3F803F80u, 0x3F803F80u, 0x3F803F80u);
    }
    __syncwarp();
    cluster_arrive(); cluster_wait();
    if (warp == 0) {
      PROFL(0, 1);
      load_w(1, 1);
    } else if (tid == 96) {
      if ((sbase & 0x3FFFF) != SOFF) __trap();
    }
    __syncwarp();
  }

  regs_dec<120>();
#pragma unroll 1
  for (unsigned pass_v = 0;;) {
    const unsigned pass = __shfl_sync(0xffffffffu, pass_v, 0);
    if (__shfl_sync(0xffffffffu, fresh_tid() >> 8, 0)) {
      if (pass > 0) {
        const unsigned layer = pass - 1;
        uint32_t xr[32];
        {
          PHASE_IDS
          float acc[64];
#pragma unroll
          for (int i = 0; i < 64; i++) acc[i] = 0.f;
          const uint32_t da0 = dlo(SOFF, 16) + (wg - 2) * 256;
          constexpr uint32_t db0 = dlo(SOFF + 16384, 8192);
#pragma unroll 1
          for (int k4 = 0; k4 < 4; k4++) {
#pragma unroll
            for (int st = 0; st < 4; st++) {
              mbar_wait(bar(B_WFULL + st), k4 & 1);
              wg_fence();
#pragma unroll
              for (int kk = 0; kk < 4; kk++)
                wg_ss128t<H64, H128>(acc, da0 + (wo_off(st) >> 4) + (kk >> 1) * 512 + (kk & 1) * 2, db0 + (wo_off(st) >> 4) + kk * 128, 1);
              wg_commit();
              if (st == 0 && k4 == 0 && warp == 9) PROF(10);
              if (warp == 9) STEPT(16 + k4 * 4 + st);
              wg_wait<1>();
              if (lane < 2 && (st == 0 ? k4 > 0 : (st < 3 || k4 < 3))) mbar_arrive_cluster(bar(B_WEMPTY + ((st + 3) & 3)), lane);
            }
          }
          mbar_wait(bar(B_RES), layer);
          mbar_wait(bar(B_RST), layer);
          const uint32_t zoff = qo_off(0, (wg - 2) * 2);
#pragma unroll
          for (int j = 0; j < 8; j++)
            ldsm_x4(sbase + zoff + srow * 128 + (j >> 2) * 8192 + ((((2 * j + (mi >> 1)) & 7) ^ (srow & 7)) << 4), xr[4 * j], xr[4 * j + 1], xr[4 * j + 2], xr[4 * j + 3]);
          wg_wait<0>();
          fence_regs<64>(acc);
          if (warp == 9) PROF(11);
#pragma unroll
          for (int j = 0; j < 32; j++) xr[j] = hadd_bf2(xr[j], pack_bf16(acc[2 * j], acc[2 * j + 1]));
        }
        PHASE_IDS
        const uint32_t tag = s_misc[M_TAG];
        const int grow = mb * 128 + (warp - 8) * 16 + g;
        {
          float d[6][4];
#pragma unroll
          for (int i = 0; i < 6; i++) d[i][0] = d[i][1] = d[i][2] = d[i][3] = 0.f;
          const uint4* tab = (const uint4*)(smem + OFF_PATCH + (g == 1 ? q * 64 : (g == 0 ? 256 : 320)));
#pragma unroll
          for (int j2 = 0; j2 < 4; j2++) {
            const uint4 w = tab[j2];
#pragma unroll
            for (int jj = 0; jj < 2; jj++) {
              const uint32_t* a = &xr[8 * j2 + 4 * jj];
              mma_16816(d[jj], a[0], a[1], a[2], a[3], jj ? w.z : w.x, jj ? w.w : w.y);
              mma_16816(d[2 + jj], a[0], a[1], a[2], a[3], a[0], a[2]);
              mma_16816(d[4 + jj], a[0], a[1], a[2], a[3], a[1], a[3]);
            }
          }
          const float sq0 = __shfl_sync(0xffffffffu, (g & 1) ? d[2][1] + d[3][1] : d[2][0] + d[3][0], g * 4 + (g >> 1));
          const float sq1 = __shfl_sync(0xffffffffu, (g & 1) ? d[4][3] + d[5][3] : d[4][2] + d[5][2], g * 4 + (g >> 1));
          uint4* dst = &g_part[layer][nb * SEQ + grow];
          if (q == 0) {
            st_relaxed4(dst, make_uint4(__float_as_uint(d[0][0] + d[1][0]), __float_as_uint(sq0), __float_as_uint(d[0][1] + d[1][1]), tag));
            st_relaxed4(dst + 8, make_uint4(__float_as_uint(d[0][2] + d[1][2]), __float_as_uint(sq1), __float_as_uint(d[0][3] + d[1][3]), tag));
          }
        }
        if (warp == 9) PROF(12);
        if (layer == 0 && lane < 2) mbar_arrive_cluster(bar(B_QFREE), lane);
        asm volatile("bar.arrive 6, 320;" ::: "memory");
        const int t_p = (int)clock();
        const uint32_t zrow = sbase + X_ST + (wg - 2) * 16384 + srow * 128;
        named_bar(5, 256);
#pragma unroll
        for (int j = 0; j < 8; j++)
          stsm_x4(zrow + (j >> 2) * 8192 + ((((2 * j + (mi >> 1)) & 7) ^ (srow & 7)) << 4), xr[4 * j], xr[4 * j + 1], xr[4 * j + 2], xr[4 * j + 3]);
        if (layer == 0) {
          fence_async_smem();
          asm volatile("bar.arrive 8, 288;" ::: "memory");
        }
#pragma unroll 1
        while ((int)clock() - t_p < DELAY_P) {}
        {
          const int rr = q >> 1;
          const uint4* src = &g_part[layer][(q & 1) * 4 * SEQ + grow + 8 * rr];
          uint4 pp[4];
          uint32_t spins = 0;
#pragma unroll 1
          do {
#pragma unroll
            for (int j = 0; j < 4; j++) pp[j] = ld_relaxed4(src + j * SEQ);
          } while (!__all_sync(0xffffffffu, pp[0].w == tag && pp[1].w == tag && pp[2].w == tag && pp[3].w == tag) && ++spins < SPIN_LIMIT);
          if (warp == 9) PROF(13);
          float s3[3] = {(__uint_as_float(pp[0].x) + __uint_as_float(pp[1].x)) + (__uint_as_float(pp[2].x) + __uint_as_float(pp[3].x)),
                         (__uint_as_float(pp[0].y) + __uint_as_float(pp[1].y)) + (__uint_as_float(pp[2].y) + __uint_as_float(pp[3].y)),
                         (__uint_as_float(pp[0].z) + __uint_as_float(pp[1].z)) + (__uint_as_float(pp[2].z) + __uint_as_float(pp[3].z))};
#pragma unroll
          for (int c = 0; c < 3; c++) s3[c] += __shfl_xor_sync(0xffffffffu, s3[c], 1);
          const float mu = s3[0] * (1.f / DM), var = fmaxf(fmaf(-mu, mu, s3[1] * (1.f / DM)), 0.f);
          const float mn = rbf(mu), iv = ln_inv(var);
          const uint32_t ky = router_key(rbf((s3[2] - mn * __uint_as_float(s_misc[M_WSUM])) * iv), grow + 8 * rr);
          const uint32_t wbest = __reduce_max_sync(0xffffffffu, ky);
          s_misc[M_KEYS + warp - 8] = wbest;
          named_bar(5, 256);
          if (__reduce_max_sync(0xffffffffu, s_misc[M_KEYS + (lane & 7)]) == wbest) {
            if (nb == 0 && ky == wbest && (q & 1) == 0) st_relaxed4(&g_slot[layer][mb * 8], make_uint4(ky, __float_as_uint(mn), __float_as_uint(iv), tag));
            const int r = ~wbest & 15;
            if ((r & 7) == g) {
#pragma unroll
              for (int j = 0; j < 4; j++) {
                const uint32_t* a = &xr[8 * j];
                st_relaxed4(&g_cand[layer][mb * 128 + nb * 16 + q * 4 + j],
                    r < 8 ? make_uint4(a[0], a[2], a[4], a[6]) : make_uint4(a[1], a[3], a[5], a[7]));
              }
            }
            __syncwarp();
          }
          if (warp == 9) PROF(14);
          if (layer == 0) {
            if ((q & 1) == 0) {
              g_rowln[nb][grow + 8 * rr] = make_float2(mn, iv);
              if (warp - 8 == nb) {
                const float mu2 = mu + (mu - mn) * iv, inv2 = ln_inv(var * (1.f + iv) * (1.f + iv));
                st_relaxed4(&g_rowab[1][grow + 8 * rr], make_uint4(__float_as_uint((1.f + iv) * inv2), __float_as_uint((mn * iv + rbf(mu2)) * inv2), tag, 0));
              }
            }
            __syncwarp();
          } else {
            const uint32_t m2 = pack_bf16(mn, mn);
            uint8_t* row = smem + X_ST + (wg - 2) * 16384 + (q & 1) * 8192 + (wi * 16 + g + 8 * rr) * 128;
#pragma unroll 2
            for (int j = 0; j < 8; j++) {
              uint4* c = (uint4*)(row + (((j + lane) & 7) << 4));
              const uint4 v = *c;
              *c = make_uint4(add_ln_pair(v.x, m2, iv), add_ln_pair(v.y, m2, iv), add_ln_pair(v.z, m2, iv), add_ln_pair(v.w, m2, iv));
            }
            fence_async_smem();
          }
          if (warp == 15) asm volatile("bar.arrive 7, 512;" ::: "memory");
        }
        if (warp < 15) {
          uint32_t gu[64];
          mbar_wait(bar(B_GU + 1), layer);
#pragma unroll
          for (int j = 0; j < 16; j++) fetch_gu(gu + 4 * j, j, warp - 8);
          fence_async_smem();
          float d[4][4] = {};
          named_bar(7, 512);
#pragma unroll
          for (int hf = 0; hf < 2; hf++) {
            uint4 xv[4] = {};
            if (g == 0) {
#pragma unroll
              for (int j = 0; j < 4; j++) xv[j] = ((const uint4*)(smem + T_XS))[32 + hf * 16 + j * 4 + q];
            }
            __syncwarp();
#pragma unroll
            for (int j = 0; j < 4; j++) {
              const uint32_t* a = gu + hf * 32 + j * 8;
              mma_16816(d[(j & 1) * 2], a[0], a[1], a[2], a[3], xv[j].x, xv[j].y);
              mma_16816(d[(j & 1) * 2 + 1], a[4], a[5], a[6], a[7], xv[j].z, xv[j].w);
            }
          }
          send_gu((d[0][0] + d[1][0]) + (d[2][0] + d[3][0]), (d[0][2] + d[1][2]) + (d[2][2] + d[3][2]), warp - 8, 4);
          __syncwarp();
        }
        if (layer == 0) asm volatile("bar.arrive 9, 512;" ::: "memory");
        else {
          uint32_t wd[64];
          mbar_wait(bar(B_DN), layer);
#pragma unroll
          for (int j = 0; j < 16; j++) {
            const uint32_t row = sbase + wo_off(0) + ((warp - 8) * 2 + (j >> 3)) * 3584 + min((j & 1) * 16 + (mi >> 1) * 8 + (lane & 7), 27) * 128;
            ldsm_x4_t(row + ((((j & 6) + (mi & 1)) ^ ((row >> 7) & 7)) << 4), wd[4 * j], wd[4 * j + 1], wd[4 * j + 2], wd[4 * j + 3]);
          }
          fence_regs_u<64>(wd);
          uint32_t hf[4];
          named_bar(10, 288);
          *(uint4*)hf = *(const uint4*)(smem + OFF_PATCH + 256 + q * 16);
          if (warp == 9) PROF(19);
          float y[4][4] = {};
#pragma unroll
          for (int j = 0; j < 16; j++)
            mma_16816(y[j & 3], wd[4 * j], wd[4 * j + 1], wd[4 * j + 2], wd[4 * j + 3], g == j >> 1 ? hf[(j & 1) * 2] : 0u, g == j >> 1 ? hf[(j & 1) * 2 + 1] : 0u);
          {
            float e[4];
#pragma unroll
            for (int c = 0; c < 4; c++) { const int i = (c & 1) * 2 + (c >> 1); e[c] = (y[0][i] + y[1][i]) + (y[2][i] + y[3][i]); }
            const bool b0 = g & 1, b1 = g & 2;
            float t0 = __shfl_xor_sync(0xffffffffu, b0 ? e[0] : e[1], 4), t1 = __shfl_xor_sync(0xffffffffu, b0 ? e[2] : e[3], 4);
            const float f0 = b0 ? t0 : e[0], f1 = b0 ? e[1] : t0, f2 = b0 ? t1 : e[2], f3 = b0 ? e[3] : t1;
            t0 = __shfl_xor_sync(0xffffffffu, b1 ? f0 : f2, 8); t1 = __shfl_xor_sync(0xffffffffu, b1 ? f1 : f3, 8);
            st_relaxed4(&g_ypart[layer][bid * 256 + (warp - 8) * 32 + (q * 4 + (g & 3)) * 2 + (g >> 2)],
                b1 ? make_uint4(__float_as_uint(t0), __float_as_uint(t1), __float_as_uint(f2), __float_as_uint(f3)) : make_uint4(__float_as_uint(f0), __float_as_uint(f1), __float_as_uint(t0), __float_as_uint(t1)));
          }
          if (warp == 9) PROF(20);
          asm volatile("bar.arrive 9, 384;" ::: "memory");
          cluster_arrive(); cluster_wait();
          return;
        }
      }
      const unsigned layer = pass;
      named_bar(1 + (fresh_tid() >> 7), 128);
      regs_inc<224>();
      float acc[2][96];
      float pa[2][2], pb[2][2];
      {
        PHASE_IDS
        const uint32_t da0 = dlo(SOFF, 16) + (wg - 2) * 512;
        constexpr uint32_t db0 = dlo(SOFF + SL_W, 2048);
        if (warp == 9) PROF(19 - 2 * layer);
        mbar_wait(bar(B_FULL), 0);
        if (warp == 9) PROF(29);
        if (warp == 9) STEPT(0);
        wg_fence();
        wg_ss192t_z(acc[0], da0, db0); wg_ss192t_z(acc[1], da0 + 1024, db0);
        wg_ss192t(acc[0], da0 + 2, db0 + 384, 1); wg_ss192t(acc[1], da0 + 1026, db0 + 384, 1);
        wg_commit();
        int s = 1, u = 0;
#pragma unroll 1
        for (int i = 1; i < 28; i++) {
          const uint32_t da = da0 + (s >> 1) * (STG >> 4) + (s & 1) * 4, db = db0 + (s >> 1) * (STG >> 4) + (s & 1) * (SL_HD >> 4);
          mbar_wait(bar(B_FULL + s), (u + (s > 1 ? layer : 0)) & 1);
          if (warp == 9 && !(i & 1)) STEPT(i >> 1);
          wg_fence();
          wg_ss192t(acc[0], da, db, 1); wg_ss192t(acc[1], da + 1024, db, 1);
          wg_ss192t(acc[0], da + 2, db + 384, 1); wg_ss192t(acc[1], da + 1026, db + 384, 1);
          wg_commit();
          wg_wait<1>();
          if (lane < 2 && i < 27) mbar_arrive_cluster(bar(B_EMPTY + (s == 0 ? 5 : s - 1)), lane);
          if (++s == 6) { s = 0; u++; }
        }
      }
      PHASE_IDS
      auto last_tile = [&](int m, int j) {
        const int e = (4 + j) % 6;
        const uint32_t da = dlo(SOFF + (e >> 1) * STG + (e & 1) * 64, 16) + (wg - 2) * 512 + m * 1024, db = dlo(SOFF + (e >> 1) * STG + SL_W + (e & 1) * SL_HD, 2048);
        wg_fence();
        wg_ss192t(acc[m], da, db, 1);
        wg_ss192t(acc[m], da + 2, db + 384, 1);
      };
      {
        if (layer == 0) mbar_wait(bar(B_CS), 0);
        const uint32_t tag = s_misc[M_TAG];
        const uint4* src = &g_rowab[layer][rb * 256 + (wg - 2 + (lane >> 4) * 2) * 64 + wi * 16 + (lane & 15)];
        uint4 v;
#pragma unroll
        for (int j = 0; j < 4; j++) {
          if (j == 2) v = ld_relaxed4(src);
          mbar_wait(bar(B_FULL + (4 + j) % 6), j < 2 ? layer : 1);
          last_tile(1, j);
          if (j == 0) { wg_commit(); wg_wait<1>(); mbar_arrive_e(bar(B_E23)); }
        }
        wg_commit();
        last_tile(0, 0);
        wg_commit();
        if (warp != 9) STEPT(4);
#pragma unroll 1
        for (uint32_t spins = 0; !__all_sync(0xffffffffu, v.z == tag) && spins < SPIN_LIMIT; spins++) v = ld_relaxed4(src);
#pragma unroll
        for (int j = 0; j < 4; j++) {
          pa[j >> 1][j & 1] = __uint_as_float(__shfl_sync(0xffffffffu, v.x, g + 8 * j));
          pb[j >> 1][j & 1] = __uint_as_float(__shfl_sync(0xffffffffu, v.y, g + 8 * j));
        }
        if (warp != 9) STEPT(5);
      }
      const int prow = (int)s_misc[M_SEL0] - rb * 256;
      const float4* cs = (const float4*)(smem + OFF_CS) + q;
      auto finish = [&](int m, int b, float2 c, uint32_t* dst) {
        dst[0] = pack_bf16(acc[m][4 * b] * pa[m][0] - c.x * pb[m][0], acc[m][4 * b + 1] * pa[m][0] - c.y * pb[m][0]);
        dst[1] = pack_bf16(acc[m][4 * b + 2] * pa[m][1] - c.x * pb[m][1], acc[m][4 * b + 3] * pa[m][1] - c.y * pb[m][1]);
      };
      auto grp = [](int n) { return n < 8 ? 4 + ((n >> 1) & 1) * 4 + (n >> 2) * 2 + (n & 1) : n - 8; };
      float4 cq[2] = {cs[grp(0) * 4], cs[grp(1) * 4]};
      auto next = [&](int m, int n, uint32_t* r) {
        if (m == 1 && n % 4 == 0) { last_tile(0, 1 + n / 4); wg_commit(); }
        const float4 c = cq[n & 1];
        cq[n & 1] = cs[grp((n + 2) % 12) * 4];
        finish(m, 2 * grp(n), make_float2(c.x, c.y), r); finish(m, 2 * grp(n) + 1, make_float2(c.z, c.w), r + 2);
      };
#pragma unroll
      for (int m = 1; m >= 0; m--) {
        if (m == 1) {
          wg_wait<1>();
          fence_regs<96>(acc[1]);
          mbar_wait(bar(B_E23), layer);
          if (warp != 9) STEPT(0);
        } else {
          wg_wait<0>();
          fence_regs<96>(acc[0]);
          if (warp != 9) STEPT(1);
          if (lane < 2) mbar_arrive_cluster(bar(B_QDONE), lane);
          if (warp == 9) PROF(2);
        }
        const int qb = wg - 2 + 2 * m;
        const bool patch = prow >> 4 == qb * 4 + wi;
#pragma unroll
        for (int jj = 0; jj < 8; jj++) {
          const int h = jj >> 2;
          uint32_t r[4];
          next(m, jj, r);
          if (m == 0 && jj == 0) named_bar(5, 256);
          stsm_x4(sbase + kv_off(h, 4 + 2 * m) + (wg - 2) * 8192 + ((jj >> 1) & 1) * 4096 + srow * 64 + ((((jj & 1) * 2 + (mi >> 1)) ^ ((srow >> 1) & 3)) << 4),
              r[0], r[1], r[2], r[3]);
        }
        if (patch) {
          mbar_wait(bar(B_CS), 1);
          __syncwarp();
          if (lane < 16)
            *(uint4*)(smem + kv_off(g >> 1, 4 + qb) + (g & 1) * 4096 + (prow & 63) * 64 + ((q ^ ((prow >> 1) & 3)) << 4)) =
              *(const uint4*)(smem + OFF_PATCH + 128 + (g & 1) * 128 + (g >> 1) * 64 + q * 16);
        }
        fence_async_smem();
        __syncwarp();
        mbar_arrive_e(bar(B_KVREADY + 1 - m));
        if (warp != 9) STEPT(3 - m);
        pa[m][0] *= SM_C; pa[m][1] *= SM_C; pb[m][0] *= SM_C; pb[m][1] *= SM_C;
#pragma unroll
        for (int jj = 0; jj < 4; jj++) {
          uint32_t r[4];
          next(m, 8 + jj, r);
          *(uint4*)(smem + qo_off(jj >> 1, 2 * m) + (warp - 8) * 1024 + (jj & 1) * 512 + lane * 16) = make_uint4(r[0], r[1], r[2], r[3]);
        }
        __syncwarp();
        if (patch) {
          *(uint32_t*)(smem + qo_off(lane >> 4, 2 * m) + (warp - 8) * 1024 + (mi & 1) * 512 + ((prow & 7) * 4 + q) * 16 + ((g & 1) * 2 + ((prow >> 3) & 1)) * 4) =
              *(const uint32_t*)(smem + OFF_PATCH + lane * 4);
          __syncwarp();
        }
      }
      if (warp == 9) PROF(3);
      mbar_arrive_e(bar(B_QREADY));
      regs_dec<120>();
    } else {
      if (pass > 0) {
        const unsigned layer = pass - 1;
        PHASE_IDS
        const uint32_t tag = s_misc[M_TAG];
        if (warp == 7) {
          uint32_t* tab = (uint32_t*)(smem + OFF_PATCH);
#pragma unroll
          for (int j = 0; j < 2; j++) { const int w = lane + 32 * j; tab[(w & 3) * 16 + (w >> 2)] = ((const uint32_t*)P.w_r)[nb * 64 + w]; }
          tab[64 + lane] = lane < 16 ? 0x3F803F80u : 0u;
          float tot = 0.f;
#pragma unroll 1
          for (int j = 0; j < 4; j++) {
            const uint4 u = ((const uint4*)P.w_r)[lane + 32 * j];
            tot += bf_lo(u.x) + bf_hi(u.x) + bf_lo(u.y) + bf_hi(u.y) + bf_lo(u.z) + bf_hi(u.z) + bf_lo(u.w) + bf_hi(u.w);
          }
          s_misc[M_WSUM] = __float_as_uint(warp_sum(tot));
        }
        if (layer == 1) {
          const float2 ln = g_rowln[nb][mb * 128 + tid - 128];
          const uint32_t m2 = pack_bf16(ln.x, ln.x);
          uint8_t* row = smem + qo_off(0, wi & 2) + (tid & 63) * 128;
          mbar_wait(bar(B_RES), 1);
#pragma unroll 1
          for (int j = 0; j < 8; j++) {
            uint4* c = (uint4*)(row + (((j + lane) & 7) << 4));
            const uint4 v = c[0], w = c[512];
            c[0] = make_uint4(add_ln_pair(v.x, m2, ln.y), add_ln_pair(v.y, m2, ln.y), add_ln_pair(v.z, m2, ln.y), add_ln_pair(v.w, m2, ln.y));
            c[512] = make_uint4(add_ln_pair(w.x, m2, ln.y), add_ln_pair(w.y, m2, ln.y), add_ln_pair(w.z, m2, ln.y), add_ln_pair(w.w, m2, ln.y));
          }
          const int prow = (int)s_misc[M_SEL0] - mb * 128;
          __syncwarp();
          if (prow >> 5 == wi && lane < 16)
            *(uint4*)(smem + qo_off(0, wi & 2) + (lane >> 3) * 8192 + (prow & 63) * 128 + (((lane ^ prow) & 7) << 4)) = poll4(&g_x2row[(nb * 16 + lane) * 2]);
          PROF(30);
        }
        __syncwarp();
        mbar_arrive_e(bar(B_RST));
        if (warp == 4) {
          named_bar(6, 320);
          spin_cycles(DELAY_S);
          uint4 c, u0 = {}, u1 = {};
          uint32_t u2 = 0, best = 0, spins = 0;
          int src;
#pragma unroll 1
          for (;;) {
            src = (~best & 0x7FFu) >> 7;
            const uint4* xsel = &g_cand[layer][src * 128];
            c = ld_relaxed4(&g_slot[layer][(lane & 15) * 8]);
            if (best) {
              u0 = ld_relaxed4(xsel + rank * 64 + lane); u1 = ld_relaxed4(xsel + rank * 64 + 32 + lane);
              u2 = ld_relaxed((const uint32_t*)(xsel + (bid >> 4) * 16 + q * 4) + (bid & 15));
            }
            const uint32_t prev = best;
            best = __reduce_max_sync(0xffffffffu, c.w == tag ? c.x : 0u);
            if ((__all_sync(0xffffffffu, c.w == tag && valid4(u0) && valid4(u1) && u2 != SENT) && best == prev) || ++spins > SPIN_LIMIT) break;
          }
          const float sel_m = __uint_as_float(__shfl_sync(0xffffffffu, c.y, src)), sel_inv = __uint_as_float(__shfl_sync(0xffffffffu, c.z, src));
          const uint32_t m2 = pack_bf16(sel_m, sel_m);
          uint4* xs = (uint4*)(smem + T_XS) + (lane & 16) + q * 4 + (g & 3);
          xs[0] = make_uint4(ln_pair(u0.x, m2, sel_inv), ln_pair(u0.y, m2, sel_inv), ln_pair(u0.z, m2, sel_inv), ln_pair(u0.w, m2, sel_inv));
          xs[32] = make_uint4(ln_pair(u1.x, m2, sel_inv), ln_pair(u1.y, m2, sel_inv), ln_pair(u1.z, m2, sel_inv), ln_pair(u1.w, m2, sel_inv));
          s_misc[M_KEY] = best; s_misc[M_MEAN] = __float_as_uint(sel_m); s_misc[M_INV] = __float_as_uint(sel_inv);
          s_misc[M_XQ + q] = u2;
          if (layer == 0) s_misc[M_SEL0] = ~best & 0x7FFu;
          PROF(16);
        }
        if (layer == 1) {
          named_bar(7, 512);
          const int sel = SEQ - 1 - (int)(s_misc[M_KEY] & 0x7FFFu), skip = sel >> 7 == mb ? (sel >> 6) & 1 : -1;
          if (warp == 7) store_tile(1, skip, false);
          if (warp == 4) {
            mbar_wait_cluster(bar(B_HX), 1);
            ((bf16*)(smem + OFF_PATCH + 256))[((lane >> 1) & 3) * 8 + (lane >> 3) * 2 + (lane & 1)] = __float2bfloat16_rn(hidden());
            asm volatile("bar.arrive 10, 288;" ::: "memory");
          }
#pragma unroll 1
          for (int c = tid - 128; c < 1024 && skip >= 0; c += 128) {
            const int r = c >> 4;
            if (r != (sel & 63))
              *(uint4*)(P.out + (size_t)(mb * 128 + skip * 64 + r) * DM + nb * 128 + (c & 15) * 8) =
                *(const uint4*)(smem + X_ST + skip * 16384 + ((c >> 3) & 1) * 8192 + r * 128 + (((c ^ r) & 7) << 4));
          }
          __syncwarp();
        } else asm volatile("bar.arrive 7, 512;" ::: "memory");
        if (warp == 5 && layer == 0) {
          named_bar(8, 288);
          if (nb > 0) spin_cycles(X_STAGGER);
          store_tile(0, -1, true);
          set_flag(&g_xflag[mb][nb].v[0], tag);
          PROF(17);
          poll_flag(&g_xflag[2 * rb + (lane & 1)][0].v[0], tag);
          fence_async_global();
          load_a(0, 0, 1);
          PROFL(1, 1);
        }
      }
      named_bar(1 + (fresh_tid() >> 7), 128);
      regs_dec<32>();
#pragma unroll 1
      for (;;) {
        const unsigned pass = __shfl_sync(0xffffffffu, pass_v, 0);
        if (pass > 0) {
          const unsigned layer = pass - 1;
          PHASE_IDS
          const uint32_t tag = s_misc[M_TAG], bkey = s_misc[M_KEY];
          const int sel = SEQ - 1 - (int)(bkey & 0x7FFFu);
          if (warp == 3) {
            if (layer == 1) {
#pragma unroll
              for (int j = 0; j < 3; j++) ((uint4*)g_vw)[bid * 96 + j * 32 + lane] = make_uint4(0, 0, 0, 0);
            }
            if (bid == 0 && lane == 0) g_sel[layer] = sel;
          }
          __syncwarp();
          if (layer == 0) {
            auto load_down = [&](int j) {
              mbar_expect_tx(bar(B_DN + j), 2 * FFN_PIECE);
              bulk_load_h(sbase + SL_F + j * 2 * FFN_PIECE, P.w_d + (size_t)((cl * 56 + rank * 28) + j * 14) * DM, 2 * FFN_PIECE, bar(B_DN + j), policy_evict_first());
            };
            if (warp == 5) {
              load_a(2, 2, 1);
              poll_flag(&g_xflag[2 * rb + (lane & 1)][(lane >> 1) & 7].v[0], tag);
              fence_async_global();
              load_a(4, 4, 1);
            }
            float hv = 0.f;
            if (wg == 1) { mbar_wait_cluster(bar(B_HX), 0); hv = rbf(hidden()); fence_regs<1>(&hv); }
            named_bar(9, 512);
            if (warp == 0) {
              fence_async_smem();
              if (lane < 16) mbar_arrive_cluster(bar(B_QFREE), lane & 1);
              mbar_wait(bar(B_QFREE), 1);
              load_w(4, 4); load_w(5, 5);
              load_down(0);
            } else if (wg == 1) {
              if (warp == 4) { mbar_wait(bar(B_DN), 0); load_down(1); }
              float d[8] = {0.f, 0.f, 0.f, 0.f, 0.f, 0.f, 0.f, 0.f};
              const uint4* wrow = (const uint4*)(smem + SL_F) + tid - 128;
              mbar_wait(bar(B_DN), 0);
              uint4 w0 = wrow[0];
#pragma unroll 1
              for (int j = 0; j < 28; j += 2) {
                const uint4 w1 = wrow[j * 128 + 128];
                fma8(d, w0, __shfl_sync(0xffffffffu, hv, j));
                if (j == 12) mbar_wait(bar(B_DN + 1), 0);
                w0 = wrow[min(j + 2, 27) * 128];
                fma8(d, w1, __shfl_sync(0xffffffffu, hv, j + 1));
              }
              uint4* dst = &g_ypart[0][bid * 256 + (tid - 128) * 2];
              st_relaxed4(dst, make_uint4(__float_as_uint(d[0]), __float_as_uint(d[1]), __float_as_uint(d[2]), __float_as_uint(d[3])));
              st_relaxed4(dst + 1, make_uint4(__float_as_uint(d[4]), __float_as_uint(d[5]), __float_as_uint(d[6]), __float_as_uint(d[7])));
              asm volatile("bar.arrive 11, 160;" ::: "memory");
              PROF(20);
            } else if (warp == 2) {
              named_bar(11, 160);
              fence_async_smem();
              load_ws(WS_PACE);
            }
          } else {
            if (wg == 1) named_bar(9, 384);
            cluster_arrive();
          }
          if (wg == 1) {
            const int t_y = (int)clock();
            const uint32_t xw = s_misc[M_XQ + ((lane & 7) >> 1)];
            const float x = (lane & 1) ? bf_hi(xw) : bf_lo(xw);
            float xn = rbf(rbf(x - __uint_as_float(s_misc[M_MEAN])) * __uint_as_float(s_misc[M_INV]));
            uint32_t u = bkey & 0xFFFF0000u;
            u = (u & 0x80000000u) ? (u & 0x7FFFFFFFu) : (~u & 0xFFFF0000u);
            float sg = rbf(__fdividef(1.f, 1.f + __expf(-__uint_as_float(u))));
            uint32_t* dst = (layer == 0 ? (uint32_t*)&g_x2row[bid * 2] : (uint32_t*)(P.out + (size_t)sel * DM + bid * 8)) + (lane >> 1);
            asm volatile("" : "+f"(xn), "+f"(sg), "+l"(dst));
#pragma unroll 1
            while ((int)clock() - t_y < DELAY_Y) {}
            const uint4* src = &g_ypart[layer][((tid - 128) >> 1) * 256 + bid * 2 + (tid & 1)];
            uint4 v, w;
            uint32_t spins = 0;
#pragma unroll 1
            do { v = ld_relaxed4(src); w = ld_relaxed4(src + 64 * 256); } while (!__all_sync(0xffffffffu, valid4(v) && valid4(w)) && ++spins < SPIN_LIMIT);
            float a[4] = {__uint_as_float(v.x) + __uint_as_float(w.x), __uint_as_float(v.y) + __uint_as_float(w.y),
                  __uint_as_float(v.z) + __uint_as_float(w.z), __uint_as_float(v.w) + __uint_as_float(w.w)};
            const bool b1 = lane & 2, b2 = lane & 4;
            float c0 = (b1 ? a[1] : a[0]) + __shfl_xor_sync(0xffffffffu, b1 ? a[0] : a[1], 2);
            float c1 = (b1 ? a[3] : a[2]) + __shfl_xor_sync(0xffffffffu, b1 ? a[2] : a[3], 2);
            float y = (b2 ? c1 : c0) + __shfl_xor_sync(0xffffffffu, b2 ? c0 : c1, 4);
            y += __shfl_xor_sync(0xffffffffu, y, 8);
            y += __shfl_xor_sync(0xffffffffu, y, 16);
            float* red = (float*)(smem + OFF_PATCH);
            red[wi * 8 + (lane & 1) * 4 + ((lane >> 1) & 3)] = y;
            named_bar(2, 128);
            if (warp == 4) {
              PROF(21);
              y = (red[lane & 7] + red[8 + (lane & 7)]) + (red[16 + (lane & 7)] + red[24 + (lane & 7)]);
              const float res = x + rbf(xn + rbf(rbf(y) * sg));
              const uint32_t pr = pack_bf16(res, __shfl_down_sync(0xffffffffu, res, 1));
              if (lane < 8 && (lane & 1) == 0) st_relaxed(dst, pr);
              PROF(22);
            }
          }
          if (pass == 2) {
            if (bid == 0 && tid == 128) g_epoch = tag;
            bulk_wait_all();
            __syncwarp();
            cluster_wait();
            return;
          }
        }
        const unsigned layer = pass;
        if (__shfl_sync(0xffffffffu, fresh_tid() >> 5, 0) > 1 - (int)layer) {
          PHASE_IDS
          uint4* xrow = (uint4*)(smem + SL_F + 4 * SL_HD);
          if (wg == 1) {
            if (layer == 0) {
              xrow[tid - 128] = make_uint4(0x3F803F80u, 0x3F803F80u, 0x3F803F80u, 0x3F803F80u);
              if (warp == 5) {
                mbar_wait(bar(B_FULL + 5), 0);
                if (lane == 0) {
#pragma unroll 1
                  for (int i = 11; i > 0; i--) prefetch_tmap(&P.mapA[0] + i);
                }
                __syncwarp();
                load_ws(WS_PACE);
              }
            } else xrow[tid - 128] = poll4(&g_x2row[(tid - 128) * 2]);
            PROF(23);
          }
          named_bar(12, 192 + 32 * layer);
          if (warp == 1) {
            float mean = 0.f;
#pragma unroll 1
            for (int pass2 = 0; pass2 < 2; pass2++) {
              float acc = 0.f;
#pragma unroll 1
              for (int j = lane; j < 128; j += 32) {
                const uint4 v = xrow[j];
                const uint32_t w[4] = {v.x, v.y, v.z, v.w};
#pragma unroll
                for (int c = 0; c < 4; c++) {
                  const float d0 = bf_lo(w[c]) - mean, d1 = bf_hi(w[c]) - mean;
                  acc += pass2 ? d0 * d0 + d1 * d1 : d0 + d1;
                }
              }
              acc = warp_sum(acc) * (1.f / DM);
              if (pass2 == 0) mean = acc;
              else { s_misc[M_PMEAN] = __float_as_uint(rbf(mean)); s_misc[M_PINV] = __float_as_uint(ln_inv(acc)); }
            }
          } else {
            mbar_wait(bar(B_WS), layer);
            const uint8_t* wa = smem + SL_F + (g >> 1) * SL_HD + ((warp - 2) >> 1) * 4096 + (g & 1) * 2048;
            const uint32_t* xs = (const uint32_t*)xrow + rb * 64 + g * 8;
            const int ch = (warp & 1) * 4 + q;
            float d[8] = {0.f, 0.f, 0.f, 0.f, 0.f, 0.f, 0.f, 0.f};
            auto wrow = [&](int j) { j = (j ^ ((g & 1) * 4)) & 15; return *(const uint4*)(wa + j * 128 + (((ch ^ j) & 7) << 4)); };
            uint4 w0 = wrow(0);
#pragma unroll 1
            for (int j = 0; j < 16; j += 2) {
              const uint32_t xx = xs[(j >> 1) ^ ((g & 1) * 2)];
              const uint4 w1 = wrow(j + 1);
              fma8(d, w0, bf_lo(xx));
              w0 = wrow(j + 2);
              fma8(d, w1, bf_hi(xx));
            }
#pragma unroll
            for (int c = 0; c < 4; c++) d[c] = ((g & 4) ? d[c + 4] : d[c]) + __shfl_xor_sync(0xffffffffu, (g & 4) ? d[c] : d[c + 4], 16);
#pragma unroll
            for (int c = 0; c < 2; c++) d[c] = ((g & 2) ? d[c + 2] : d[c]) + __shfl_xor_sync(0xffffffffu, (g & 2) ? d[c] : d[c + 2], 8);
            d[0] = ((g & 1) ? d[1] : d[0]) + __shfl_xor_sync(0xffffffffu, (g & 1) ? d[0] : d[1], 4);
            st_relaxed(&g_vw[layer][rb][((warp - 2) >> 1) * DM + hp * 64 + ch * 8 + g], enc(d[0]));
          }
          named_bar(12, 192 + 32 * layer);
          PROF(24);
        }
        PHASE_IDS
        if (wg == 0) {
          if (warp == 0) {
            if (layer == 0) {
#pragma unroll 1
              for (int i = 2; i < 6; i++) { load_w(i, i); if (!(i & 1)) load_a(i, i, 0); }
            }
            int s = 0, u = 0;
#pragma unroll 1
            for (int i = 6; i < 32; i++) {
              if (layer == 1) mbar_arrive_e(bar(B_EMPTY + s));
              mbar_wait(bar(B_EMPTY + s), (u + (s > 1 ? 0 : layer)) & 1);
              if (s & 1) load_a(s - 1, i - 1, layer);
              load_w(s, i);
              if (++s == 6) { s = 0; u++; }
            }
          } else if (warp == 1) {
            if (layer == 0) {
              const uint32_t tag = ld_relaxed(&g_epoch) + 1;
              if (lane < 16) g_rowab[0][rb * 256 + hp * 16 + lane] = make_uint4(0, 0, 0, 0);
              float shift = 0.f, sum = 0.f, sq = 0.f;
              const int r = hp * 16 + (lane >> 1);
#pragma unroll 1
              for (int i = 0; i < 32; i++) {
                mbar_wait(bar(B_FULL + i % 6), (i / 6) & 1);
                const uint8_t* base = smem + ((i % 6) >> 1) * STG + r * 128;
                uint4 v[2];
#pragma unroll
                for (int j = 0; j < 2; j++) v[j] = *(const uint4*)(base + ((((i & 1) * 4 + (lane & 1) * 2 + j) ^ (r & 7)) << 4));
                if (i == 0) shift = __shfl_sync(0xffffffffu, bf_lo(v[0].x), lane & ~1);
#pragma unroll
                for (int j = 0; j < 2; j++) {
                  const uint32_t w[4] = {v[j].x, v[j].y, v[j].z, v[j].w};
#pragma unroll
                  for (int c = 0; c < 4; c++) {
                    const float d0 = bf_lo(w[c]) - shift, d1 = bf_hi(w[c]) - shift;
                    sum += d0 + d1; sq = fmaf(d0, d0, fmaf(d1, d1, sq));
                  }
                }
                fence_async_smem();
                __syncwarp();
                if (i < 26) mbar_arrive_e(bar(B_EMPTY + i % 6));
              }
              sum += __shfl_xor_sync(0xffffffffu, sum, 1); sq += __shfl_xor_sync(0xffffffffu, sq, 1);
              const float dm = sum * (1.f / DM), var = fmaxf(sq * (1.f / DM) - dm * dm, 0.f), mean = shift + dm;
              const float inv = ln_inv(var);
              if ((lane & 1) == 0) st_relaxed4(&g_rowab[0][rb * 256 + r], make_uint4(__float_as_uint(inv), __float_as_uint(rbf(mean) * inv), tag, 0));
            }
            __syncwarp();
            mbar_arrive_e(bar(B_E23));
            if (rb == 0) {
              mbar_wait(bar(B_QDONE), layer);
#pragma unroll 1
              for (int j = lane; j < 512; j += 32) ((uint4*)(smem + kv_off(1, 0)))[j] = make_uint4(0, 0, 0, 0);
              fence_async_smem();
              __syncwarp();
              if (lane < 3) mbar_arrive(bar(B_HALO + lane));
            }
          } else if (warp == 3) {
            if (rb > 0) { mbar_expect_tx(bar(B_HALO), 16384); mbar_expect_tx(bar(B_HALO + 1), 16384); mbar_expect_tx(bar(B_HALO + 2), 32768); }
            fence_async_smem();
            load_gu(0, layer ? GU_PACE1 : GU_PACE, 0, 4);
            PROF(27);
          } else {
            const uint4 sent = make_uint4(SENT, SENT, SENT, SENT), zero = make_uint4(0, 0, 0, 0);
            if (layer == 0) {
              const int f = lane >> 1;
              Flag* fl = f < 2 ? &g_kvflag[rb >> 1][hp][f] : f < 4 ? &g_oflag[rb][f & 1][hp] : &g_xflag[mb][nb];
              if (f < 5 && (f >= 2 || (rank == 1 && rb < 7))) ((uint4*)fl)[lane & 1] = zero;
            }
#pragma unroll 1
            for (int t = lane; t < 128; t += 32) {
              g_ypart[layer][bid * 256 + t] = sent; g_ypart[layer][bid * 256 + 128 + t] = sent;
              g_part[layer][nb * SEQ + mb * 128 + t] = zero;
              if (t < 16) g_cand[layer][mb * 128 + nb * 16 + t] = sent;
              else if (t < 18) { if (nb == 0) g_slot[layer][mb * 8 + t - 16] = zero; }
              else if (t < 20) { if (layer == 0) g_x2row[bid * 2 + t - 18] = sent; }
            }
            __syncwarp();
            mbar_arrive_e(bar(B_CS));
          }
          __syncwarp();
          if (warp == 0) {
            if (rank == 0) mbar_wait(bar(B_QDONE), layer);
            mbar_wait(bar(B_KVREADY), layer);
            export_halo(0);
            if (rank == 1) {
              bulk_wait_all();
              asm volatile("bar.arrive 13, 64;" ::: "memory");
              if (rb < 7) set_flag(&g_kvflag[rb >> 1][hp][0].v[layer], s_misc[M_TAG]);
            }
            PROF(4);
          } else if (warp == 3 && rank == 1) {
            mbar_wait(bar(B_KVREADY + 1), layer);
            named_bar(13, 64);
            export_halo(1);
          }
        } else {
          const int t = tid - 128, go = (t >> 5) * DM + hp * 64 + (t & 31) * 2;
          if (layer == 0 && t == 96) { s_misc[M_TAG] = ld_relaxed(&g_epoch) + 1; s_misc[M_SEL0] = 0xFFFFFFFFu; s_misc[M_PROG] = s_misc[M_PROG + 1] = 0; }
          if ((layer == 0 || (int)s_misc[M_SEL0] >> 8 == rb) && warp < 7) {
            spin_cycles(layer ? 300 : 1500);
            uint2 w[8];
            uint32_t spins = 0;
            bool ok;
#pragma unroll 1
            do {
              ok = true;
#pragma unroll
              for (int j = 0; j < 8; j++) w[j] = ld_relaxed2(&g_vw[layer][j][go]);
#pragma unroll
              for (int j = 0; j < 8; j++) ok = ok && w[j].x && w[j].y;
            } while (!__all_sync(0xffffffffu, ok) && ++spins < SPIN_LIMIT);
            float s0 = 0.f, s1 = 0.f;
#pragma unroll
            for (int j = 0; j < 8; j++) { s0 += dec(w[j].x); s1 += dec(w[j].y); }
            float2* csp = (float2*)(smem + OFF_CS) + (t & ~7) + (t & 3) * 2 + ((t >> 2) & 1);
            if (layer == 0) *csp = make_float2(s0, s1);
            else {
              const float2 c = *csp;
              const float a = __uint_as_float(s_misc[M_PINV]) * (warp == 4 ? SM_C : 1.f), b = __uint_as_float(s_misc[M_PMEAN]) * a;
              ((uint32_t*)(smem + OFF_PATCH))[t] = pack_bf16(s0 * a - c.x * b, s1 * a - c.y * b);
            }
            PROF(25);
          }
          __syncwarp();
          mbar_arrive_e(bar(B_CS));
        }
        __syncwarp();
        if (wi == 0) mbar_wait(bar(B_QREADY), layer);
        named_bar(1 + (fresh_tid() >> 7), 128);
        if (__shfl_sync(0xffffffffu, fresh_tid() >> 7, 0) == 0) {
          regs_inc<152>();
          uint32_t gu[112];
          {
            PHASE_IDS
            const uint32_t tag = s_misc[M_TAG];
            mbar_wait(bar(B_GU), layer);
#pragma unroll
            for (int j = 0; j < 28; j++) fetch_gu(gu + 4 * j, warp * 4 + (j & 3), j >> 2);
            fence_async_smem();
            named_bar(1, 128);
            if (warp == 0) {
              mbar_wait(bar(B_ADONE), layer);
#pragma unroll 1
              for (int k = 2; k < 16; k++) {
#pragma unroll 1
                for (uint32_t spins = 0; (int)s_misc[M_PROG + (k >> 3)] <= (k & 7) + 16 * (int)layer && spins < SPIN_LIMIT; spins++) {}
                if (k >= 4) mbar_wait(bar(B_WEMPTY + (k & 3)), ((k >> 2) - 1 + ((k & 2) ? layer : 0)) & 1);
                load_o(k); load_wo(k);
                STEPT(16 + k);
                if (k == RES_K) { mbar_wait(bar(B_OST + 1), layer); load_res(1, layer); }
              }
              if (layer == 1) {
                mbar_wait(bar(B_WEMPTY + 1), 1);
                mbar_expect_tx(bar(B_DN), 4 * FFN_PIECE);
                tma_load3_h(sbase + wo_off(0), &P.mapD, 0, (cl * 56 + rank * 28), 0, bar(B_DN), policy_evict_first());
              }
              named_bar(6, 320);
              if (layer == 0) {
                mbar_wait(bar(B_QFREE), 0);
#pragma unroll 1
                for (int i = 0; i < 4; i++) load_w(i, i);
              } else tma_load3_h(sbase + wo_off(0) + 2 * FFN_PIECE, &P.mapD, 0, (cl * 56 + rank * 28), 8, bar(B_DN), policy_evict_first());
            } else if (warp < 3) {
              const int h = warp - 1;
#pragma unroll 1
              for (int qb = 3; qb >= 0; qb--) {
                mbar_wait(bar(B_UNIT + h * 4 + 3 - qb), layer);
                bulk_store(g_o + (size_t)((((rb * 2 + (qb >> 1)) * 2 + h) * 16 + hp) * 2 + (qb & 1)) * 4096, sbase + qo_off(h, qb), 4096);
              }
              bulk_commit();
              if (h == 0 && lane < 2) mbar_arrive_cluster(bar(B_OST), lane);
              bulk_wait_all();
              if (h == 1) mbar_arrive_e(bar(B_OST + 1));
              set_flag(&g_oflag[rb][h][hp].v[layer], tag);
              PROF(28 + 3 * h);
              if (h == 0) { load_res(0, layer); mbar_wait(bar(B_OST), layer); load_wo(0); load_wo(1); }
              int n = 0, first = h;
#pragma unroll 1
              for (uint32_t spins = 0; n < 8 && spins < SPIN_LIMIT; spins++) {
                n = (__ffs(__ballot_sync(0xffffffffu, ld_relaxed(&g_oflag[rb][h][lane & 15].v[layer]) != tag || lane == 16)) - 1) >> 1;
                asm volatile("fence.acquire.gpu;" ::: "memory");
                fence_async_global();
                if (!first && n >= 2) {
                  first = 1;
                  load_o(0); load_o(1);
                  PROF(15);
                }
                s_misc[M_PROG + h] = n + 16 * layer;
              }
              if (h) PROF(26);
            } else {
              mbar_expect_tx(bar(B_HX), 2240);
#pragma unroll 1
              for (int p = 0; p < 2; p++) {
                if (rank == 0 && rb > 0) {
                  poll_flag(&g_kvflag[(rb - 1) >> 1][hp][p].v[layer], tag);
                  fence_async_global();
#pragma unroll 1
                  for (int h = 0; h < 2; h++)
                    bulk_load_h(sbase + kv_off(h, 2 - 2 * p), g_kv + (size_t)((cl - 16) * 4 + p * 2 + h) * 16384, 16384, bar(B_HALO + (p ? 2 : h)), policy_evict_first());
                }
                if (p == 0) {
                  PROF(5);
                  if (rank == 0) { load_gu(1, 0, 0, 1); export_halo(1); }
                  else if (rb < 7) { bulk_wait_all(); set_flag(&g_kvflag[rb >> 1][hp][1].v[layer], tag); }
                }
              }
              if (rb == 0 || rb == 7) spin_cycles(1000);
              PROF(6);
              load_gu(1, GUB_PACE, 1 - rank, 4);
            }
          }
          PHASE_IDS
          uint4 xa = {}, xb = {};
          named_bar(7, 512);
          if (g == 0) { xa = ((const uint4*)(smem + T_XS))[warp * 8 + q]; xb = ((const uint4*)(smem + T_XS))[warp * 8 + 4 + q]; }
          __syncwarp();
          float d[7][4] = {};
#pragma unroll
          for (int j = 0; j < 28; j++) {
            const int ks = j / 7, ct = j % 7;
            const uint32_t* a = gu + ct * 16 + ks * 4;
            mma_16816(d[ct], a[0], a[1], a[2], a[3], ks == 0 ? xa.x : ks == 1 ? xa.z : ks == 2 ? xb.x : xb.z, ks == 0 ? xa.y : ks == 1 ? xa.w : ks == 2 ? xb.y : xb.w);
          }
#pragma unroll
          for (int ct = 0; ct < 7; ct++) send_gu(d[ct][0], d[ct][2], ct, warp);
          __syncwarp();
          if (warp == 2) PROF(18);
          regs_dec<32>();
          pass_v = pass + 1;
          continue;
        }
        break;
      }
      regs_inc<120>();
    }
    const unsigned layer = pass;
    {
      PHASE_IDS
      mbar_wait(bar(B_QREADY), layer);
      if (warp != 9) STEPT(7);
      const int bmin = rb == 0 ? 4 : 0;
      auto kdesc = [&](int h, int b) { const uint32_t v = dlo(SOFF, 16) + (kv_off(h, b) >> 4); return b < bmin ? dlo(SOFF + kv_off(1, 0), 16) : v; };
      auto vdesc = [&](int h, int b) {
        const uint32_t v = dlo(SOFF + 4096, OFF_ONES - 4096) + (kv_off(h, b) >> 10) * VSTEP;
        return b < bmin ? dlo(SOFF + kv_off(1, 0), 4096) : v;
      };
      const int units = wg == 3 ? 0x8630 : (wg == 2 ? 0x8721 : 0x854);
      auto need = [&](int h, int b) { if (b == 3 || b == 1) mbar_wait(bar(B_HALO + (b == 1 ? 2 : h)), layer); };
      auto load_q = [&](uint32_t* qf, int u) {
        *(uint4*)&qf[0] = *(const uint4*)(smem + qo_off(u >> 2, ~u & 3) + wi * 1024 + lane * 16);
        *(uint4*)&qf[4] = *(const uint4*)(smem + qo_off(u >> 2, ~u & 3) + wi * 1024 + 512 + lane * 16);
      };
      auto store_o = [&](const float* o, int u) {
        const float i0 = rcp(o[16]), i1 = rcp(o[18]);
        if (u >= 4 && lane < 2) mbar_arrive_cluster(bar(B_ADONE), lane);
#pragma unroll
        for (int j = 0; j < 2; j++)
          stsm_x4(sbase + qo_off(u >> 2, ~u & 3) + srow * 64 + (((2 * j + (mi >> 1)) ^ ((srow >> 1) & 3)) << 4),
            pack_bf16(o[8 * j] * i0, o[8 * j + 1] * i0), pack_bf16(o[8 * j + 2] * i1, o[8 * j + 3] * i1),
            pack_bf16(o[8 * j + 4] * i0, o[8 * j + 5] * i0), pack_bf16(o[8 * j + 6] * i1, o[8 * j + 7] * i1));
        fence_async_smem();
        __syncwarp();
        mbar_arrive_e(bar(B_UNIT + u));
      };
      int redo = 0;
      {
        const int dl = g - 2 * q;
        const uint32_t mt = shl_clamp(0xFFFFFFFFu, max(16 * dl + 16, 0));
        uint32_t qf[8];
        float s[32];
        load_q(qf, units & 7);
        wg_fence();
        qk64(s, qf, kdesc((units >> 2) & 1, 6 - (units & 3)));
        wg_commit();
        wg_wait<0>();
        fence_regs<32>(s);
#pragma unroll 1
        for (int ul = units; ul != 8; ul >>= 4) {
          const int u = ul & 7, h = u >> 2, qb = 3 - (u & 3);
          float o[20];
          uint32_t p1[16], p2[16], p3[16], p4[16], p5[16];
          if (warp != 9) STEPT(8 + nu * 8);
          exp_pack<8>(s, p1);
          fence_regs_u<16>(p1);
          need(h, qb + 2);
          {
            float s2[32];
            const uint32_t vd = vdesc(h, qb + 3);
            wg_fence();
            qk64(s2, qf, kdesc(h, qb + 2));
            wg_commit();
            wg_rs40t_z<H64>(o, p1[0], p1[1], p1[2], p1[3], vd);
            wg_rs40t<H64>(o, p1[4], p1[5], p1[6], p1[7], vd + VSTEP, 1);
            pv32(o, p1 + 8, vd + 2 * VSTEP);
            wg_commit();
            wg_wait<1>();
            fence_regs<32>(s2);
            if (warp != 9) STEPT(9 + nu * 8);
            exp_pack<8>(s2, p2);
            fence_regs_u<16>(p2);
            wg_wait<0>();
            fence_regs<20>(o);
          }
          need(h, qb + 1);
          {
            float s3[32];
            wg_fence();
            qk64(s3, qf, kdesc(h, qb + 1));
            wg_commit();
            pv32(o, p2, vdesc(h, qb + 2)); pv32(o, p2 + 8, vdesc(h, qb + 2) + 2 * VSTEP);
            wg_commit();
            wg_wait<1>();
            fence_regs<32>(s3);
            if (warp != 9) STEPT(10 + nu * 8);
            exp_pack<8>(s3, p3);
            fence_regs_u<16>(p3);
            wg_wait<0>();
            fence_regs<20>(o);
          }
          need(h, qb);
          const uint32_t kd = kdesc(h, qb + 4), kt = kdesc(h, qb), vd = vdesc(h, qb + 4), vt = vdesc(h, qb);
          {
            float sd[16], st[16];
            wg_fence();
            qk32x2(sd, st, qf, kd, kt);
            wg_commit();
            pv32(o, p3, vdesc(h, qb + 1)); pv32(o, p3 + 8, vdesc(h, qb + 1) + 2 * VSTEP);
            wg_commit();
            wg_wait<1>();
            fence_regs<16>(sd); fence_regs<16>(st);
            if (warp != 9) STEPT(11 + nu * 8);
            edge32(sd, st, p4, p4 + 8, wi, dl, mt);
            fence_regs_u<16>(p4);
            wg_wait<0>();
            fence_regs<20>(o);
          }
          const int un = (ul >> 4) == 8 ? 4 : (ul >> 4) & 7;
          {
            float sd[16], st[16];
            wg_fence();
            qk32x2(sd, st, qf, kd + 128, kt + 128);
            wg_commit();
            pv32(o, p4, vd); pv32(o, p4 + 8, vt);
            wg_commit();
            wg_wait<1>();
            fence_regs<16>(sd); fence_regs<16>(st);
            load_q(qf, un);
            edge32(sd, st, p5, p5 + 8, wi - 2, dl, mt);
            fence_regs_u<16>(p5);
          }
          need(un >> 2, 6 - (un & 3));
          wg_fence();
          pv32(o, p5, vd + 2 * VSTEP); pv32(o, p5 + 8, vt + 2 * VSTEP);
          wg_commit();
          qk64(s, qf, kdesc(un >> 2, 6 - (un & 3)));
          wg_commit();
          wg_wait<1>();
          fence_regs<20>(o);
          if (warp != 9) STEPT(12 + nu * 8);
          const bool unsafe = !(o[16] >= LSUM_MIN && o[16] <= LSUM_MAX && o[18] >= LSUM_MIN && o[18] <= LSUM_MAX);
          if (__any_sync(0xffffffffu, unsafe)) redo |= 1 << u;
          else store_o(o, u);
          wg_wait<0>();
          fence_regs<32>(s);
        }
      }
      if (warp != 9) STEPT(31);
      if (bar_red_or(1 + wg, 128, redo)) {
#pragma unroll 1
        for (int ul = units; ul != 8; ul >>= 4) {
          const int u = ul & 7;
          if (!bar_red_or(1 + wg, 128, redo >> u & 1)) continue;
          const int h = u >> 2, qb = 3 - (u & 3);
          uint32_t qf[8], p[16];
          float o[20], m0 = -INFINITY, m1 = -INFINITY;
          load_q(qf, u);
#pragma unroll
          for (int i = 0; i < 20; i++) o[i] = 0.f;
#pragma unroll 1
          for (int j = 0; j <= (rb == 0 ? qb : 4); j++) {
            const int b = qb + 4 - j;
            float s[32];
            wg_fence();
            qk64(s, qf, kdesc(h, b));
            wg_commit();
            wg_wait<0>();
            fence_regs<32>(s);
            float mx0 = m0, mx1 = m1;
#pragma unroll
            for (int c = 0; c < 8; c++) {
#pragma unroll
              for (int i = 0; i < 4; i++) {
                const int diff = j * 64 + (16 * wi + g + (i >> 1) * 8) - (8 * c + 2 * q + (i & 1));
                if (diff < 0 || diff > 255) s[4 * c + i] = -INFINITY;
              }
              mx0 = fmaxf(mx0, fmaxf(s[4 * c], s[4 * c + 1]));
              mx1 = fmaxf(mx1, fmaxf(s[4 * c + 2], s[4 * c + 3]));
            }
            mx0 = fmaxf(mx0, __shfl_xor_sync(0xffffffffu, mx0, 1)); mx1 = fmaxf(mx1, __shfl_xor_sync(0xffffffffu, mx1, 1));
            mx0 = fmaxf(mx0, __shfl_xor_sync(0xffffffffu, mx0, 2)); mx1 = fmaxf(mx1, __shfl_xor_sync(0xffffffffu, mx1, 2));
            const float r0 = j == 0 ? 0.f : ex2(m0 - mx0), r1 = j == 0 ? 0.f : ex2(m1 - mx1);
            m0 = mx0; m1 = mx1;
#pragma unroll
            for (int i = 0; i < 5; i++) { o[4 * i] *= r0; o[4 * i + 1] *= r0; o[4 * i + 2] *= r1; o[4 * i + 3] *= r1; }
#pragma unroll
            for (int c = 0; c < 8; c++) { s[4 * c] -= m0; s[4 * c + 1] -= m0; s[4 * c + 2] -= m1; s[4 * c + 3] -= m1; }
            exp_pack<8>(s, p);
            fence_regs<20>(o); fence_regs_u<16>(p);
            wg_fence();
            pv32(o, p, vdesc(h, b)); pv32(o, p + 8, vdesc(h, b) + 2 * VSTEP);
            wg_commit();
            wg_wait<0>();
            fence_regs<20>(o);
          }
          named_bar(1 + wg, 128);
          if (redo >> u & 1) store_o(o, u);
          __syncwarp();
        }
      }
      if (wi == 0) PROF(6 + wg);
    }
    pass_v = pass + 1;
  }
}

}

typedef CUresult (*EncodeFn)(CUtensorMap*, CUtensorMapDataType, cuuint32_t, void*, const cuuint64_t*, const cuuint64_t*,
                             const cuuint32_t*, const cuuint32_t*, CUtensorMapInterleave, CUtensorMapSwizzle,
                             CUtensorMapL2promotion, CUtensorMapFloatOOBfill);
static EncodeFn g_encode = nullptr;
struct Dim { uint64_t size, stride; uint32_t box; };
template <int N> static CUtensorMap make_map(const void* ptr, const Dim (&d)[N], int swizzle) {
  CUtensorMap m;
  cuuint64_t dims[N], strides[N];
  cuuint32_t box[N], es[N];
  for (int i = 0; i < N; i++) { dims[i] = d[i].size; strides[i] = d[i].stride; box[i] = d[i].box; es[i] = 1; }
  g_encode(&m, CU_TENSOR_MAP_DATA_TYPE_BFLOAT16, N, const_cast<void*>(ptr), dims, strides + 1, box, es, CU_TENSOR_MAP_INTERLEAVE_NONE,
           swizzle == 128 ? CU_TENSOR_MAP_SWIZZLE_128B : (swizzle == 64 ? CU_TENSOR_MAP_SWIZZLE_64B : CU_TENSOR_MAP_SWIZZLE_NONE),
           swizzle ? CU_TENSOR_MAP_L2_PROMOTION_L2_256B : CU_TENSOR_MAP_L2_PROMOTION_L2_128B, CU_TENSOR_MAP_FLOAT_OOB_FILL_NONE);
  return m;
}
static CUtensorMap map2(const void* ptr, uint64_t inner, uint64_t outer, uint32_t bi, uint32_t bo, int swizzle) {
  const Dim d[2] = {{inner, 0, bi}, {outer, inner * 2, bo}};
  return make_map(ptr, d, swizzle);
}
template <class T> static void* sym_addr(T& sym) { void* p = nullptr; cudaGetSymbolAddress(&p, sym); return p; }

static Params h_p;
static const void* h_key[9];

static cudaLaunchConfig_t launch_cfg(int grid, cudaLaunchAttribute* at) {
  cudaLaunchConfig_t cfg = {};
  cfg.gridDim = dim3(grid); cfg.blockDim = dim3(512); cfg.dynamicSmemBytes = SMEM_BYTES; cfg.stream = cudaStreamPerThread;
  at[0].id = cudaLaunchAttributeClusterDimension;
  at[0].val.clusterDim.x = 2; at[0].val.clusterDim.y = 1; at[0].val.clusterDim.z = 1;
  cfg.attrs = at; cfg.numAttrs = 1;
  return cfg;
}

extern "C" void kernel_launch(void* const* d_in, const int* in_sizes, int n_in, void* d_out, int out_size) {
  const bf16* x = (const bf16*)d_in[0];
  const bf16* wqkv = (const bf16*)d_in[1];
  const bf16* wo = (const bf16*)d_in[2];
  cudaLaunchAttribute at[1];
  bool fresh = g_encode != nullptr && h_key[8] == d_out;
  for (int i = 0; i < 8; i++) fresh = fresh && h_key[i] == d_in[i];
  if (!fresh) {
    if (!g_encode) {
      void* fn = nullptr;
      cudaDriverEntryPointQueryResult st;
      cudaGetDriverEntryPoint("cuTensorMapEncodeTiled", &fn, cudaEnableDefault, &st);
      g_encode = (EncodeFn)fn;
      cudaFuncSetAttribute(mega_kernel, cudaFuncAttributeMaxDynamicSharedMemorySize, SMEM_BYTES);
    }
    bf16* x1 = (bf16*)sym_addr(g_x1);
    Params& p = h_p;
    p.w_r = (const bf16*)d_in[4]; p.w_d = (const bf16*)d_in[7];
    p.out = (bf16*)d_out;
    p.mapA[0] = map2(x, DM, SEQ, 64, 256, 128);
    p.mapA[1] = map2(x1, DM, SEQ, 64, 256, 128);
    { const Dim d[3] = {{DM, 0, 64}, {DM, 3 * DM * 2, 16}, {3, DM * 2, 3}}; p.mapW = make_map(wqkv, d, 128); }
    { const Dim d[3] = {{DM, 0, 64}, {DM, 3 * DM * 2, 32}, {3, DM * 2, 3}}; p.mapWs = make_map(wqkv, d, 128); }
    { const Dim d[3] = {{DM, 0, 64}, {64, DM * 2, 32}, {16, 64 * DM * 2, 2}}; p.mapWo = make_map(wo, d, 128); }
    p.mapRes[0] = map2(x, DM, SEQ, 64, 64, 128);
    p.mapRes[1] = p.mapXst[0] = map2(x1, DM, SEQ, 64, 64, 128);
    p.mapXst[1] = map2(d_out, DM, SEQ, 64, 64, 128);
    p.mapG = map2(d_in[5], FF, DM, 56, 128, 0);
    p.mapU = map2(d_in[6], FF, DM, 56, 128, 0);
    { const Dim d[3] = {{64, 0, 64}, {FF, DM * 2, 28}, {DM / 64, 128, 8}}; p.mapD = make_map(p.w_d, d, 128); }
    for (int b = 0; b < 128; b++) {
      static const int perm[8] = {0, 6, 4, 5, 1, 2, 3, 7};
      const int c = b >> 1, col = c < 4 ? 0 : (c < 36 ? (c - 4) & 7 : (c - 36) % 7 + 1), j = c < 4 ? 4 + c : (c < 36 ? (c - 4) >> 3 : 4 + (c - 36) / 7);
      p.role[b] = (b & 1) | (perm[col] >> 1) << 1 | j << 3 | (perm[col] & 1) << 6;
    }
    for (int i = 0; i < 8; i++) h_key[i] = d_in[i];
    h_key[8] = d_out;
  }
  void* a0[] = {&h_p};
  cudaLaunchConfig_t cfg = launch_cfg(128, at);
  cudaLaunchKernelExC(&cfg, (const void*)mega_kernel, a0);
}
```

```cpp
#include <cuda_runtime.h>
#include <cuda_bf16.h>
#include <cuda.h>
#include <stdint.h>
#pragma nv_diag_suppress 550

namespace {

constexpr int SEQ = 2048, DM = 1024, FF = 3584;
constexpr float LN_EPS = 1e-5f;
typedef __nv_bfloat16 bf16;

__device__ __align__(1024) uint8_t g_kv[3 * 16 * 65536];
__device__ __align__(1024) uint8_t g_o[SEQ * DM * 2];
__device__ __align__(1024) bf16 g_x1[SEQ * DM];
__device__ unsigned g_epoch;
struct __align__(128) Flag { unsigned v[32]; };
__device__ Flag g_kvflag[3][16][2], g_oflag[8][3][16], g_xflag[16][8];
__device__ uint4 g_rowab[2][SEQ];
__device__ __align__(16) uint32_t g_vw[2][8][3 * DM];
constexpr uint32_t SENT = 0xFFFFFFFFu;
__device__ uint4 g_part[2][8 * SEQ];
__device__ uint4 g_slot[2][16 * 8];
__device__ uint4 g_cand[2][16 * 128];
__device__ uint4 g_ypart[2][128 * DM / 4];
__device__ uint4 g_x2row[128 * 2];
__device__ float2 g_rowln[8][SEQ];
__device__ int g_sel[2];

#define PROFL(l, e)
#define PROF(e) PROFL(layer, e)
#define STEPT(i)
#define SPIN_LIMIT 4000000u
__device__ __forceinline__ uint32_t smem_u32(const void* p) { return (uint32_t)__cvta_generic_to_shared(p); }
__device__ __forceinline__ void mbar_init(uint32_t bar, uint32_t cnt) {
  asm volatile("mbarrier.init.shared::cta.b64 [%0], %1;" ::"r"(bar), "r"(cnt) : "memory");
}
#define ELECT "{\n.reg .pred e;\nelect.sync _|e, 0xffffffff;\n@e "
__device__ __forceinline__ void mbar_expect_tx(uint32_t bar, uint32_t bytes) {
  asm volatile(ELECT "mbarrier.arrive.expect_tx.shared::cta.b64 _, [%0], %1;\n}" ::"r"(bar), "r"(bytes) : "memory");
}
__device__ __forceinline__ void mbar_arrive(uint32_t bar) {
  asm volatile("mbarrier.arrive.shared::cta.b64 _, [%0];" ::"r"(bar) : "memory");
}
__device__ __forceinline__ void mbar_arrive_e(uint32_t bar) {
  asm volatile(ELECT "mbarrier.arrive.shared::cta.b64 _, [%0];\n}" ::"r"(bar) : "memory");
}
__device__ __forceinline__ uint32_t mapa(uint32_t addr, uint32_t cta) {
  uint32_t r; asm("mapa.shared::cluster.u32 %0, %1, %2;" : "=r"(r) : "r"(addr), "r"(cta)); return r;
}
__device__ __forceinline__ void mbar_arrive_cluster(uint32_t bar, uint32_t cta) {
  asm volatile("mbarrier.arrive.shared::cluster.b64 _, [%0];" ::"r"(mapa(bar, cta)) : "memory");
}
#define MBAR_WAIT_ASM(QUAL)                                                                                                \
  asm volatile("{\n.reg .pred p;\nWAIT_LOOP:\n.pragma \"nounroll\";\nmbarrier.try_wait.parity" QUAL ".shared::cta.b64 p, [%0], %1;\n" \
               "@!p bra WAIT_LOOP;\n}" ::"r"(bar), "r"(parity) : "memory")
__device__ __forceinline__ void mbar_wait(uint32_t bar, uint32_t parity) { MBAR_WAIT_ASM(""); }
__device__ __forceinline__ void mbar_wait_cluster(uint32_t bar, uint32_t parity) { MBAR_WAIT_ASM(".acquire.cluster"); }
__device__ __forceinline__ void st_async2(uint32_t addr, float a, float b, uint32_t bar) {
  asm volatile("st.async.weak.shared::cluster.mbarrier::complete_tx::bytes.v2.f32 [%0], {%1, %2}, [%3];"
               ::"r"(addr), "f"(a), "f"(b), "r"(bar) : "memory");
}
__device__ __forceinline__ uint64_t policy_evict_first() {
  uint64_t p; asm volatile("createpolicy.fractional.L2::evict_first.b64 %0, 1.0;" : "=l"(p)); return p;
}
__device__ __forceinline__ void tma_load2(uint32_t dst, const CUtensorMap* m, int c0, int c1, uint32_t bar) {
  asm volatile(ELECT "cp.async.bulk.tensor.2d.shared::cluster.global.mbarrier::complete_tx::bytes [%0], [%1, {%3, %4}], [%2];\n}"
               ::"r"(dst), "l"(m), "r"(bar), "r"(c0), "r"(c1) : "memory");
}
__device__ __forceinline__ void tma_load2_h(uint32_t dst, const CUtensorMap* m, int c0, int c1, uint32_t bar, uint64_t pol) {
  asm volatile(ELECT "cp.async.bulk.tensor.2d.shared::cluster.global.mbarrier::complete_tx::bytes.L2::cache_hint [%0], [%1, {%3, %4}], [%2], %5;\n}"
               ::"r"(dst), "l"(m), "r"(bar), "r"(c0), "r"(c1), "l"(pol) : "memory");
}
__device__ __forceinline__ void tma_load3(uint32_t dst, const CUtensorMap* m, int c0, int c1, int c2, uint32_t bar) {
  asm volatile(ELECT "cp.async.bulk.tensor.3d.shared::cluster.global.mbarrier::complete_tx::bytes [%0], [%1, {%3, %4, %5}], [%2];\n}"
               ::"r"(dst), "l"(m), "r"(bar), "r"(c0), "r"(c1), "r"(c2) : "memory");
}
__device__ __forceinline__ void tma_load3_h(uint32_t dst, const CUtensorMap* m, int c0, int c1, int c2, uint32_t bar, uint64_t pol) {
  asm volatile(ELECT "cp.async.bulk.tensor.3d.shared::cluster.global.mbarrier::complete_tx::bytes.L2::cache_hint [%0], [%1, {%3, %4, %5}], [%2], %6;\n}"
               ::"r"(dst), "l"(m), "r"(bar), "r"(c0), "r"(c1), "r"(c2), "l"(pol) : "memory");
}
__device__ __forceinline__ void tma_load3_mc(uint32_t dst, const CUtensorMap* m, int c0, int c1, int c2, uint32_t bar) {
  asm volatile(ELECT "cp.async.bulk.tensor.3d.shared::cluster.global.mbarrier::complete_tx::bytes.multicast::cluster [%0], [%1, {%3, %4, %5}], [%2], %6;\n}"
               ::"r"(dst), "l"(m), "r"(bar), "r"(c0), "r"(c1), "r"(c2), "h"((uint16_t)3) : "memory");
}
__device__ __forceinline__ void bulk_push(uint32_t dst, uint32_t src, uint32_t bytes, uint32_t bar) {
  asm volatile(ELECT "cp.async.bulk.shared::cluster.shared::cta.mbarrier::complete_tx::bytes [%0], [%1], %2, [%3];\n}"
               ::"r"(dst), "r"(src), "r"(bytes), "r"(bar) : "memory");
}
template <int N> __device__ __forceinline__ void regs_inc() { asm volatile("setmaxnreg.inc.sync.aligned.u32 %0;" ::"n"(N)); }
template <int N> __device__ __forceinline__ void regs_dec() { asm volatile("setmaxnreg.dec.sync.aligned.u32 %0;" ::"n"(N)); }
__device__ __forceinline__ void tma_store(const CUtensorMap* m, uint32_t src, int c0, int c1) {
  asm volatile(ELECT "cp.async.bulk.tensor.2d.global.shared::cta.bulk_group [%0, {%2, %3}], [%1];\n}"
               ::"l"(m), "r"(src), "r"(c0), "r"(c1) : "memory");
}
__device__ __forceinline__ void bulk_load_h(uint32_t dst, const void* src, uint32_t bytes, uint32_t bar, uint64_t pol) {
  asm volatile(ELECT "cp.async.bulk.shared::cluster.global.mbarrier::complete_tx::bytes.L2::cache_hint [%0], [%1], %2, [%3], %4;\n}"
               ::"r"(dst), "l"(src), "r"(bytes), "r"(bar), "l"(pol) : "memory");
}
__device__ __forceinline__ void bulk_store(void* dst, uint32_t src, uint32_t bytes) {
  asm volatile(ELECT "cp.async.bulk.global.shared::cta.bulk_group [%0], [%1], %2;\n}" ::"l"(dst), "r"(src), "r"(bytes) : "memory");
}
__device__ __forceinline__ void bulk_commit() { asm volatile("cp.async.bulk.commit_group;" ::: "memory"); }
__device__ __forceinline__ void bulk_wait_all() { asm volatile("cp.async.bulk.wait_group 0;" ::: "memory"); }
__device__ __forceinline__ void fence_async_smem() { asm volatile("fence.proxy.async.shared::cta;" ::: "memory"); }
__device__ __forceinline__ void fence_async_global() { asm volatile("fence.proxy.async.global;" ::: "memory"); }
__device__ __forceinline__ void prefetch_tmap(const CUtensorMap* m) { asm volatile("prefetch.tensormap [%0];" ::"l"(m) : "memory"); }
__device__ __forceinline__ void named_bar(int id, int n) { asm volatile("bar.sync %0, %1;" ::"r"(id), "r"(n) : "memory"); }
__device__ __forceinline__ bool bar_red_or(int id, int n, bool v) {
  uint32_t r;
  asm volatile("{\n.reg .pred p, q;\nsetp.ne.u32 q, %3, 0;\nbarrier.cta.red.or.pred p, %1, %2, q;\nselp.u32 %0, 1, 0, p;\n}"
               : "=r"(r) : "r"(id), "r"(n), "r"((uint32_t)v) : "memory");
  return r != 0;
}
__device__ __forceinline__ void cluster_arrive() { asm volatile("barrier.cluster.arrive.relaxed.aligned;" ::: "memory"); }
__device__ __forceinline__ void cluster_wait() { asm volatile("barrier.cluster.wait.aligned;" ::: "memory"); }
__device__ __forceinline__ unsigned ld_relaxed(const unsigned* p) {
  unsigned v; asm volatile("ld.relaxed.gpu.global.u32 %0, [%1];" : "=r"(v) : "l"(p) : "memory"); return v;
}
__device__ __forceinline__ uint4 ld_relaxed4(const uint4* p) {
  uint4 v; asm volatile("ld.relaxed.gpu.global.v4.u32 {%0, %1, %2, %3}, [%4];" : "=r"(v.x), "=r"(v.y), "=r"(v.z), "=r"(v.w) : "l"(p) : "memory"); return v;
}
__device__ __forceinline__ void st_relaxed(unsigned* p, unsigned v) {
  asm volatile("st.relaxed.gpu.global.u32 [%0], %1;" ::"l"(p), "r"(v) : "memory");
}
__device__ __forceinline__ uint2 ld_relaxed2(const void* p) {
  uint2 v; asm volatile("ld.relaxed.gpu.global.v2.u32 {%0, %1}, [%2];" : "=r"(v.x), "=r"(v.y) : "l"(p) : "memory"); return v;
}
__device__ __forceinline__ void st_relaxed4(uint4* p, uint4 v) {
  asm volatile("st.relaxed.gpu.global.v4.u32 [%0], {%1, %2, %3, %4};" ::"l"(p), "r"(v.x), "r"(v.y), "r"(v.z), "r"(v.w) : "memory");
}
__device__ __forceinline__ bool valid4(uint4 v) { return v.x != SENT && v.y != SENT && v.z != SENT && v.w != SENT; }
__device__ __forceinline__ uint4 poll4(const uint4* p) {
  uint4 v;
  uint32_t spins = 0;
#pragma unroll 1
  do { v = ld_relaxed4(p); } while (!valid4(v) && ++spins < SPIN_LIMIT);
  return v;
}
__device__ __forceinline__ void set_flag(unsigned* p, unsigned tag) {
  asm volatile(ELECT "st.release.gpu.global.u32 [%0], %1;\n}" ::"l"(p), "r"(tag) : "memory");
}
__device__ __forceinline__ void poll_flag(const unsigned* p, unsigned tag) {
#pragma unroll 1
  for (uint32_t spins = 0; !__all_sync(0xffffffffu, ld_relaxed(p) == tag) && spins < SPIN_LIMIT; spins++) {}
  asm volatile("fence.acquire.gpu;" ::: "memory");
}
__device__ __forceinline__ uint32_t enc(float x) { return __float_as_uint(x + 0.0f) ^ 0x80000000u; }
__device__ __forceinline__ float dec(uint32_t u) { return __uint_as_float(u ^ 0x80000000u); }
__device__ __forceinline__ uint32_t hadd_bf2(uint32_t a, uint32_t b) {
  uint32_t r; asm("add.rn.bf16x2 %0, %1, %2;" : "=r"(r) : "r"(a), "r"(b)); return r;
}
__device__ __forceinline__ uint32_t hsub_bf2(uint32_t a, uint32_t b) {
  uint32_t r; asm("sub.rn.bf16x2 %0, %1, %2;" : "=r"(r) : "r"(a), "r"(b)); return r;
}
__device__ __forceinline__ void wg_fence() { asm volatile("wgmma.fence.sync.aligned;" ::: "memory"); }
__device__ __forceinline__ void wg_commit() { asm volatile("wgmma.commit_group.sync.aligned;" ::: "memory"); }
template <int N> __device__ __forceinline__ void wg_wait() { asm volatile("wgmma.wait_group.sync.aligned %0;" ::"n"(N) : "memory"); }
template <int R> __device__ __forceinline__ void fence_regs(float* d) {
#pragma unroll
  for (int i = 0; i < R; i++) asm volatile("" : "+f"(d[i])::"memory");
}
template <int R> __device__ __forceinline__ void fence_regs_u(uint32_t* d) {
#pragma unroll
  for (int i = 0; i < R; i++) asm volatile("" : "+r"(d[i])::"memory");
}
__host__ __device__ constexpr uint32_t dlo(uint32_t addr, uint32_t lbo) { return ((addr & 0x3FFFF) >> 4) | ((lbo >> 4) << 16); }
constexpr uint32_t H128 = 0x40000040u, H64 = 0x80000020u;
__device__ __forceinline__ void stsm_x4(uint32_t addr, uint32_t r0, uint32_t r1, uint32_t r2, uint32_t r3) {
  asm volatile("stmatrix.sync.aligned.m8n8.x4.shared.b16 [%0], {%1, %2, %3, %4};"
               ::"r"(addr), "r"(r0), "r"(r1), "r"(r2), "r"(r3) : "memory");
}
__device__ __forceinline__ void ldsm_x4(uint32_t addr, uint32_t& r0, uint32_t& r1, uint32_t& r2, uint32_t& r3) {
  asm volatile("ldmatrix.sync.aligned.m8n8.x4.shared.b16 {%0, %1, %2, %3}, [%4];"
               : "=r"(r0), "=r"(r1), "=r"(r2), "=r"(r3) : "r"(addr) : "memory");
}
__device__ __forceinline__ void ldsm_x4_t(uint32_t addr, uint32_t& r0, uint32_t& r1, uint32_t& r2, uint32_t& r3) {
  asm volatile("ldmatrix.sync.aligned.m8n8.x4.trans.shared.b16 {%0, %1, %2, %3}, [%4];"
               : "=r"(r0), "=r"(r1), "=r"(r2), "=r"(r3) : "r"(addr) : "memory");
}
__device__ __forceinline__ void mma_16816(float* d, uint32_t a0, uint32_t a1, uint32_t a2, uint32_t a3, uint32_t b0, uint32_t b1) {
  asm volatile("mma.sync.aligned.m16n8k16.row.col.f32.bf16.bf16.f32 {%0, %1, %2, %3}, {%4, %5, %6, %7}, {%8, %9}, {%0, %1, %2, %3};"
               : "+f"(d[0]), "+f"(d[1]), "+f"(d[2]), "+f"(d[3]) : "r"(a0), "r"(a1), "r"(a2), "r"(a3), "r"(b0), "r"(b1));
}
__device__ __forceinline__ void spin_cycles(int n) {
  const int t0 = (int)clock();
#pragma unroll 1
  while ((int)clock() - t0 < n) {}
}
__device__ __forceinline__ uint32_t pack_bf16(float lo, float hi) {
  uint32_t r; asm("cvt.rn.bf16x2.f32 %0, %1, %2;" : "=r"(r) : "f"(hi), "f"(lo)); return r;
}
__device__ __forceinline__ float bf_lo(uint32_t v) { return __uint_as_float(v << 16); }
__device__ __forceinline__ float bf_hi(uint32_t v) { return __uint_as_float(v & 0xffff0000u); }
__device__ __forceinline__ float rbf(float x) { return __bfloat162float(__float2bfloat16_rn(x)); }
__device__ __forceinline__ float ex2(float x) { float y; asm("ex2.approx.ftz.f32 %0, %1;" : "=f"(y) : "f"(x)); return y; }
__device__ __forceinline__ float rcp(float x) { float y; asm("rcp.approx.ftz.f32 %0, %1;" : "=f"(y) : "f"(x)); return y; }
__device__ __forceinline__ uint32_t shl_clamp(uint32_t v, uint32_t n) {
  uint32_t r; asm("shl.b32 %0, %1, %2;" : "=r"(r) : "r"(v), "r"(n)); return r;
}
__device__ __forceinline__ float warp_sum(float v) {
#pragma unroll
  for (int o = 16; o > 0; o >>= 1) v += __shfl_xor_sync(0xffffffffu, v, o);
  return v;
}
__device__ __forceinline__ float ln_inv(float var) {
  float r;
  asm("sqrt.approx.ftz.f32 %0, %1;" : "=f"(r) : "f"(rbf(rbf(var) + LN_EPS)));
  asm("rcp.approx.ftz.f32 %0, %1;" : "=f"(r) : "f"(rbf(r)));
  return r;
}
__device__ __forceinline__ uint32_t ln_pair(uint32_t x, uint32_t mean2, float inv) {
  const uint32_t d = hsub_bf2(x, mean2);
  return pack_bf16(bf_lo(d) * inv, bf_hi(d) * inv);
}
__device__ __forceinline__ uint32_t add_ln_pair(uint32_t x, uint32_t mean2, float inv) { return hadd_bf2(x, ln_pair(x, mean2, inv)); }
__device__ __forceinline__ uint32_t router_key(float r_bf, int row) {
  uint32_t u = __float_as_uint(r_bf);
  u = (u & 0x80000000u) ? ~u : (u | 0x80000000u);
  return (u & 0xFFFF0000u) | 0x8000u | (uint32_t)(SEQ - 1 - row);
}

template <uint32_t HA = 0x40000040u, uint32_t HB = 0x40000040u>
__device__ __forceinline__ void wg_ss192t(float* d, uint32_t da, uint32_t db, int scale_d) {
  asm volatile("{\n.reg .pred p;\n.reg .b64 dA, dB;\nmov.b64 dA, {%96, %99};\nmov.b64 dB, {%97, %100};\nsetp.ne.b32 p, %98, 0;\n"
    "wgmma.mma_async.sync.aligned.m64n192k16.f32.bf16.bf16 "
    "{%0, %1, %2, %3, %4, %5, %6, %7, %8, %9, %10, %11, %12, %13, %14, %15, "
    "%16, %17, %18, %19, %20, %21, %22, %23, %24, %25, %26, %27, %28, %29, %30, %31, "
    "%32, %33, %34, %35, %36, %37, %38, %39, %40, %41, %42, %43, %44, %45, %46, %47, "
    "%48, %49, %50, %51, %52, %53, %54, %55, %56, %57, %58, %59, %60, %61, %62, %63, "
    "%64, %65, %66, %67, %68, %69, %70, %71, %72, %73, %74, %75, %76, %77, %78, %79, "
    "%80, %81, %82, %83, %84, %85, %86, %87, %88, %89, %90, %91, %92, %93, %94, %95}, "
    "dA, dB, p, 1, 1, 0, 1;\n}\n"
    : "+f"(d[0]), "+f"(d[1]), "+f"(d[2]), "+f"(d[3]), "+f"(d[4]), "+f"(d[5]), "+f"(d[6]), "+f"(d[7]),
      "+f"(d[8]), "+f"(d[9]), "+f"(d[10]), "+f"(d[11]), "+f"(d[12]), "+f"(d[13]), "+f"(d[14]), "+f"(d[15]),
      "+f"(d[16]), "+f"(d[17]), "+f"(d[18]), "+f"(d[19]), "+f"(d[20]), "+f"(d[21]), "+f"(d[22]), "+f"(d[23]),
      "+f"(d[24]), "+f"(d[25]), "+f"(d[26]), "+f"(d[27]), "+f"(d[28]), "+f"(d[29]), "+f"(d[30]), "+f"(d[31]),
      "+f"(d[32]), "+f"(d[33]), "+f"(d[34]), "+f"(d[35]), "+f"(d[36]), "+f"(d[37]), "+f"(d[38]), "+f"(d[39]),
      "+f"(d[40]), "+f"(d[41]), "+f"(d[42]), "+f"(d[43]), "+f"(d[44]), "+f"(d[45]), "+f"(d[46]), "+f"(d[47]),
      "+f"(d[48]), "+f"(d[49]), "+f"(d[50]), "+f"(d[51]), "+f"(d[52]), "+f"(d[53]), "+f"(d[54]), "+f"(d[55]),
      "+f"(d[56]), "+f"(d[57]), "+f"(d[58]), "+f"(d[59]), "+f"(d[60]), "+f"(d[61]), "+f"(d[62]), "+f"(d[63]),
      "+f"(d[64]), "+f"(d[65]), "+f"(d[66]), "+f"(d[67]), "+f"(d[68]), "+f"(d[69]), "+f"(d[70]), "+f"(d[71]),
      "+f"(d[72]), "+f"(d[73]), "+f"(d[74]), "+f"(d[75]), "+f"(d[76]), "+f"(d[77]), "+f"(d[78]), "+f"(d[79]),
      "+f"(d[80]), "+f"(d[81]), "+f"(d[82]), "+f"(d[83]), "+f"(d[84]), "+f"(d[85]), "+f"(d[86]), "+f"(d[87]),
      "+f"(d[88]), "+f"(d[89]), "+f"(d[90]), "+f"(d[91]), "+f"(d[92]), "+f"(d[93]), "+f"(d[94]), "+f"(d[95])
    : "r"(da), "r"(db), "r"(scale_d), "n"(HA), "n"(HB));
}
template <uint32_t HA = 0x40000040u, uint32_t HB = 0x40000040u>
__device__ __forceinline__ void wg_ss192t_z(float* d, uint32_t da, uint32_t db) {
  asm volatile("{\n.reg .pred p;\n.reg .b64 dA, dB;\nmov.b64 dA, {%96, %98};\nmov.b64 dB, {%97, %99};\nsetp.ne.b32 p, 0, 0;\n"
    "wgmma.mma_async.sync.aligned.m64n192k16.f32.bf16.bf16 "
    "{%0, %1, %2, %3, %4, %5, %6, %7, %8, %9, %10, %11, %12, %13, %14, %15, "
    "%16, %17, %18, %19, %20, %21, %22, %23, %24, %25, %26, %27, %28, %29, %30, %31, "
    "%32, %33, %34, %35, %36, %37, %38, %39, %40, %41, %42, %43, %44, %45, %46, %47, "
    "%48, %49, %50, %51, %52, %53, %54, %55, %56, %57, %58, %59, %60, %61, %62, %63, "
    "%64, %65, %66, %67, %68, %69, %70, %71, %72, %73, %74, %75, %76, %77, %78, %79, "
    "%80, %81, %82, %83, %84, %85, %86, %87, %88, %89, %90, %91, %92, %93, %94, %95}, "
    "dA, dB, p, 1, 1, 0, 1;\n}\n"
    : "=f"(d[0]), "=f"(d[1]), "=f"(d[2]), "=f"(d[3]), "=f"(d[4]), "=f"(d[5]), "=f"(d[6]), "=f"(d[7]),
      "=f"(d[8]), "=f"(d[9]), "=f"(d[10]), "=f"(d[11]), "=f"(d[12]), "=f"(d[13]), "=f"(d[14]), "=f"(d[15]),
      "=f"(d[16]), "=f"(d[17]), "=f"(d[18]), "=f"(d[19]), "=f"(d[20]), "=f"(d[21]), "=f"(d[22]), "=f"(d[23]),
      "=f"(d[24]), "=f"(d[25]), "=f"(d[26]), "=f"(d[27]), "=f"(d[28]), "=f"(d[29]), "=f"(d[30]), "=f"(d[31]),
      "=f"(d[32]), "=f"(d[33]), "=f"(d[34]), "=f"(d[35]), "=f"(d[36]), "=f"(d[37]), "=f"(d[38]), "=f"(d[39]),
      "=f"(d[40]), "=f"(d[41]), "=f"(d[42]), "=f"(d[43]), "=f"(d[44]), "=f"(d[45]), "=f"(d[46]), "=f"(d[47]),
      "=f"(d[48]), "=f"(d[49]), "=f"(d[50]), "=f"(d[51]), "=f"(d[52]), "=f"(d[53]), "=f"(d[54]), "=f"(d[55]),
      "=f"(d[56]), "=f"(d[57]), "=f"(d[58]), "=f"(d[59]), "=f"(d[60]), "=f"(d[61]), "=f"(d[62]), "=f"(d[63]),
      "=f"(d[64]), "=f"(d[65]), "=f"(d[66]), "=f"(d[67]), "=f"(d[68]), "=f"(d[69]), "=f"(d[70]), "=f"(d[71]),
      "=f"(d[72]), "=f"(d[73]), "=f"(d[74]), "=f"(d[75]), "=f"(d[76]), "=f"(d[77]), "=f"(d[78]), "=f"(d[79]),
      "=f"(d[80]), "=f"(d[81]), "=f"(d[82]), "=f"(d[83]), "=f"(d[84]), "=f"(d[85]), "=f"(d[86]), "=f"(d[87]),
      "=f"(d[88]), "=f"(d[89]), "=f"(d[90]), "=f"(d[91]), "=f"(d[92]), "=f"(d[93]), "=f"(d[94]), "=f"(d[95])
    : "r"(da), "r"(db), "n"(HA), "n"(HB));
}
template <uint32_t HA = 0x40000040u, uint32_t HB = 0x40000040u>
__device__ __forceinline__ void wg_ss128t(float* d, uint32_t da, uint32_t db, int scale_d) {
  asm volatile("{\n.reg .pred p;\n.reg .b64 dA, dB;\nmov.b64 dA, {%64, %67};\nmov.b64 dB, {%65, %68};\nsetp.ne.b32 p, %66, 0;\n"
    "wgmma.mma_async.sync.aligned.m64n128k16.f32.bf16.bf16 "
    "{%0, %1, %2, %3, %4, %5, %6, %7, %8, %9, %10, %11, %12, %13, %14, %15, "
    "%16, %17, %18, %19, %20, %21, %22, %23, %24, %25, %26, %27, %28, %29, %30, %31, "
    "%32, %33, %34, %35, %36, %37, %38, %39, %40, %41, %42, %43, %44, %45, %46, %47, "
    "%48, %49, %50, %51, %52, %53, %54, %55, %56, %57, %58, %59, %60, %61, %62, %63}, "
    "dA, dB, p, 1, 1, 0, 1;\n}\n"
    : "+f"(d[0]), "+f"(d[1]), "+f"(d[2]), "+f"(d[3]), "+f"(d[4]), "+f"(d[5]), "+f"(d[6]), "+f"(d[7]),
      "+f"(d[8]), "+f"(d[9]), "+f"(d[10]), "+f"(d[11]), "+f"(d[12]), "+f"(d[13]), "+f"(d[14]), "+f"(d[15]),
      "+f"(d[16]), "+f"(d[17]), "+f"(d[18]), "+f"(d[19]), "+f"(d[20]), "+f"(d[21]), "+f"(d[22]), "+f"(d[23]),
      "+f"(d[24]), "+f"(d[25]), "+f"(d[26]), "+f"(d[27]), "+f"(d[28]), "+f"(d[29]), "+f"(d[30]), "+f"(d[31]),
      "+f"(d[32]), "+f"(d[33]), "+f"(d[34]), "+f"(d[35]), "+f"(d[36]), "+f"(d[37]), "+f"(d[38]), "+f"(d[39]),
      "+f"(d[40]), "+f"(d[41]), "+f"(d[42]), "+f"(d[43]), "+f"(d[44]), "+f"(d[45]), "+f"(d[46]), "+f"(d[47]),
      "+f"(d[48]), "+f"(d[49]), "+f"(d[50]), "+f"(d[51]), "+f"(d[52]), "+f"(d[53]), "+f"(d[54]), "+f"(d[55]),
      "+f"(d[56]), "+f"(d[57]), "+f"(d[58]), "+f"(d[59]), "+f"(d[60]), "+f"(d[61]), "+f"(d[62]), "+f"(d[63])
    : "r"(da), "r"(db), "r"(scale_d), "n"(HA), "n"(HB));
}
template <uint32_t HB = 0x40000040u>
__device__ __forceinline__ void wg_rs64(float* d, uint32_t a0, uint32_t a1, uint32_t a2, uint32_t a3, uint32_t db, int scale_d) {
  asm volatile("{\n.reg .pred p;\n.reg .b64 dB;\nmov.b64 dB, {%36, %38};\nsetp.ne.b32 p, %37, 0;\n"
    "wgmma.mma_async.sync.aligned.m64n64k16.f32.bf16.bf16 "
    "{%0, %1, %2, %3, %4, %5, %6, %7, %8, %9, %10, %11, %12, %13, %14, %15, "
    "%16, %17, %18, %19, %20, %21, %22, %23, %24, %25, %26, %27, %28, %29, %30, %31}, "
    "{%32, %33, %34, %35}, dB, p, 1, 1, 0;\n}\n"
    : "+f"(d[0]), "+f"(d[1]), "+f"(d[2]), "+f"(d[3]), "+f"(d[4]), "+f"(d[5]), "+f"(d[6]), "+f"(d[7]),
      "+f"(d[8]), "+f"(d[9]), "+f"(d[10]), "+f"(d[11]), "+f"(d[12]), "+f"(d[13]), "+f"(d[14]), "+f"(d[15]),
      "+f"(d[16]), "+f"(d[17]), "+f"(d[18]), "+f"(d[19]), "+f"(d[20]), "+f"(d[21]), "+f"(d[22]), "+f"(d[23]),
      "+f"(d[24]), "+f"(d[25]), "+f"(d[26]), "+f"(d[27]), "+f"(d[28]), "+f"(d[29]), "+f"(d[30]), "+f"(d[31])
    : "r"(a0), "r"(a1), "r"(a2), "r"(a3), "r"(db), "r"(scale_d), "n"(HB));
}
template <uint32_t HB = 0x40000040u>
__device__ __forceinline__ void wg_rs64_z(float* d, uint32_t a0, uint32_t a1, uint32_t a2, uint32_t a3, uint32_t db) {
  asm volatile("{\n.reg .pred p;\n.reg .b64 dB;\nmov.b64 dB, {%36, %37};\nsetp.ne.b32 p, 0, 0;\n"
    "wgmma.mma_async.sync.aligned.m64n64k16.f32.bf16.bf16 "
    "{%0, %1, %2, %3, %4, %5, %6, %7, %8, %9, %10, %11, %12, %13, %14, %15, "
    "%16, %17, %18, %19, %20, %21, %22, %23, %24, %25, %26, %27, %28, %29, %30, %31}, "
    "{%32, %33, %34, %35}, dB, p, 1, 1, 0;\n}\n"
    : "=f"(d[0]), "=f"(d[1]), "=f"(d[2]), "=f"(d[3]), "=f"(d[4]), "=f"(d[5]), "=f"(d[6]), "=f"(d[7]),
      "=f"(d[8]), "=f"(d[9]), "=f"(d[10]), "=f"(d[11]), "=f"(d[12]), "=f"(d[13]), "=f"(d[14]), "=f"(d[15]),
      "=f"(d[16]), "=f"(d[17]), "=f"(d[18]), "=f"(d[19]), "=f"(d[20]), "=f"(d[21]), "=f"(d[22]), "=f"(d[23]),
      "=f"(d[24]), "=f"(d[25]), "=f"(d[26]), "=f"(d[27]), "=f"(d[28]), "=f"(d[29]), "=f"(d[30]), "=f"(d[31])
    : "r"(a0), "r"(a1), "r"(a2), "r"(a3), "r"(db), "n"(HB));
}
template <uint32_t HB = 0x40000040u>
__device__ __forceinline__ void wg_rs32(float* d, uint32_t a0, uint32_t a1, uint32_t a2, uint32_t a3, uint32_t db, int scale_d) {
  asm volatile("{\n.reg .pred p;\n.reg .b64 dB;\nmov.b64 dB, {%20, %22};\nsetp.ne.b32 p, %21, 0;\n"
    "wgmma.mma_async.sync.aligned.m64n32k16.f32.bf16.bf16 "
    "{%0, %1, %2, %3, %4, %5, %6, %7, %8, %9, %10, %11, %12, %13, %14, %15}, "
    "{%16, %17, %18, %19}, dB, p, 1, 1, 0;\n}\n"
    : "+f"(d[0]), "+f"(d[1]), "+f"(d[2]), "+f"(d[3]), "+f"(d[4]), "+f"(d[5]), "+f"(d[6]), "+f"(d[7]),
      "+f"(d[8]), "+f"(d[9]), "+f"(d[10]), "+f"(d[11]), "+f"(d[12]), "+f"(d[13]), "+f"(d[14]), "+f"(d[15])
    : "r"(a0), "r"(a1), "r"(a2), "r"(a3), "r"(db), "r"(scale_d), "n"(HB));
}
template <uint32_t HB = 0x40000040u>
__device__ __forceinline__ void wg_rs32_z(float* d, uint32_t a0, uint32_t a1, uint32_t a2, uint32_t a3, uint32_t db) {
  asm volatile("{\n.reg .pred p;\n.reg .b64 dB;\nmov.b64 dB, {%20, %21};\nsetp.ne.b32 p, 0, 0;\n"
    "wgmma.mma_async.sync.aligned.m64n32k16.f32.bf16.bf16 "
    "{%0, %1, %2, %3, %4, %5, %6, %7, %8, %9, %10, %11, %12, %13, %14, %15}, "
    "{%16, %17, %18, %19}, dB, p, 1, 1, 0;\n}\n"
    : "=f"(d[0]), "=f"(d[1]), "=f"(d[2]), "=f"(d[3]), "=f"(d[4]), "=f"(d[5]), "=f"(d[6]), "=f"(d[7]),
      "=f"(d[8]), "=f"(d[9]), "=f"(d[10]), "=f"(d[11]), "=f"(d[12]), "=f"(d[13]), "=f"(d[14]), "=f"(d[15])
    : "r"(a0), "r"(a1), "r"(a2), "r"(a3), "r"(db), "n"(HB));
}
template <uint32_t HB = 0x40000040u>
__device__ __forceinline__ void wg_rs40t(float* d, uint32_t a0, uint32_t a1, uint32_t a2, uint32_t a3, uint32_t db, int scale_d) {
  asm volatile("{\n.reg .pred p;\n.reg .b64 dB;\nmov.b64 dB, {%24, %26};\nsetp.ne.b32 p, %25, 0;\n"
    "wgmma.mma_async.sync.aligned.m64n40k16.f32.bf16.bf16 "
    "{%0, %1, %2, %3, %4, %5, %6, %7, %8, %9, %10, %11, %12, %13, %14, %15, "
    "%16, %17, %18, %19}, "
    "{%20, %21, %22, %23}, dB, p, 1, 1, 1;\n}\n"
    : "+f"(d[0]), "+f"(d[1]), "+f"(d[2]), "+f"(d[3]), "+f"(d[4]), "+f"(d[5]), "+f"(d[6]), "+f"(d[7]),
      "+f"(d[8]), "+f"(d[9]), "+f"(d[10]), "+f"(d[11]), "+f"(d[12]), "+f"(d[13]), "+f"(d[14]), "+f"(d[15]),
      "+f"(d[16]), "+f"(d[17]), "+f"(d[18]), "+f"(d[19])
    : "r"(a0), "r"(a1), "r"(a2), "r"(a3), "r"(db), "r"(scale_d), "n"(HB));
}
template <uint32_t HB = 0x40000040u>
__device__ __forceinline__ void wg_rs40t_z(float* d, uint32_t a0, uint32_t a1, uint32_t a2, uint32_t a3, uint32_t db) {
  asm volatile("{\n.reg .pred p;\n.reg .b64 dB;\nmov.b64 dB, {%24, %25};\nsetp.ne.b32 p, 0, 0;\n"
    "wgmma.mma_async.sync.aligned.m64n40k16.f32.bf16.bf16 "
    "{%0, %1, %2, %3, %4, %5, %6, %7, %8, %9, %10, %11, %12, %13, %14, %15, "
    "%16, %17, %18, %19}, "
    "{%20, %21, %22, %23}, dB, p, 1, 1, 1;\n}\n"
    : "=f"(d[0]), "=f"(d[1]), "=f"(d[2]), "=f"(d[3]), "=f"(d[4]), "=f"(d[5]), "=f"(d[6]), "=f"(d[7]),
      "=f"(d[8]), "=f"(d[9]), "=f"(d[10]), "=f"(d[11]), "=f"(d[12]), "=f"(d[13]), "=f"(d[14]), "=f"(d[15]),
      "=f"(d[16]), "=f"(d[17]), "=f"(d[18]), "=f"(d[19])
    : "r"(a0), "r"(a1), "r"(a2), "r"(a3), "r"(db), "n"(HB));
}

constexpr uint32_t SOFF = 1024;
constexpr int STG = 57344, SL_W = 32768, SL_HD = 12288, SL_F = 3 * STG, X_ST = 131072;
__host__ __device__ constexpr int kv_off(int h, int b) { return 16384 + h * 81920 + (b ^ (6 * h)) * 8192; }
__host__ __device__ constexpr int qo_off(int h, int qb) { return (qb >> 1) * 81920 + h * 8192 + (qb & 1) * 4096; }
__host__ __device__ constexpr int wo_off(int st) { return 16384 + st * 32768 + (st >> 1) * 16384; }
constexpr int OFF_ONES = 4 * STG;
constexpr int OFF_PATCH = OFF_ONES + 1024;
constexpr int OFF_CS = OFF_PATCH + 768;
constexpr int OFF_BAR = OFF_CS + 768;
constexpr int OFF_MISC = OFF_BAR + 416;
constexpr int SMEM_BYTES = OFF_MISC + 96;
enum { B_FULL = 0, B_EMPTY = 6, B_HALO = 12, B_CS = 15, B_KVREADY, B_QDONE = B_KVREADY + 2, B_QREADY, B_OST, B_ADONE = B_OST + 2,
       B_QFREE, B_WS, B_WFULL, B_WEMPTY = B_WFULL + 4, B_GU = B_WEMPTY + 4, B_RES = B_GU + 2, B_DN,
       B_HX = B_DN + 2, B_RST, B_E23, B_UNIT, B_COUNT = B_UNIT + 8 };
static_assert(B_COUNT <= 52, "barrier area");
__host__ __device__ constexpr int bar_count(int i) {
  return i >= B_EMPTY && i < B_HALO ? 17 : i == B_CS ? 5 : i == B_QFREE ? 16
       : i == B_KVREADY || i == B_KVREADY + 1 || i == B_QREADY ? 8 : i == B_E23 ? 9 : i == B_ADONE ? 32 : i == B_OST ? 2 : i >= B_UNIT ? 4
       : i == B_QDONE || (i >= B_WEMPTY && i < B_GU) ? 16 : i == B_RST ? 4 : i == B_RES ? 2 : 1;
}
enum { M_KEY = 0, M_MEAN, M_INV, M_WSUM, M_TAG, M_SEL0, M_PMEAN, M_PINV, M_XQ = 8, M_KEYS = 12, M_PROG = 20 };
constexpr int FFN_PIECE = 14336;
constexpr int T_XS = 163840, T_HP = T_XS + 1024;
constexpr float LSUM_MIN = 5.421010862427522e-20f, LSUM_MAX = 1.8446744073709552e19f;
constexpr float SM_C = 0.17677669529663687f * 1.4426950408889634f;
constexpr uint32_t VSTEP = 64u - (64u << 16);
constexpr int DELAY_P = 600, DELAY_S = 2000, DELAY_Y = 500, X_STAGGER = 500;
constexpr int GU_PACE = 2000, GU_PACE1 = 1700, GUB_PACE = 900, WS_PACE = 500;
constexpr int RES_K = 4;

struct Params {
  CUtensorMap mapA[2], mapW, mapWo, mapRes[2], mapXst[2], mapG, mapU, mapD, mapWs;
  const bf16 *w_r, *w_d;
  bf16* out;
  int role[128];
};

template <int N> __device__ __forceinline__ void exp_pack(const float* s, uint32_t* p) {
#pragma unroll
  for (int b = 0; b < N; b++) {
    p[2 * b] = pack_bf16(ex2(s[4 * b]), ex2(s[4 * b + 1]));
    p[2 * b + 1] = pack_bf16(ex2(s[4 * b + 2]), ex2(s[4 * b + 3]));
  }
}
template <int KIND> __device__ __forceinline__ void edge16(const float* sd, const float* st, uint32_t* pd, uint32_t* pt, int dl, uint32_t mt) {
  if (KIND == 0) { exp_pack<2>(sd, pd); pt[0] = pt[1] = pt[2] = pt[3] = 0; }
  else if (KIND == 1) { exp_pack<2>(st, pt); pd[0] = pd[1] = pd[2] = pd[3] = 0; }
  else {
    const uint32_t a = pack_bf16(ex2(dl >= 0 ? sd[0] : st[0]), ex2(dl >= 1 ? sd[1] : st[1]));
    const uint32_t c = pack_bf16(ex2(dl >= 0 ? sd[6] : st[6]), ex2(dl >= 1 ? sd[7] : st[7]));
    pd[0] = a & ~mt; pt[0] = a & mt; pd[3] = c & ~mt; pt[3] = c & mt;
    pd[1] = pack_bf16(ex2(sd[2]), ex2(sd[3])); pt[1] = 0;
    pt[2] = pack_bf16(ex2(st[4]), ex2(st[5])); pd[2] = 0;
  }
}
__device__ __forceinline__ void edge32(const float* sd, const float* st, uint32_t* pd, uint32_t* pt, int rel, int dl, uint32_t mt) {
  if (rel > 1) { edge16<0>(sd, st, pd, pt, dl, mt); edge16<0>(sd + 8, st + 8, pd + 4, pt + 4, dl, mt); }
  else if (rel == 1) { edge16<0>(sd, st, pd, pt, dl, mt); edge16<2>(sd + 8, st + 8, pd + 4, pt + 4, dl, mt); }
  else if (rel == 0) { edge16<2>(sd, st, pd, pt, dl, mt); edge16<1>(sd + 8, st + 8, pd + 4, pt + 4, dl, mt); }
  else { edge16<1>(sd, st, pd, pt, dl, mt); edge16<1>(sd + 8, st + 8, pd + 4, pt + 4, dl, mt); }
}
__device__ __forceinline__ void qk64(float* s, const uint32_t* qf, uint32_t kd) {
  wg_rs64_z<H64>(s, qf[0], qf[1], qf[2], qf[3], kd);
  wg_rs64<H64>(s, qf[4], qf[5], qf[6], qf[7], kd + 2, 1);
}
__device__ __forceinline__ void qk32x2(float* a, float* b, const uint32_t* qf, uint32_t ka, uint32_t kb) {
  wg_rs32_z<H64>(a, qf[0], qf[1], qf[2], qf[3], ka); wg_rs32_z<H64>(b, qf[0], qf[1], qf[2], qf[3], kb);
  wg_rs32<H64>(a, qf[4], qf[5], qf[6], qf[7], ka + 2, 1); wg_rs32<H64>(b, qf[4], qf[5], qf[6], qf[7], kb + 2, 1);
}
__device__ __forceinline__ void pv32(float* o, const uint32_t* p, uint32_t vd) {
  wg_rs40t<H64>(o, p[0], p[1], p[2], p[3], vd, 1);
  wg_rs40t<H64>(o, p[4], p[5], p[6], p[7], vd + VSTEP, 1);
}

__device__ __forceinline__ void fma8(float* d, uint4 w, float x) {
  d[0] += x * bf_lo(w.x); d[1] += x * bf_hi(w.x); d[2] += x * bf_lo(w.y); d[3] += x * bf_hi(w.y);
  d[4] += x * bf_lo(w.z); d[5] += x * bf_hi(w.z); d[6] += x * bf_lo(w.w); d[7] += x * bf_hi(w.w);
}

__device__ __forceinline__ int fresh_tid() { int r; asm volatile("mov.u32 %0, %%tid.x;" : "=r"(r)); return r; }
__device__ __forceinline__ int fresh_bid() { int r; asm volatile("mov.u32 %0, %%ctaid.x;" : "=r"(r)); return r; }
#define PHASE_IDS                                                                                                              \
  const uint32_t sbase = smem_u32(smem);                                                                                       \
  const int tid = fresh_tid(), bid = P.role[fresh_bid()];                                                                      \
  const int warp = __shfl_sync(0xffffffffu, tid >> 5, 0), lane = tid & 31;                                                     \
  const int rank = bid & 1, rb = bid & 7, hp = bid >> 3, cl = (rb >> 1) * 16 + hp;                  \
  const int mb = 2 * rb + (hp >> 3), nb = hp & 7;                                            \
  const int wg = warp >> 2, wi = warp & 3, g = lane >> 2, q = lane & 3;                                                        \
  const int mi = lane >> 3, srow = wi * 16 + (mi & 1) * 8 + (lane & 7);      \
  auto bar = [&](int i) { return sbase + OFF_BAR + 8 * i; };                                                                   \
  volatile uint32_t* s_misc = (volatile uint32_t*)(smem + OFF_MISC);                                                           \
  auto load_w = [&](int s, int kt) {                           \
    mbar_expect_tx(bar(B_FULL + s), (s & 1) ? SL_HD : SL_HD + 32768);                        \
    tma_load3_mc(sbase + (s >> 1) * STG + SL_W + (s & 1) * SL_HD + rank * 6144, &P.mapW, hp * 64, kt * 32 + rank * 16, 0, bar(B_FULL + s));              \
  };                                                                                                                           \
  auto load_a = [&](int s, int kt, int layer) { tma_load2(sbase + (s >> 1) * STG, &P.mapA[layer], kt * 32, rb * 256, bar(B_FULL + s)); }; \
  auto load_wo = [&](int k) {                                                 \
    mbar_expect_tx(bar(B_WFULL + (k & 3)), 32768);                                                                             \
    tma_load3_mc(sbase + wo_off(k & 3) + 16384 + rank * 8192, &P.mapWo, nb * 128 + rank * 64, (k >> 3) * 32, (k & 7) * 2, bar(B_WFULL + (k & 3))); \
  };                                                                                                                           \
  auto load_o = [&](int k) {                                                            \
    bulk_load_h(sbase + wo_off(k & 3), g_o + (size_t)(mb * 16 + k) * 16384, 16384, bar(B_WFULL + (k & 3)), policy_evict_first());                    \
  };                                                                                                                           \
  auto export_halo = [&](int p) {                                                        \
    _Pragma("unroll 1")                                                                                                        \
    for (int h = 0; h < 2; h++) {                                                                                              \
      if (rank == 0) bulk_push(mapa(sbase + kv_off(h, 2 - 2 * p), 1), sbase + kv_off(h, 6 - 2 * p), 16384, mapa(bar(B_HALO + (p ? 2 : h)), 1)); \
      else if (rb < 7) bulk_store(g_kv + (size_t)(cl * 4 + p * 2 + h) * 16384, sbase + kv_off(h, 6 - 2 * p), 16384);           \
    }                                                                                                                          \
    bulk_commit();                                                                                                             \
  };                                                                                                                           \
  auto load_res = [&](int half, int layer) {      \
    mbar_expect_tx(bar(B_RES), 16384);                                                                                         \
    tma_load2_h(sbase + qo_off(half, 0), &P.mapRes[layer], nb * 128 + half * 64, mb * 128, bar(B_RES), policy_evict_first());  \
    tma_load2_h(sbase + qo_off(half, 2), &P.mapRes[layer], nb * 128 + half * 64, mb * 128 + 64, bar(B_RES), policy_evict_first()); \
  };                                                                                                                           \
  auto store_tile = [&](int layer, int skip, bool wait) {                                           \
    _Pragma("unroll 1")                                                                                                        \
    for (int j = 0; j < 4; j++)                                                                                                \
      if ((j & 1) != skip) tma_store(&P.mapXst[layer], sbase + X_ST + (j & 1) * 16384 + (j >> 1) * 8192, nb * 128 + (j >> 1) * 64, mb * 128 + (j & 1) * 64); \
    bulk_commit();                                                                                                             \
    if (wait) bulk_wait_all();                                                                                                 \
  };                                                                                                                           \
  auto load_ws = [&](int pace) {                                    \
    mbar_expect_tx(bar(B_WS), 4 * SL_HD);                                                                                      \
    _Pragma("unroll 1")                                                                                                        \
    for (int j = 0; j < 4; j++) {                                                                                              \
      tma_load3(sbase + SL_F + j * SL_HD, &P.mapWs, hp * 64, rb * 128 + j * 32, 0, bar(B_WS));                                 \
      if (pace) spin_cycles(pace);                                                                                             \
    }                                                                                                                          \
  };                                                                                                                           \
  auto load_gu = [&](int half, int pace, int j0, int j1) {                             \
    if (j0 == 0) mbar_expect_tx(bar(B_GU + half), 4 * FFN_PIECE);                                                                         \
    _Pragma("unroll 1")                                                                                                        \
    for (int j = j0; j < j1; j++) {                                                                                            \
      tma_load2_h(sbase + SL_F + j * FFN_PIECE, &P.mapG + (j >> 1), cl * 56, rank * 512 + half * 256 + (j & 1) * 128, bar(B_GU + half), policy_evict_first()); \
      if (j < j1 - 1) spin_cycles(pace);                                                                                       \
    }                                                                                                                          \
  };                                                                                                                           \
  auto fetch_gu = [&](uint32_t* a, int ks, int ct) {                 \
    ldsm_x4_t(sbase + SL_F + (mi & 1) * 2 * FFN_PIECE + (ks * 16 + (mi >> 1) * 8 + (lane & 7)) * 112 + ct * 16, a[0], a[1], a[2], a[3]); \
  };                                                                                                                           \
  auto send_gu = [&](float gate, float up, int ct, int part) {        \
    const int u = 8 * ct + g, own = u >= 28;                                                                                   \
    if (q == 0) st_async2(mapa(sbase + T_HP + ((rank * 5 + part) * 28 + u - 28 * own) * 8, own), gate, up, mapa(bar(B_HX), own)); \
  };                                                                                                                           \
  auto hidden = [&]() {                                     \
    const float2* hpart = (const float2*)(smem + T_HP) + min(lane, 27);                                                        \
    float gs[2] = {0.f, 0.f}, us[2] = {0.f, 0.f};                                                                              \
    _Pragma("unroll")                                                                                                          \
    for (int j = 0; j < 10; j++) { const float2 v = hpart[j * 28]; gs[j & 1] += v.x; us[j & 1] += v.y; }                       \
    const float gb = rbf(gs[0] + gs[1]), ub = rbf(us[0] + us[1]);                                                              \
    return lane < 28 ? rbf(__fdividef(gb, 1.f + __expf(-gb))) * ub : 0.f;                                                      \
  };                                                                                                                           \
  (void)load_wo; (void)load_o; (void)export_halo; (void)load_res; (void)store_tile; (void)fetch_gu; (void)load_ws; (void)load_gu; (void)send_gu; (void)hidden; (void)cl; (void)mb; (void)nb; (void)wg; (void)g; (void)q; (void)srow; (void)s_misc; (void)load_w; (void)load_a;

__global__ void __launch_bounds__(512, 1) mega_kernel(const __grid_constant__ Params P) {
  extern __shared__ __align__(1024) uint8_t smem[];
  {
    PHASE_IDS
    if (warp == 0) {
      if (lane == 0) {
        prefetch_tmap(&P.mapA[0]); prefetch_tmap(&P.mapW);
#pragma unroll
        for (int i = 0; i < 6; i++) mbar_init(bar(B_FULL + i), 1);
        asm volatile("fence.mbarrier_init.release.cluster;" ::: "memory");
      }
      __syncwarp();
      mbar_expect_tx(bar(B_FULL), SL_HD + 32768);
      tma_load3(sbase + SL_W, &P.mapW, hp * 64, 0, 0, bar(B_FULL));
      tma_load3(sbase + SL_W + 6144, &P.mapW, hp * 64, 16, 0, bar(B_FULL));
      load_a(0, 0, 0);
    } else if (tid == 32) {
#pragma unroll
      for (int i = 6; i < B_COUNT; i++) mbar_init(bar(i), bar_count(i));
      asm volatile("fence.mbarrier_init.release.cluster;" ::: "memory");
    } else if (warp == 8) {
      ((uint4*)(smem + OFF_ONES))[lane] = make_uint4(0x3F803F80u, 0x3F803F80u, 0x3F803F80u, 0x3F803F80u);
      ((uint4*)(smem + OFF_ONES))[lane + 32] = make_uint4(0x3F803F80u, 0x3F803F80u, 0x3F803F80u, 0x3F803F80u);
    }
    __syncwarp();
    cluster_arrive(); cluster_wait();
    if (warp == 0) {
      PROFL(0, 1);
      load_w(1, 1);
    } else if (tid == 96) {
      if ((sbase & 0x3FFFF) != SOFF) __trap();
    }
    __syncwarp();
  }

  regs_dec<120>();
#pragma unroll 1
  for (unsigned pass_v = 0;;) {
    const unsigned pass = __shfl_sync(0xffffffffu, pass_v, 0);
    if (__shfl_sync(0xffffffffu, fresh_tid() >> 8, 0)) {
      if (pass > 0) {
        const unsigned layer = pass - 1;
        uint32_t xr[32];
        {
          PHASE_IDS
          float acc[64];
#pragma unroll
          for (int i = 0; i < 64; i++) acc[i] = 0.f;
          const uint32_t da0 = dlo(SOFF, 16) + (wg - 2) * 256;
          constexpr uint32_t db0 = dlo(SOFF + 16384, 8192);
#pragma unroll 1
          for (int k4 = 0; k4 < 4; k4++) {
#pragma unroll
            for (int st = 0; st < 4; st++) {
              mbar_wait(bar(B_WFULL + st), k4 & 1);
              wg_fence();
#pragma unroll
              for (int kk = 0; kk < 4; kk++)
                wg_ss128t<H64, H128>(acc, da0 + (wo_off(st) >> 4) + (kk >> 1) * 512 + (kk & 1) * 2, db0 + (wo_off(st) >> 4) + kk * 128, 1);
              wg_commit();
              if (st == 0 && k4 == 0 && warp == 9) PROF(10);
              if (warp == 9) STEPT(16 + k4 * 4 + st);
              wg_wait<1>();
              if (lane < 2 && (st == 0 ? k4 > 0 : (st < 3 || k4 < 3))) mbar_arrive_cluster(bar(B_WEMPTY + ((st + 3) & 3)), lane);
            }
          }
          mbar_wait(bar(B_RES), layer);
          mbar_wait(bar(B_RST), layer);
          const uint32_t zoff = qo_off(0, (wg - 2) * 2);
#pragma unroll
          for (int j = 0; j < 8; j++)
            ldsm_x4(sbase + zoff + srow * 128 + (j >> 2) * 8192 + ((((2 * j + (mi >> 1)) & 7) ^ (srow & 7)) << 4), xr[4 * j], xr[4 * j + 1], xr[4 * j + 2], xr[4 * j + 3]);
          wg_wait<0>();
          fence_regs<64>(acc);
          if (warp == 9) PROF(11);
#pragma unroll
          for (int j = 0; j < 32; j++) xr[j] = hadd_bf2(xr[j], pack_bf16(acc[2 * j], acc[2 * j + 1]));
        }
        PHASE_IDS
        const uint32_t tag = s_misc[M_TAG];
        const int grow = mb * 128 + (warp - 8) * 16 + g;
        {
          float d[6][4];
#pragma unroll
          for (int i = 0; i < 6; i++) d[i][0] = d[i][1] = d[i][2] = d[i][3] = 0.f;
          const uint4* tab = (const uint4*)(smem + OFF_PATCH + (g == 1 ? q * 64 : (g == 0 ? 256 : 320)));
#pragma unroll
          for (int j2 = 0; j2 < 4; j2++) {
            const uint4 w = tab[j2];
#pragma unroll
            for (int jj = 0; jj < 2; jj++) {
              const uint32_t* a = &xr[8 * j2 + 4 * jj];
              mma_16816(d[jj], a[0], a[1], a[2], a[3], jj ? w.z : w.x, jj ? w.w : w.y);
              mma_16816(d[2 + jj], a[0], a[1], a[2], a[3], a[0], a[2]);
              mma_16816(d[4 + jj], a[0], a[1], a[2], a[3], a[1], a[3]);
            }
          }
          const float sq0 = __shfl_sync(0xffffffffu, (g & 1) ? d[2][1] + d[3][1] : d[2][0] + d[3][0], g * 4 + (g >> 1));
          const float sq1 = __shfl_sync(0xffffffffu, (g & 1) ? d[4][3] + d[5][3] : d[4][2] + d[5][2], g * 4 + (g >> 1));
          uint4* dst = &g_part[layer][nb * SEQ + grow];
          if (q == 0) {
            st_relaxed4(dst, make_uint4(__float_as_uint(d[0][0] + d[1][0]), __float_as_uint(sq0), __float_as_uint(d[0][1] + d[1][1]), tag));
            st_relaxed4(dst + 8, make_uint4(__float_as_uint(d[0][2] + d[1][2]), __float_as_uint(sq1), __float_as_uint(d[0][3] + d[1][3]), tag));
          }
        }
        if (warp == 9) PROF(12);
        if (layer == 0 && lane < 2) mbar_arrive_cluster(bar(B_QFREE), lane);
        asm volatile("bar.arrive 6, 320;" ::: "memory");
        const int t_p = (int)clock();
        const uint32_t zrow = sbase + X_ST + (wg - 2) * 16384 + srow * 128;
        named_bar(5, 256);
#pragma unroll
        for (int j = 0; j < 8; j++)
          stsm_x4(zrow + (j >> 2) * 8192 + ((((2 * j + (mi >> 1)) & 7) ^ (srow & 7)) << 4), xr[4 * j], xr[4 * j + 1], xr[4 * j + 2], xr[4 * j + 3]);
        if (layer == 0) {
          fence_async_smem();
          asm volatile("bar.arrive 8, 288;" ::: "memory");
        }
#pragma unroll 1
        while ((int)clock() - t_p < DELAY_P) {}
        {
          const int rr = q >> 1;
          const uint4* src = &g_part[layer][(q & 1) * 4 * SEQ + grow + 8 * rr];
          uint4 pp[4];
          uint32_t spins = 0;
#pragma unroll 1
          do {
#pragma unroll
            for (int j = 0; j < 4; j++) pp[j] = ld_relaxed4(src + j * SEQ);
          } while (!__all_sync(0xffffffffu, pp[0].w == tag && pp[1].w == tag && pp[2].w == tag && pp[3].w == tag) && ++spins < SPIN_LIMIT);
          if (warp == 9) PROF(13);
          float s3[3] = {(__uint_as_float(pp[0].x) + __uint_as_float(pp[1].x)) + (__uint_as_float(pp[2].x) + __uint_as_float(pp[3].x)),
                         (__uint_as_float(pp[0].y) + __uint_as_float(pp[1].y)) + (__uint_as_float(pp[2].y) + __uint_as_float(pp[3].y)),
                         (__uint_as_float(pp[0].z) + __uint_as_float(pp[1].z)) + (__uint_as_float(pp[2].z) + __uint_as_float(pp[3].z))};
#pragma unroll
          for (int c = 0; c < 3; c++) s3[c] += __shfl_xor_sync(0xffffffffu, s3[c], 1);
          const float mu = s3[0] * (1.f / DM), var = fmaxf(fmaf(-mu, mu, s3[1] * (1.f / DM)), 0.f);
          const float mn = rbf(mu), iv = ln_inv(var);
          const uint32_t ky = router_key(rbf((s3[2] - mn * __uint_as_float(s_misc[M_WSUM])) * iv), grow + 8 * rr);
          const uint32_t wbest = __reduce_max_sync(0xffffffffu, ky);
          s_misc[M_KEYS + warp - 8] = wbest;
          named_bar(5, 256);
          if (__reduce_max_sync(0xffffffffu, s_misc[M_KEYS + (lane & 7)]) == wbest) {
            if (nb == 0 && ky == wbest && (q & 1) == 0) st_relaxed4(&g_slot[layer][mb * 8], make_uint4(ky, __float_as_uint(mn), __float_as_uint(iv), tag));
            const int r = ~wbest & 15;
            if ((r & 7) == g) {
#pragma unroll
              for (int j = 0; j < 4; j++) {
                const uint32_t* a = &xr[8 * j];
                st_relaxed4(&g_cand[layer][mb * 128 + nb * 16 + q * 4 + j],
                    r < 8 ? make_uint4(a[0], a[2], a[4], a[6]) : make_uint4(a[1], a[3], a[5], a[7]));
              }
            }
            __syncwarp();
          }
          if (warp == 9) PROF(14);
          if (layer == 0) {
            if ((q & 1) == 0) {
              g_rowln[nb][grow + 8 * rr] = make_float2(mn, iv);
              if (warp - 8 == nb) {
                const float mu2 = mu + (mu - mn) * iv, inv2 = ln_inv(var * (1.f + iv) * (1.f + iv));
                st_relaxed4(&g_rowab[1][grow + 8 * rr], make_uint4(__float_as_uint((1.f + iv) * inv2), __float_as_uint((mn * iv + rbf(mu2)) * inv2), tag, 0));
              }
            }
            __syncwarp();
          } else {
            const uint32_t m2 = pack_bf16(mn, mn);
            uint8_t* row = smem + X_ST + (wg - 2) * 16384 + (q & 1) * 8192 + (wi * 16 + g + 8 * rr) * 128;
#pragma unroll 2
            for (int j = 0; j < 8; j++) {
              uint4* c = (uint4*)(row + (((j + lane) & 7) << 4));
              const uint4 v = *c;
              *c = make_uint4(add_ln_pair(v.x, m2, iv), add_ln_pair(v.y, m2, iv), add_ln_pair(v.z, m2, iv), add_ln_pair(v.w, m2, iv));
            }
            fence_async_smem();
          }
          if (warp == 15) asm volatile("bar.arrive 7, 512;" ::: "memory");
        }
        if (warp < 15) {
          uint32_t gu[64];
          mbar_wait(bar(B_GU + 1), layer);
#pragma unroll
          for (int j = 0; j < 16; j++) fetch_gu(gu + 4 * j, j, warp - 8);
          fence_async_smem();
          float d[4][4] = {};
          named_bar(7, 512);
#pragma unroll
          for (int hf = 0; hf < 2; hf++) {
            uint4 xv[4] = {};
            if (g == 0) {
#pragma unroll
              for (int j = 0; j < 4; j++) xv[j] = ((const uint4*)(smem + T_XS))[32 + hf * 16 + j * 4 + q];
            }
            __syncwarp();
#pragma unroll
            for (int j = 0; j < 4; j++) {
              const uint32_t* a = gu + hf * 32 + j * 8;
              mma_16816(d[(j & 1) * 2], a[0], a[1], a[2], a[3], xv[j].x, xv[j].y);
              mma_16816(d[(j & 1) * 2 + 1], a[4], a[5], a[6], a[7], xv[j].z, xv[j].w);
            }
          }
          send_gu((d[0][0] + d[1][0]) + (d[2][0] + d[3][0]), (d[0][2] + d[1][2]) + (d[2][2] + d[3][2]), warp - 8, 4);
          __syncwarp();
        }
        if (layer == 0) asm volatile("bar.arrive 9, 512;" ::: "memory");
        else {
          uint32_t wd[64];
          mbar_wait(bar(B_DN), layer);
#pragma unroll
          for (int j = 0; j < 16; j++) {
            const uint32_t row = sbase + wo_off(0) + ((warp - 8) * 2 + (j >> 3)) * 3584 + min((j & 1) * 16 + (mi >> 1) * 8 + (lane & 7), 27) * 128;
            ldsm_x4_t(row + ((((j & 6) + (mi & 1)) ^ ((row >> 7) & 7)) << 4), wd[4 * j], wd[4 * j + 1], wd[4 * j + 2], wd[4 * j + 3]);
          }
          fence_regs_u<64>(wd);
          uint32_t hf[4];
          named_bar(10, 288);
          *(uint4*)hf = *(const uint4*)(smem + OFF_PATCH + 256 + q * 16);
          if (warp == 9) PROF(19);
          float y[4][4] = {};
#pragma unroll
          for (int j = 0; j < 16; j++)
            mma_16816(y[j & 3], wd[4 * j], wd[4 * j + 1], wd[4 * j + 2], wd[4 * j + 3], g == j >> 1 ? hf[(j & 1) * 2] : 0u, g == j >> 1 ? hf[(j & 1) * 2 + 1] : 0u);
          {
            float e[4];
#pragma unroll
            for (int c = 0; c < 4; c++) { const int i = (c & 1) * 2 + (c >> 1); e[c] = (y[0][i] + y[1][i]) + (y[2][i] + y[3][i]); }
            const bool b0 = g & 1, b1 = g & 2;
            float t0 = __shfl_xor_sync(0xffffffffu, b0 ? e[0] : e[1], 4), t1 = __shfl_xor_sync(0xffffffffu, b0 ? e[2] : e[3], 4);
            const float f0 = b0 ? t0 : e[0], f1 = b0 ? e[1] : t0, f2 = b0 ? t1 : e[2], f3 = b0 ? e[3] : t1;
            t0 = __shfl_xor_sync(0xffffffffu, b1 ? f0 : f2, 8); t1 = __shfl_xor_sync(0xffffffffu, b1 ? f1 : f3, 8);
            st_relaxed4(&g_ypart[layer][bid * 256 + (warp - 8) * 32 + (q * 4 + (g & 3)) * 2 + (g >> 2)],
                b1 ? make_uint4(__float_as_uint(t0), __float_as_uint(t1), __float_as_uint(f2), __float_as_uint(f3)) : make_uint4(__float_as_uint(f0), __float_as_uint(f1), __float_as_uint(t0), __float_as_uint(t1)));
          }
          if (warp == 9) PROF(20);
          asm volatile("bar.arrive 9, 384;" ::: "memory");
          cluster_arrive(); cluster_wait();
          return;
        }
      }
      const unsigned layer = pass;
      named_bar(1 + (fresh_tid() >> 7), 128);
      regs_inc<224>();
      float acc[2][96];
      float pa[2][2], pb[2][2];
      {
        PHASE_IDS
        const uint32_t da0 = dlo(SOFF, 16) + (wg - 2) * 512;
        constexpr uint32_t db0 = dlo(SOFF + SL_W, 2048);
        if (warp == 9) PROF(19 - 2 * layer);
        mbar_wait(bar(B_FULL), 0);
        if (warp == 9) PROF(29);
        if (warp == 9) STEPT(0);
        wg_fence();
        wg_ss192t_z(acc[0], da0, db0); wg_ss192t_z(acc[1], da0 + 1024, db0);
        wg_ss192t(acc[0], da0 + 2, db0 + 384, 1); wg_ss192t(acc[1], da0 + 1026, db0 + 384, 1);
        wg_commit();
        int s = 1, u = 0;
#pragma unroll 1
        for (int i = 1; i < 28; i++) {
          const uint32_t da = da0 + (s >> 1) * (STG >> 4) + (s & 1) * 4, db = db0 + (s >> 1) * (STG >> 4) + (s & 1) * (SL_HD >> 4);
          mbar_wait(bar(B_FULL + s), (u + (s > 1 ? layer : 0)) & 1);
          if (warp == 9 && !(i & 1)) STEPT(i >> 1);
          wg_fence();
          wg_ss192t(acc[0], da, db, 1); wg_ss192t(acc[1], da + 1024, db, 1);
          wg_ss192t(acc[0], da + 2, db + 384, 1); wg_ss192t(acc[1], da + 1026, db + 384, 1);
          wg_commit();
          wg_wait<1>();
          if (lane < 2 && i < 27) mbar_arrive_cluster(bar(B_EMPTY + (s == 0 ? 5 : s - 1)), lane);
          if (++s == 6) { s = 0; u++; }
        }
      }
      PHASE_IDS
      auto last_tile = [&](int m, int j) {
        const int e = (4 + j) % 6;
        const uint32_t da = dlo(SOFF + (e >> 1) * STG + (e & 1) * 64, 16) + (wg - 2) * 512 + m * 1024, db = dlo(SOFF + (e >> 1) * STG + SL_W + (e & 1) * SL_HD, 2048);
        wg_fence();
        wg_ss192t(acc[m], da, db, 1);
        wg_ss192t(acc[m], da + 2, db + 384, 1);
      };
      {
        if (layer == 0) mbar_wait(bar(B_CS), 0);
        const uint32_t tag = s_misc[M_TAG];
        const uint4* src = &g_rowab[layer][rb * 256 + (wg - 2 + (lane >> 4) * 2) * 64 + wi * 16 + (lane & 15)];
        uint4 v;
#pragma unroll
        for (int j = 0; j < 4; j++) {
          if (j == 2) v = ld_relaxed4(src);
          mbar_wait(bar(B_FULL + (4 + j) % 6), j < 2 ? layer : 1);
          last_tile(1, j);
          if (j == 0) { wg_commit(); wg_wait<1>(); mbar_arrive_e(bar(B_E23)); }
        }
        wg_commit();
        last_tile(0, 0);
        wg_commit();
        if (warp != 9) STEPT(4);
#pragma unroll 1
        for (uint32_t spins = 0; !__all_sync(0xffffffffu, v.z == tag) && spins < SPIN_LIMIT; spins++) v = ld_relaxed4(src);
#pragma unroll
        for (int j = 0; j < 4; j++) {
          pa[j >> 1][j & 1] = __uint_as_float(__shfl_sync(0xffffffffu, v.x, g + 8 * j));
          pb[j >> 1][j & 1] = __uint_as_float(__shfl_sync(0xffffffffu, v.y, g + 8 * j));
        }
        if (warp != 9) STEPT(5);
      }
      const int prow = (int)s_misc[M_SEL0] - rb * 256;
      const float4* cs = (const float4*)(smem + OFF_CS) + q;
      auto finish = [&](int m, int b, float2 c, uint32_t* dst) {
        dst[0] = pack_bf16(acc[m][4 * b] * pa[m][0] - c.x * pb[m][0], acc[m][4 * b + 1] * pa[m][0] - c.y * pb[m][0]);
        dst[1] = pack_bf16(acc[m][4 * b + 2] * pa[m][1] - c.x * pb[m][1], acc[m][4 * b + 3] * pa[m][1] - c.y * pb[m][1]);
      };
      auto grp = [](int n) { return n < 8 ? 4 + ((n >> 1) & 1) * 4 + (n >> 2) * 2 + (n & 1) : n - 8; };
      float4 cq[2] = {cs[grp(0) * 4], cs[grp(1) * 4]};
      auto next = [&](int m, int n, uint32_t* r) {
        if (m == 1 && n % 4 == 0) { last_tile(0, 1 + n / 4); wg_commit(); }
        const float4 c = cq[n & 1];
        cq[n & 1] = cs[grp((n + 2) % 12) * 4];
        finish(m, 2 * grp(n), make_float2(c.x, c.y), r); finish(m, 2 * grp(n) + 1, make_float2(c.z, c.w), r + 2);
      };
#pragma unroll
      for (int m = 1; m >= 0; m--) {
        if (m == 1) {
          wg_wait<1>();
          fence_regs<96>(acc[1]);
          mbar_wait(bar(B_E23), layer);
          if (warp != 9) STEPT(0);
        } else {
          wg_wait<0>();
          fence_regs<96>(acc[0]);
          if (warp != 9) STEPT(1);
          if (lane < 2) mbar_arrive_cluster(bar(B_QDONE), lane);
          if (warp == 9) PROF(2);
        }
        const int qb = wg - 2 + 2 * m;
        const bool patch = prow >> 4 == qb * 4 + wi;
#pragma unroll
        for (int jj = 0; jj < 8; jj++) {
          const int h = jj >> 2;
          uint32_t r[4];
          next(m, jj, r);
          if (m == 0 && jj == 0) named_bar(5, 256);
          stsm_x4(sbase + kv_off(h, 4 + 2 * m) + (wg - 2) * 8192 + ((jj >> 1) & 1) * 4096 + srow * 64 + ((((jj & 1) * 2 + (mi >> 1)) ^ ((srow >> 1) & 3)) << 4),
              r[0], r[1], r[2], r[3]);
        }
        if (patch) {
          mbar_wait(bar(B_CS), 1);
          __syncwarp();
          if (lane < 16)
            *(uint4*)(smem + kv_off(g >> 1, 4 + qb) + (g & 1) * 4096 + (prow & 63) * 64 + ((q ^ ((prow >> 1) & 3)) << 4)) =
              *(const uint4*)(smem + OFF_PATCH + 128 + (g & 1) * 128 + (g >> 1) * 64 + q * 16);
        }
        fence_async_smem();
        __syncwarp();
        mbar_arrive_e(bar(B_KVREADY + 1 - m));
        if (warp != 9) STEPT(3 - m);
        pa[m][0] *= SM_C; pa[m][1] *= SM_C; pb[m][0] *= SM_C; pb[m][1] *= SM_C;
#pragma unroll
        for (int jj = 0; jj < 4; jj++) {
          uint32_t r[4];
          next(m, 8 + jj, r);
          *(uint4*)(smem + qo_off(jj >> 1, 2 * m) + (warp - 8) * 1024 + (jj & 1) * 512 + lane * 16) = make_uint4(r[0], r[1], r[2], r[3]);
        }
        __syncwarp();
        if (patch) {
          *(uint32_t*)(smem + qo_off(lane >> 4, 2 * m) + (warp - 8) * 1024 + (mi & 1) * 512 + ((prow & 7) * 4 + q) * 16 + ((g & 1) * 2 + ((prow >> 3) & 1)) * 4) =
              *(const uint32_t*)(smem + OFF_PATCH + lane * 4);
          __syncwarp();
        }
      }
      if (warp == 9) PROF(3);
      mbar_arrive_e(bar(B_QREADY));
      regs_dec<120>();
    } else {
      if (pass > 0) {
        const unsigned layer = pass - 1;
        PHASE_IDS
        const uint32_t tag = s_misc[M_TAG];
        if (warp == 7) {
          uint32_t* tab = (uint32_t*)(smem + OFF_PATCH);
#pragma unroll
          for (int j = 0; j < 2; j++) { const int w = lane + 32 * j; tab[(w & 3) * 16 + (w >> 2)] = ((const uint32_t*)P.w_r)[nb * 64 + w]; }
          tab[64 + lane] = lane < 16 ? 0x3F803F80u : 0u;
          float tot = 0.f;
#pragma unroll 1
          for (int j = 0; j < 4; j++) {
            const uint4 u = ((const uint4*)P.w_r)[lane + 32 * j];
            tot += bf_lo(u.x) + bf_hi(u.x) + bf_lo(u.y) + bf_hi(u.y) + bf_lo(u.z) + bf_hi(u.z) + bf_lo(u.w) + bf_hi(u.w);
          }
          s_misc[M_WSUM] = __float_as_uint(warp_sum(tot));
        }
        if (layer == 1) {
          const float2 ln = g_rowln[nb][mb * 128 + tid - 128];
          const uint32_t m2 = pack_bf16(ln.x, ln.x);
          uint8_t* row = smem + qo_off(0, wi & 2) + (tid & 63) * 128;
          mbar_wait(bar(B_RES), 1);
#pragma unroll 1
          for (int j = 0; j < 8; j++) {
            uint4* c = (uint4*)(row + (((j + lane) & 7) << 4));
            const uint4 v = c[0], w = c[512];
            c[0] = make_uint4(add_ln_pair(v.x, m2, ln.y), add_ln_pair(v.y, m2, ln.y), add_ln_pair(v.z, m2, ln.y), add_ln_pair(v.w, m2, ln.y));
            c[512] = make_uint4(add_ln_pair(w.x, m2, ln.y), add_ln_pair(w.y, m2, ln.y), add_ln_pair(w.z, m2, ln.y), add_ln_pair(w.w, m2, ln.y));
          }
          const int prow = (int)s_misc[M_SEL0] - mb * 128;
          __syncwarp();
          if (prow >> 5 == wi && lane < 16)
            *(uint4*)(smem + qo_off(0, wi & 2) + (lane >> 3) * 8192 + (prow & 63) * 128 + (((lane ^ prow) & 7) << 4)) = poll4(&g_x2row[(nb * 16 + lane) * 2]);
        }
        __syncwarp();
        mbar_arrive_e(bar(B_RST));
        if (warp == 4) {
          named_bar(6, 320);
          spin_cycles(DELAY_S);
          uint4 c, u0 = {}, u1 = {};
          uint32_t u2 = 0, best = 0, spins = 0;
          int src;
#pragma unroll 1
          for (;;) {
            src = (~best & 0x7FFu) >> 7;
            const uint4* xsel = &g_cand[layer][src * 128];
            c = ld_relaxed4(&g_slot[layer][(lane & 15) * 8]);
            if (best) {
              u0 = ld_relaxed4(xsel + rank * 64 + lane); u1 = ld_relaxed4(xsel + rank * 64 + 32 + lane);
              u2 = ld_relaxed((const uint32_t*)(xsel + (bid >> 4) * 16 + q * 4) + (bid & 15));
            }
            const uint32_t prev = best;
            best = __reduce_max_sync(0xffffffffu, c.w == tag ? c.x : 0u);
            if ((__all_sync(0xffffffffu, c.w == tag && valid4(u0) && valid4(u1) && u2 != SENT) && best == prev) || ++spins > SPIN_LIMIT) break;
          }
          const float sel_m = __uint_as_float(__shfl_sync(0xffffffffu, c.y, src)), sel_inv = __uint_as_float(__shfl_sync(0xffffffffu, c.z, src));
          const uint32_t m2 = pack_bf16(sel_m, sel_m);
          uint4* xs = (uint4*)(smem + T_XS) + (lane & 16) + q * 4 + (g & 3);
          xs[0] = make_uint4(ln_pair(u0.x, m2, sel_inv), ln_pair(u0.y, m2, sel_inv), ln_pair(u0.z, m2, sel_inv), ln_pair(u0.w, m2, sel_inv));
          xs[32] = make_uint4(ln_pair(u1.x, m2, sel_inv), ln_pair(u1.y, m2, sel_inv), ln_pair(u1.z, m2, sel_inv), ln_pair(u1.w, m2, sel_inv));
          s_misc[M_KEY] = best; s_misc[M_MEAN] = __float_as_uint(sel_m); s_misc[M_INV] = __float_as_uint(sel_inv);
          s_misc[M_XQ + q] = u2;
          if (layer == 0) s_misc[M_SEL0] = ~best & 0x7FFu;
          PROF(16);
        }
        if (layer == 1) {
          named_bar(7, 512);
          const int sel = SEQ - 1 - (int)(s_misc[M_KEY] & 0x7FFFu), skip = sel >> 7 == mb ? (sel >> 6) & 1 : -1;
          if (warp == 7) store_tile(1, skip, false);
          if (warp == 4) {
            mbar_wait_cluster(bar(B_HX), 1);
            ((bf16*)(smem + OFF_PATCH + 256))[((lane >> 1) & 3) * 8 + (lane >> 3) * 2 + (lane & 1)] = __float2bfloat16_rn(hidden());
            asm volatile("bar.arrive 10, 288;" ::: "memory");
          }
#pragma unroll 1
          for (int c = tid - 128; c < 1024 && skip >= 0; c += 128) {
            const int r = c >> 4;
            if (r != (sel & 63))
              *(uint4*)(P.out + (size_t)(mb * 128 + skip * 64 + r) * DM + nb * 128 + (c & 15) * 8) =
                *(const uint4*)(smem + X_ST + skip * 16384 + ((c >> 3) & 1) * 8192 + r * 128 + (((c ^ r) & 7) << 4));
          }
          __syncwarp();
        } else asm volatile("bar.arrive 7, 512;" ::: "memory");
        if (warp == 5 && layer == 0) {
          named_bar(8, 288);
          if (nb > 0) spin_cycles(X_STAGGER);
          store_tile(0, -1, true);
          set_flag(&g_xflag[mb][nb].v[0], tag);
          PROF(17);
          poll_flag(&g_xflag[2 * rb + (lane & 1)][0].v[0], tag);
          fence_async_global();
          load_a(0, 0, 1);
          PROFL(1, 1);
        }
      }
      named_bar(1 + (fresh_tid() >> 7), 128);
      regs_dec<32>();
#pragma unroll 1
      for (;;) {
        const unsigned pass = __shfl_sync(0xffffffffu, pass_v, 0);
        if (pass > 0) {
          const unsigned layer = pass - 1;
          PHASE_IDS
          const uint32_t tag = s_misc[M_TAG], bkey = s_misc[M_KEY];
          const int sel = SEQ - 1 - (int)(bkey & 0x7FFFu);
          if (warp == 3) {
            if (layer == 1) {
#pragma unroll
              for (int j = 0; j < 3; j++) ((uint4*)g_vw)[bid * 96 + j * 32 + lane] = make_uint4(0, 0, 0, 0);
            }
            if (bid == 0 && lane == 0) g_sel[layer] = sel;
          }
          __syncwarp();
          if (layer == 0) {
            auto load_down = [&](int j) {
              mbar_expect_tx(bar(B_DN + j), 2 * FFN_PIECE);
              bulk_load_h(sbase + SL_F + j * 2 * FFN_PIECE, P.w_d + (size_t)((cl * 56 + rank * 28) + j * 14) * DM, 2 * FFN_PIECE, bar(B_DN + j), policy_evict_first());
            };
            if (warp == 5) {
              load_a(2, 2, 1);
              poll_flag(&g_xflag[2 * rb + (lane & 1)][(lane >> 1) & 7].v[0], tag);
              fence_async_global();
              load_a(4, 4, 1);
            }
            float hv = 0.f;
            if (wg == 1) { mbar_wait_cluster(bar(B_HX), 0); hv = rbf(hidden()); fence_regs<1>(&hv); }
            named_bar(9, 512);
            if (warp == 0) {
              fence_async_smem();
              if (lane < 16) mbar_arrive_cluster(bar(B_QFREE), lane & 1);
              mbar_wait(bar(B_QFREE), 1);
              load_w(4, 4); load_w(5, 5);
              load_down(0);
            } else if (wg == 1) {
              if (warp == 4) { mbar_wait(bar(B_DN), 0); load_down(1); }
              float d[8] = {0.f, 0.f, 0.f, 0.f, 0.f, 0.f, 0.f, 0.f};
              const uint4* wrow = (const uint4*)(smem + SL_F) + tid - 128;
              mbar_wait(bar(B_DN), 0);
              uint4 w0 = wrow[0];
#pragma unroll 1
              for (int j = 0; j < 28; j += 2) {
                const uint4 w1 = wrow[j * 128 + 128];
                fma8(d, w0, __shfl_sync(0xffffffffu, hv, j));
                if (j == 12) mbar_wait(bar(B_DN + 1), 0);
                w0 = wrow[min(j + 2, 27) * 128];
                fma8(d, w1, __shfl_sync(0xffffffffu, hv, j + 1));
              }
              uint4* dst = &g_ypart[0][bid * 256 + (tid - 128) * 2];
              st_relaxed4(dst, make_uint4(__float_as_uint(d[0]), __float_as_uint(d[1]), __float_as_uint(d[2]), __float_as_uint(d[3])));
              st_relaxed4(dst + 1, make_uint4(__float_as_uint(d[4]), __float_as_uint(d[5]), __float_as_uint(d[6]), __float_as_uint(d[7])));
              asm volatile("bar.arrive 11, 160;" ::: "memory");
              PROF(20);
            } else if (warp == 2) {
              named_bar(11, 160);
              fence_async_smem();
              load_ws(WS_PACE);
            }
          } else {
            if (wg == 1) named_bar(9, 384);
            cluster_arrive();
          }
          if (wg == 1) {
            const int t_y = (int)clock();
            const uint32_t xw = s_misc[M_XQ + ((lane & 7) >> 1)];
            const float x = (lane & 1) ? bf_hi(xw) : bf_lo(xw);
            float xn = rbf(rbf(x - __uint_as_float(s_misc[M_MEAN])) * __uint_as_float(s_misc[M_INV]));
            uint32_t u = bkey & 0xFFFF0000u;
            u = (u & 0x80000000u) ? (u & 0x7FFFFFFFu) : (~u & 0xFFFF0000u);
            float sg = rbf(__fdividef(1.f, 1.f + __expf(-__uint_as_float(u))));
            uint32_t* dst = (layer == 0 ? (uint32_t*)&g_x2row[bid * 2] : (uint32_t*)(P.out + (size_t)sel * DM + bid * 8)) + (lane >> 1);
            asm volatile("" : "+f"(xn), "+f"(sg), "+l"(dst));
#pragma unroll 1
            while ((int)clock() - t_y < DELAY_Y) {}
            const uint4* src = &g_ypart[layer][((tid - 128) >> 1) * 256 + bid * 2 + (tid & 1)];
            uint4 v, w;
            uint32_t spins = 0;
#pragma unroll 1
            do { v = ld_relaxed4(src); w = ld_relaxed4(src + 64 * 256); } while (!__all_sync(0xffffffffu, valid4(v) && valid4(w)) && ++spins < SPIN_LIMIT);
            float a[4] = {__uint_as_float(v.x) + __uint_as_float(w.x), __uint_as_float(v.y) + __uint_as_float(w.y),
                  __uint_as_float(v.z) + __uint_as_float(w.z), __uint_as_float(v.w) + __uint_as_float(w.w)};
            const bool b1 = lane & 2, b2 = lane & 4;
            float c0 = (b1 ? a[1] : a[0]) + __shfl_xor_sync(0xffffffffu, b1 ? a[0] : a[1], 2);
            float c1 = (b1 ? a[3] : a[2]) + __shfl_xor_sync(0xffffffffu, b1 ? a[2] : a[3], 2);
            float y = (b2 ? c1 : c0) + __shfl_xor_sync(0xffffffffu, b2 ? c0 : c1, 4);
            y += __shfl_xor_sync(0xffffffffu, y, 8);
            y += __shfl_xor_sync(0xffffffffu, y, 16);
            float* red = (float*)(smem + OFF_PATCH);
            red[wi * 8 + (lane & 1) * 4 + ((lane >> 1) & 3)] = y;
            named_bar(2, 128);
            if (warp == 4) {
              PROF(21);
              y = (red[lane & 7] + red[8 + (lane & 7)]) + (red[16 + (lane & 7)] + red[24 + (lane & 7)]);
              const float res = x + rbf(xn + rbf(rbf(y) * sg));
              const uint32_t pr = pack_bf16(res, __shfl_down_sync(0xffffffffu, res, 1));
              if (lane < 8 && (lane & 1) == 0) st_relaxed(dst, pr);
              PROF(22);
            }
          }
          if (pass == 2) {
            if (bid == 0 && tid == 128) g_epoch = tag;
            bulk_wait_all();
            __syncwarp();
            cluster_wait();
            return;
          }
        }
        const unsigned layer = pass;
        if (__shfl_sync(0xffffffffu, fresh_tid() >> 5, 0) > 1 - (int)layer) {
          PHASE_IDS
          uint4* xrow = (uint4*)(smem + SL_F + 4 * SL_HD);
          if (wg == 1) {
            if (layer == 0) {
              xrow[tid - 128] = make_uint4(0x3F803F80u, 0x3F803F80u, 0x3F803F80u, 0x3F803F80u);
              if (warp == 5) {
                mbar_wait(bar(B_FULL + 5), 0);
                if (lane == 0) {
#pragma unroll 1
                  for (int i = 11; i > 0; i--) prefetch_tmap(&P.mapA[0] + i);
                }
                __syncwarp();
                load_ws(WS_PACE);
              }
            } else xrow[tid - 128] = poll4(&g_x2row[(tid - 128) * 2]);
            PROF(23);
          }
          named_bar(12, 192 + 32 * layer);
          if (warp == 1) {
            float mean = 0.f;
#pragma unroll 1
            for (int pass2 = 0; pass2 < 2; pass2++) {
              float acc = 0.f;
#pragma unroll 1
              for (int j = lane; j < 128; j += 32) {
                const uint4 v = xrow[j];
                const uint32_t w[4] = {v.x, v.y, v.z, v.w};
#pragma unroll
                for (int c = 0; c < 4; c++) {
                  const float d0 = bf_lo(w[c]) - mean, d1 = bf_hi(w[c]) - mean;
                  acc += pass2 ? d0 * d0 + d1 * d1 : d0 + d1;
                }
              }
              acc = warp_sum(acc) * (1.f / DM);
              if (pass2 == 0) mean = acc;
              else { s_misc[M_PMEAN] = __float_as_uint(rbf(mean)); s_misc[M_PINV] = __float_as_uint(ln_inv(acc)); }
            }
          } else {
            mbar_wait(bar(B_WS), layer);
            const uint8_t* wa = smem + SL_F + (g >> 1) * SL_HD + ((warp - 2) >> 1) * 4096 + (g & 1) * 2048;
            const uint32_t* xs = (const uint32_t*)xrow + rb * 64 + g * 8;
            const int ch = (warp & 1) * 4 + q;
            float d[8] = {0.f, 0.f, 0.f, 0.f, 0.f, 0.f, 0.f, 0.f};
            auto wrow = [&](int j) { j = (j ^ ((g & 1) * 4)) & 15; return *(const uint4*)(wa + j * 128 + (((ch ^ j) & 7) << 4)); };
            uint4 w0 = wrow(0);
#pragma unroll 1
            for (int j = 0; j < 16; j += 2) {
              const uint32_t xx = xs[(j >> 1) ^ ((g & 1) * 2)];
              const uint4 w1 = wrow(j + 1);
              fma8(d, w0, bf_lo(xx));
              w0 = wrow(j + 2);
              fma8(d, w1, bf_hi(xx));
            }
#pragma unroll
            for (int c = 0; c < 4; c++) d[c] = ((g & 4) ? d[c + 4] : d[c]) + __shfl_xor_sync(0xffffffffu, (g & 4) ? d[c] : d[c + 4], 16);
#pragma unroll
            for (int c = 0; c < 2; c++) d[c] = ((g & 2) ? d[c + 2] : d[c]) + __shfl_xor_sync(0xffffffffu, (g & 2) ? d[c] : d[c + 2], 8);
            d[0] = ((g & 1) ? d[1] : d[0]) + __shfl_xor_sync(0xffffffffu, (g & 1) ? d[0] : d[1], 4);
            st_relaxed(&g_vw[layer][rb][((warp - 2) >> 1) * DM + hp * 64 + ch * 8 + g], enc(d[0]));
          }
          named_bar(12, 192 + 32 * layer);
          PROF(24);
        }
        PHASE_IDS
        if (wg == 0) {
          if (warp == 0) {
            if (layer == 0) {
#pragma unroll 1
              for (int i = 2; i < 6; i++) { load_w(i, i); if (!(i & 1)) load_a(i, i, 0); }
            }
            int s = 0, u = 0;
#pragma unroll 1
            for (int i = 6; i < 32; i++) {
              if (layer == 1) mbar_arrive_e(bar(B_EMPTY + s));
              mbar_wait(bar(B_EMPTY + s), (u + (s > 1 ? 0 : layer)) & 1);
              if (s & 1) load_a(s - 1, i - 1, layer);
              load_w(s, i);
              if (++s == 6) { s = 0; u++; }
            }
          } else if (warp == 1) {
            if (layer == 0) {
              const uint32_t tag = ld_relaxed(&g_epoch) + 1;
              if (lane < 16) g_rowab[0][rb * 256 + hp * 16 + lane] = make_uint4(0, 0, 0, 0);
              float shift = 0.f, sum = 0.f, sq = 0.f;
              const int r = hp * 16 + (lane >> 1);
#pragma unroll 1
              for (int i = 0; i < 32; i++) {
                mbar_wait(bar(B_FULL + i % 6), (i / 6) & 1);
                const uint8_t* base = smem + ((i % 6) >> 1) * STG + r * 128;
                uint4 v[2];
#pragma unroll
                for (int j = 0; j < 2; j++) v[j] = *(const uint4*)(base + ((((i & 1) * 4 + (lane & 1) * 2 + j) ^ (r & 7)) << 4));
                if (i == 0) shift = __shfl_sync(0xffffffffu, bf_lo(v[0].x), lane & ~1);
#pragma unroll
                for (int j = 0; j < 2; j++) {
                  const uint32_t w[4] = {v[j].x, v[j].y, v[j].z, v[j].w};
#pragma unroll
                  for (int c = 0; c < 4; c++) {
                    const float d0 = bf_lo(w[c]) - shift, d1 = bf_hi(w[c]) - shift;
                    sum += d0 + d1; sq = fmaf(d0, d0, fmaf(d1, d1, sq));
                  }
                }
                fence_async_smem();
                __syncwarp();
                if (i < 26) mbar_arrive_e(bar(B_EMPTY + i % 6));
              }
              sum += __shfl_xor_sync(0xffffffffu, sum, 1); sq += __shfl_xor_sync(0xffffffffu, sq, 1);
              const float dm = sum * (1.f / DM), var = fmaxf(sq * (1.f / DM) - dm * dm, 0.f), mean = shift + dm;
              const float inv = ln_inv(var);
              if ((lane & 1) == 0) st_relaxed4(&g_rowab[0][rb * 256 + r], make_uint4(__float_as_uint(inv), __float_as_uint(rbf(mean) * inv), tag, 0));
            }
            __syncwarp();
            mbar_arrive_e(bar(B_E23));
            if (rb == 0) {
              mbar_wait(bar(B_QDONE), layer);
#pragma unroll 1
              for (int j = lane; j < 512; j += 32) ((uint4*)(smem + kv_off(1, 0)))[j] = make_uint4(0, 0, 0, 0);
              fence_async_smem();
              __syncwarp();
              if (lane < 3) mbar_arrive(bar(B_HALO + lane));
            }
          } else if (warp == 3) {
            if (rb > 0) { mbar_expect_tx(bar(B_HALO), 16384); mbar_expect_tx(bar(B_HALO + 1), 16384); mbar_expect_tx(bar(B_HALO + 2), 32768); }
            fence_async_smem();
            load_gu(0, layer ? GU_PACE1 : GU_PACE, 0, 4);
            PROF(27);
          } else {
            const uint4 sent = make_uint4(SENT, SENT, SENT, SENT), zero = make_uint4(0, 0, 0, 0);
            if (layer == 0) {
              const int f = lane >> 1;
              Flag* fl = f < 2 ? &g_kvflag[rb >> 1][hp][f] : f < 5 ? &g_oflag[rb][f - 2][hp] : &g_xflag[mb][nb];
              if (f < 6 && (f >= 2 || (rank == 1 && rb < 7))) ((uint4*)fl)[lane & 1] = zero;
            }
#pragma unroll 1
            for (int t = lane; t < 128; t += 32) {
              g_ypart[layer][bid * 256 + t] = sent; g_ypart[layer][bid * 256 + 128 + t] = sent;
              g_part[layer][nb * SEQ + mb * 128 + t] = zero;
              if (t < 16) g_cand[layer][mb * 128 + nb * 16 + t] = sent;
              else if (t < 18) { if (nb == 0) g_slot[layer][mb * 8 + t - 16] = zero; }
              else if (t < 20) { if (layer == 0) g_x2row[bid * 2 + t - 18] = sent; }
            }
            __syncwarp();
            mbar_arrive_e(bar(B_CS));
          }
          __syncwarp();
          if (warp == 0) {
            if (rank == 0) mbar_wait(bar(B_QDONE), layer);
            mbar_wait(bar(B_KVREADY), layer);
            export_halo(0);
            if (rank == 1) {
              bulk_wait_all();
              asm volatile("bar.arrive 13, 64;" ::: "memory");
              if (rb < 7) set_flag(&g_kvflag[rb >> 1][hp][0].v[layer], s_misc[M_TAG]);
            }
            PROF(4);
          } else if (warp == 3 && rank == 1) {
            mbar_wait(bar(B_KVREADY + 1), layer);
            named_bar(13, 64);
            export_halo(1);
          }
        } else {
          const int t = tid - 128, go = (t >> 5) * DM + hp * 64 + (t & 31) * 2;
          if (layer == 0 && t == 96) { s_misc[M_TAG] = ld_relaxed(&g_epoch) + 1; s_misc[M_SEL0] = 0xFFFFFFFFu; s_misc[M_PROG] = 0; }
          if ((layer == 0 || (int)s_misc[M_SEL0] >> 8 == rb) && warp < 7) {
            spin_cycles(layer ? 300 : 1500);
            uint2 w[8];
            uint32_t spins = 0;
            bool ok;
#pragma unroll 1
            do {
              ok = true;
#pragma unroll
              for (int j = 0; j < 8; j++) w[j] = ld_relaxed2(&g_vw[layer][j][go]);
#pragma unroll
              for (int j = 0; j < 8; j++) ok = ok && w[j].x && w[j].y;
            } while (!__all_sync(0xffffffffu, ok) && ++spins < SPIN_LIMIT);
            float s0 = 0.f, s1 = 0.f;
#pragma unroll
            for (int j = 0; j < 8; j++) { s0 += dec(w[j].x); s1 += dec(w[j].y); }
            float2* csp = (float2*)(smem + OFF_CS) + (t & ~7) + (t & 3) * 2 + ((t >> 2) & 1);
            if (layer == 0) *csp = make_float2(s0, s1);
            else {
              const float2 c = *csp;
              const float a = __uint_as_float(s_misc[M_PINV]) * (warp == 4 ? SM_C : 1.f), b = __uint_as_float(s_misc[M_PMEAN]) * a;
              ((uint32_t*)(smem + OFF_PATCH))[t] = pack_bf16(s0 * a - c.x * b, s1 * a - c.y * b);
            }
            PROF(25);
          }
          __syncwarp();
          mbar_arrive_e(bar(B_CS));
        }
        __syncwarp();
        if (wi == 0) mbar_wait(bar(B_QREADY), layer);
        named_bar(1 + (fresh_tid() >> 7), 128);
        if (__shfl_sync(0xffffffffu, fresh_tid() >> 7, 0) == 0) {
          regs_inc<152>();
          uint32_t gu[112];
          {
            PHASE_IDS
            const uint32_t tag = s_misc[M_TAG];
            mbar_wait(bar(B_GU), layer);
#pragma unroll
            for (int j = 0; j < 28; j++) fetch_gu(gu + 4 * j, warp * 4 + (j & 3), j >> 2);
            fence_async_smem();
            named_bar(1, 128);
            if (warp == 0) {
              mbar_wait(bar(B_ADONE), layer);
#pragma unroll 1
              for (int k = 2; k < 16; k++) {
#pragma unroll 1
                for (uint32_t spins = 0; (int)s_misc[M_PROG] <= k + 32 * (int)layer && spins < SPIN_LIMIT; spins++) {}
                if (k >= 4) mbar_wait(bar(B_WEMPTY + (k & 3)), ((k >> 2) - 1 + ((k & 2) ? layer : 0)) & 1);
                const int kd = k >= 8 && hp < 8 ? k ^ 4 : k;
                load_o(kd); load_wo(kd);
                STEPT(16 + k);
                if (k == RES_K) { mbar_wait(bar(B_OST + 1), layer); load_res(1, layer); }
              }
              if (layer == 1) {
                mbar_wait(bar(B_WEMPTY + 1), 1);
                mbar_expect_tx(bar(B_DN), 4 * FFN_PIECE);
                tma_load3_h(sbase + wo_off(0), &P.mapD, 0, (cl * 56 + rank * 28), 0, bar(B_DN), policy_evict_first());
              }
              named_bar(6, 320);
              if (layer == 0) {
                mbar_wait(bar(B_QFREE), 0);
#pragma unroll 1
                for (int i = 0; i < 4; i++) load_w(i, i);
              } else tma_load3_h(sbase + wo_off(0) + 2 * FFN_PIECE, &P.mapD, 0, (cl * 56 + rank * 28), 8, bar(B_DN), policy_evict_first());
            } else if (warp < 3) {
#pragma unroll 1
              for (int f = warp - 1; f < 2 * warp - 1; f++) {
                const int u0 = f == 0 ? 0 : 4 + 2 * ((f + (hp >> 3) + 1) & 1);
#pragma unroll 1
                for (int u = u0; u < u0 + (f ? 2 : 4); u++) {
                  mbar_wait(bar(B_UNIT + u), layer);
                  bulk_store(g_o + (size_t)((((rb * 2 + ((~u >> 1) & 1)) * 2 + (u >> 2)) * 16 + hp) * 2 + (~u & 1)) * 4096, sbase + qo_off(u >> 2, ~u & 3), 4096);
                }
                bulk_commit();
                if (f == 0 && lane < 2) mbar_arrive_cluster(bar(B_OST), lane);
                bulk_wait_all();
                if (f == 2) mbar_arrive_e(bar(B_OST + 1));
                set_flag(&g_oflag[rb][f][hp].v[layer], tag);
                PROF(f ? 29 + f : 28);
              }
              if (warp == 1) {
                load_res(0, layer);
                mbar_wait(bar(B_OST), layer);
                load_wo(0); load_wo(1);
                const unsigned* flag = &g_oflag[rb][lane < 16 ? 0 : (lane >> 3) - 1][lane < 16 ? lane : (lane ^ hp ^ 8) & 8 | lane & 7].v[layer];
                int n = 0;
#pragma unroll 1
                for (uint32_t spins = 0; n < 16 && spins < SPIN_LIMIT; spins++) {
                  const int before = n;
                  if (n == 8 || n == 12) mbar_wait(bar(B_ADONE), layer);
                  const bool pending = lane >= 2 * n && (lane >= (n < 8 ? 16 : 32) || ld_relaxed(flag) != tag);
                  n = __clz(__brev(__ballot_sync(0xffffffffu, pending))) >> 1;
                  asm volatile("fence.acquire.gpu;" ::: "memory");
                  fence_async_global();
                  if (before < 2 && n >= 2) { load_o(0); load_o(1); PROF(15); }
                  s_misc[M_PROG] = n + 32 * layer;
                }
                PROF(26);
              }
            } else {
              mbar_expect_tx(bar(B_HX), 2240);
              const int early = rank == 0 && hp < 8;
#pragma unroll 1
              for (int p = 0; p < 2; p++) {
                if (rank == 0 && rb > 0) {
                  poll_flag(&g_kvflag[(rb - 1) >> 1][hp][p].v[layer], tag);
                  fence_async_global();
#pragma unroll 1
                  for (int h = 0; h < 2; h++)
                    bulk_load_h(sbase + kv_off(h, 2 - 2 * p), g_kv + (size_t)((cl - 16) * 4 + p * 2 + h) * 16384, 16384, bar(B_HALO + (p ? 2 : h)), policy_evict_first());
                }
                if (p == 0) {
                  PROF(5);
                  if (rank == 0) { if (early) load_gu(1, 0, 0, 1); export_halo(1); }
                  else if (rb < 7) { bulk_wait_all(); set_flag(&g_kvflag[rb >> 1][hp][1].v[layer], tag); }
                }
              }
              if (rb == 0 || rb == 7) spin_cycles(1000);
              PROF(6);
              load_gu(1, GUB_PACE, early, 4);
            }
          }
          PHASE_IDS
          uint4 xa = {}, xb = {};
          named_bar(7, 512);
          if (g == 0) { xa = ((const uint4*)(smem + T_XS))[warp * 8 + q]; xb = ((const uint4*)(smem + T_XS))[warp * 8 + 4 + q]; }
          __syncwarp();
          float d[7][4] = {};
#pragma unroll
          for (int j = 0; j < 28; j++) {
            const int ks = j / 7, ct = j % 7;
            const uint32_t* a = gu + ct * 16 + ks * 4;
            mma_16816(d[ct], a[0], a[1], a[2], a[3], ks == 0 ? xa.x : ks == 1 ? xa.z : ks == 2 ? xb.x : xb.z, ks == 0 ? xa.y : ks == 1 ? xa.w : ks == 2 ? xb.y : xb.w);
          }
#pragma unroll
          for (int ct = 0; ct < 7; ct++) send_gu(d[ct][0], d[ct][2], ct, warp);
          __syncwarp();
          if (warp == 2) PROF(18);
          regs_dec<32>();
          pass_v = pass + 1;
          continue;
        }
        break;
      }
      regs_inc<120>();
    }
    const unsigned layer = pass;
    {
      PHASE_IDS
      mbar_wait(bar(B_QREADY), layer);
      if (warp != 9) STEPT(7);
      const int bmin = rb == 0 ? 4 : 0;
      auto kdesc = [&](int h, int b) { const uint32_t v = dlo(SOFF, 16) + (kv_off(h, b) >> 4); return b < bmin ? dlo(SOFF + kv_off(1, 0), 16) : v; };
      auto vdesc = [&](int h, int b) {
        const uint32_t v = dlo(SOFF + 4096, OFF_ONES - 4096) + (kv_off(h, b) >> 10) * VSTEP;
        return b < bmin ? dlo(SOFF + kv_off(1, 0), 4096) : v;
      };
      const int units = hp < 8 ? (wg == 3 ? 0x8630 : (wg == 2 ? 0x8721 : 0x854)) : (wg == 3 ? 0x8430 : (wg == 2 ? 0x8521 : 0x876));
      auto need = [&](int h, int b) { if (b == 3 || b == 1) mbar_wait(bar(B_HALO + (b == 1 ? 2 : h)), layer); };
      auto load_q = [&](uint32_t* qf, int u) {
        *(uint4*)&qf[0] = *(const uint4*)(smem + qo_off(u >> 2, ~u & 3) + wi * 1024 + lane * 16);
        *(uint4*)&qf[4] = *(const uint4*)(smem + qo_off(u >> 2, ~u & 3) + wi * 1024 + 512 + lane * 16);
      };
      auto store_o = [&](const float* o, int u) {
        const float i0 = rcp(o[16]), i1 = rcp(o[18]);
        if (u >= 4 && lane < 2) mbar_arrive_cluster(bar(B_ADONE), lane);
#pragma unroll
        for (int j = 0; j < 2; j++)
          stsm_x4(sbase + qo_off(u >> 2, ~u & 3) + srow * 64 + (((2 * j + (mi >> 1)) ^ ((srow >> 1) & 3)) << 4),
            pack_bf16(o[8 * j] * i0, o[8 * j + 1] * i0), pack_bf16(o[8 * j + 2] * i1, o[8 * j + 3] * i1),
            pack_bf16(o[8 * j + 4] * i0, o[8 * j + 5] * i0), pack_bf16(o[8 * j + 6] * i1, o[8 * j + 7] * i1));
        fence_async_smem();
        __syncwarp();
        mbar_arrive_e(bar(B_UNIT + u));
      };
      int redo = 0;
      {
        const int dl = g - 2 * q;
        const uint32_t mt = shl_clamp(0xFFFFFFFFu, max(16 * dl + 16, 0));
        uint32_t qf[8];
        float s[32];
        load_q(qf, units & 7);
        wg_fence();
        qk64(s, qf, kdesc((units >> 2) & 1, 6 - (units & 3)));
        wg_commit();
        wg_wait<0>();
        fence_regs<32>(s);
#pragma unroll 1
        for (int ul = units; ul != 8; ul >>= 4) {
          const int u = ul & 7, h = u >> 2, qb = 3 - (u & 3);
          float o[20];
          uint32_t p1[16], p2[16], p3[16], p4[16], p5[16];
          if (warp != 9) STEPT(8 + nu * 8);
          exp_pack<8>(s, p1);
          fence_regs_u<16>(p1);
          need(h, qb + 2);
          {
            float s2[32];
            const uint32_t vd = vdesc(h, qb + 3);
            wg_fence();
            qk64(s2, qf, kdesc(h, qb + 2));
            wg_commit();
            wg_rs40t_z<H64>(o, p1[0], p1[1], p1[2], p1[3], vd);
            wg_rs40t<H64>(o, p1[4], p1[5], p1[6], p1[7], vd + VSTEP, 1);
            pv32(o, p1 + 8, vd + 2 * VSTEP);
            wg_commit();
            wg_wait<1>();
            fence_regs<32>(s2);
            if (warp != 9) STEPT(9 + nu * 8);
            exp_pack<8>(s2, p2);
            fence_regs_u<16>(p2);
            wg_wait<0>();
            fence_regs<20>(o);
          }
          need(h, qb + 1);
          {
            float s3[32];
            wg_fence();
            qk64(s3, qf, kdesc(h, qb + 1));
            wg_commit();
            pv32(o, p2, vdesc(h, qb + 2)); pv32(o, p2 + 8, vdesc(h, qb + 2) + 2 * VSTEP);
            wg_commit();
            wg_wait<1>();
            fence_regs<32>(s3);
            if (warp != 9) STEPT(10 + nu * 8);
            exp_pack<8>(s3, p3);
            fence_regs_u<16>(p3);
            wg_wait<0>();
            fence_regs<20>(o);
          }
          need(h, qb);
          const uint32_t kd = kdesc(h, qb + 4), kt = kdesc(h, qb), vd = vdesc(h, qb + 4), vt = vdesc(h, qb);
          {
            float sd[16], st[16];
            wg_fence();
            qk32x2(sd, st, qf, kd, kt);
            wg_commit();
            pv32(o, p3, vdesc(h, qb + 1)); pv32(o, p3 + 8, vdesc(h, qb + 1) + 2 * VSTEP);
            wg_commit();
            wg_wait<1>();
            fence_regs<16>(sd); fence_regs<16>(st);
            if (warp != 9) STEPT(11 + nu * 8);
            edge32(sd, st, p4, p4 + 8, wi, dl, mt);
            fence_regs_u<16>(p4);
            wg_wait<0>();
            fence_regs<20>(o);
          }
          const int un = (ul >> 4) == 8 ? 4 : (ul >> 4) & 7;
          {
            float sd[16], st[16];
            wg_fence();
            qk32x2(sd, st, qf, kd + 128, kt + 128);
            wg_commit();
            pv32(o, p4, vd); pv32(o, p4 + 8, vt);
            wg_commit();
            wg_wait<1>();
            fence_regs<16>(sd); fence_regs<16>(st);
            load_q(qf, un);
            edge32(sd, st, p5, p5 + 8, wi - 2, dl, mt);
            fence_regs_u<16>(p5);
          }
          need(un >> 2, 6 - (un & 3));
          wg_fence();
          pv32(o, p5, vd + 2 * VSTEP); pv32(o, p5 + 8, vt + 2 * VSTEP);
          wg_commit();
          qk64(s, qf, kdesc(un >> 2, 6 - (un & 3)));
          wg_commit();
          wg_wait<1>();
          fence_regs<20>(o);
          if (warp != 9) STEPT(12 + nu * 8);
          const bool unsafe = !(o[16] >= LSUM_MIN && o[16] <= LSUM_MAX && o[18] >= LSUM_MIN && o[18] <= LSUM_MAX);
          if (__any_sync(0xffffffffu, unsafe)) redo |= 1 << u;
          else store_o(o, u);
          wg_wait<0>();
          fence_regs<32>(s);
        }
      }
      if (warp != 9) STEPT(31);
      if (bar_red_or(1 + wg, 128, redo)) {
#pragma unroll 1
        for (int ul = units; ul != 8; ul >>= 4) {
          const int u = ul & 7;
          if (!bar_red_or(1 + wg, 128, redo >> u & 1)) continue;
          const int h = u >> 2, qb = 3 - (u & 3);
          uint32_t qf[8], p[16];
          float o[20], m0 = -INFINITY, m1 = -INFINITY;
          load_q(qf, u);
#pragma unroll
          for (int i = 0; i < 20; i++) o[i] = 0.f;
#pragma unroll 1
          for (int j = 0; j <= (rb == 0 ? qb : 4); j++) {
            const int b = qb + 4 - j;
            float s[32];
            wg_fence();
            qk64(s, qf, kdesc(h, b));
            wg_commit();
            wg_wait<0>();
            fence_regs<32>(s);
            float mx0 = m0, mx1 = m1;
#pragma unroll
            for (int c = 0; c < 8; c++) {
#pragma unroll
              for (int i = 0; i < 4; i++) {
                const int diff = j * 64 + (16 * wi + g + (i >> 1) * 8) - (8 * c + 2 * q + (i & 1));
                if (diff < 0 || diff > 255) s[4 * c + i] = -INFINITY;
              }
              mx0 = fmaxf(mx0, fmaxf(s[4 * c], s[4 * c + 1]));
              mx1 = fmaxf(mx1, fmaxf(s[4 * c + 2], s[4 * c + 3]));
            }
            mx0 = fmaxf(mx0, __shfl_xor_sync(0xffffffffu, mx0, 1)); mx1 = fmaxf(mx1, __shfl_xor_sync(0xffffffffu, mx1, 1));
            mx0 = fmaxf(mx0, __shfl_xor_sync(0xffffffffu, mx0, 2)); mx1 = fmaxf(mx1, __shfl_xor_sync(0xffffffffu, mx1, 2));
            const float r0 = j == 0 ? 0.f : ex2(m0 - mx0), r1 = j == 0 ? 0.f : ex2(m1 - mx1);
            m0 = mx0; m1 = mx1;
#pragma unroll
            for (int i = 0; i < 5; i++) { o[4 * i] *= r0; o[4 * i + 1] *= r0; o[4 * i + 2] *= r1; o[4 * i + 3] *= r1; }
#pragma unroll
            for (int c = 0; c < 8; c++) { s[4 * c] -= m0; s[4 * c + 1] -= m0; s[4 * c + 2] -= m1; s[4 * c + 3] -= m1; }
            exp_pack<8>(s, p);
            fence_regs<20>(o); fence_regs_u<16>(p);
            wg_fence();
            pv32(o, p, vdesc(h, b)); pv32(o, p + 8, vdesc(h, b) + 2 * VSTEP);
            wg_commit();
            wg_wait<0>();
            fence_regs<20>(o);
          }
          named_bar(1 + wg, 128);
          if (redo >> u & 1) store_o(o, u);
          __syncwarp();
        }
      }
      if (wi == 0) PROF(6 + wg);
    }
    pass_v = pass + 1;
  }
}

}

typedef CUresult (*EncodeFn)(CUtensorMap*, CUtensorMapDataType, cuuint32_t, void*, const cuuint64_t*, const cuuint64_t*,
                             const cuuint32_t*, const cuuint32_t*, CUtensorMapInterleave, CUtensorMapSwizzle,
                             CUtensorMapL2promotion, CUtensorMapFloatOOBfill);
static EncodeFn g_encode = nullptr;
struct Dim { uint64_t size, stride; uint32_t box; };
template <int N> static CUtensorMap make_map(const void* ptr, const Dim (&d)[N], int swizzle) {
  CUtensorMap m;
  cuuint64_t dims[N], strides[N];
  cuuint32_t box[N], es[N];
  for (int i = 0; i < N; i++) { dims[i] = d[i].size; strides[i] = d[i].stride; box[i] = d[i].box; es[i] = 1; }
  g_encode(&m, CU_TENSOR_MAP_DATA_TYPE_BFLOAT16, N, const_cast<void*>(ptr), dims, strides + 1, box, es, CU_TENSOR_MAP_INTERLEAVE_NONE,
           swizzle == 128 ? CU_TENSOR_MAP_SWIZZLE_128B : (swizzle == 64 ? CU_TENSOR_MAP_SWIZZLE_64B : CU_TENSOR_MAP_SWIZZLE_NONE),
           swizzle ? CU_TENSOR_MAP_L2_PROMOTION_L2_256B : CU_TENSOR_MAP_L2_PROMOTION_L2_128B, CU_TENSOR_MAP_FLOAT_OOB_FILL_NONE);
  return m;
}
static CUtensorMap map2(const void* ptr, uint64_t inner, uint64_t outer, uint32_t bi, uint32_t bo, int swizzle) {
  const Dim d[2] = {{inner, 0, bi}, {outer, inner * 2, bo}};
  return make_map(ptr, d, swizzle);
}
template <class T> static void* sym_addr(T& sym) { void* p = nullptr; cudaGetSymbolAddress(&p, sym); return p; }

static Params h_p;
static const void* h_key[9];

static cudaLaunchConfig_t launch_cfg(int grid, cudaLaunchAttribute* at) {
  cudaLaunchConfig_t cfg = {};
  cfg.gridDim = dim3(grid); cfg.blockDim = dim3(512); cfg.dynamicSmemBytes = SMEM_BYTES; cfg.stream = cudaStreamPerThread;
  at[0].id = cudaLaunchAttributeClusterDimension;
  at[0].val.clusterDim.x = 2; at[0].val.clusterDim.y = 1; at[0].val.clusterDim.z = 1;
  cfg.attrs = at; cfg.numAttrs = 1;
  return cfg;
}

extern "C" void kernel_launch(void* const* d_in, const int* in_sizes, int n_in, void* d_out, int out_size) {
  const bf16* x = (const bf16*)d_in[0];
  const bf16* wqkv = (const bf16*)d_in[1];
  const bf16* wo = (const bf16*)d_in[2];
  cudaLaunchAttribute at[1];
  bool fresh = g_encode != nullptr && h_key[8] == d_out;
  for (int i = 0; i < 8; i++) fresh = fresh && h_key[i] == d_in[i];
  if (!fresh) {
    if (!g_encode) {
      void* fn = nullptr;
      cudaDriverEntryPointQueryResult st;
      cudaGetDriverEntryPoint("cuTensorMapEncodeTiled", &fn, cudaEnableDefault, &st);
      g_encode = (EncodeFn)fn;
      cudaFuncSetAttribute(mega_kernel, cudaFuncAttributeMaxDynamicSharedMemorySize, SMEM_BYTES);
    }
    bf16* x1 = (bf16*)sym_addr(g_x1);
    Params& p = h_p;
    p.w_r = (const bf16*)d_in[4]; p.w_d = (const bf16*)d_in[7];
    p.out = (bf16*)d_out;
    p.mapA[0] = map2(x, DM, SEQ, 64, 256, 128);
    p.mapA[1] = map2(x1, DM, SEQ, 64, 256, 128);
    { const Dim d[3] = {{DM, 0, 64}, {DM, 3 * DM * 2, 16}, {3, DM * 2, 3}}; p.mapW = make_map(wqkv, d, 128); }
    { const Dim d[3] = {{DM, 0, 64}, {DM, 3 * DM * 2, 32}, {3, DM * 2, 3}}; p.mapWs = make_map(wqkv, d, 128); }
    { const Dim d[3] = {{DM, 0, 64}, {64, DM * 2, 32}, {16, 64 * DM * 2, 2}}; p.mapWo = make_map(wo, d, 128); }
    p.mapRes[0] = map2(x, DM, SEQ, 64, 64, 128);
    p.mapRes[1] = p.mapXst[0] = map2(x1, DM, SEQ, 64, 64, 128);
    p.mapXst[1] = map2(d_out, DM, SEQ, 64, 64, 128);
    p.mapG = map2(d_in[5], FF, DM, 56, 128, 0);
    p.mapU = map2(d_in[6], FF, DM, 56, 128, 0);
    { const Dim d[3] = {{64, 0, 64}, {FF, DM * 2, 28}, {DM / 64, 128, 8}}; p.mapD = make_map(p.w_d, d, 128); }
    for (int b = 0; b < 128; b++) {
      static const int perm[8] = {0, 6, 4, 5, 1, 2, 3, 7};
      const int c = b >> 1, col = c < 4 ? 0 : (c < 36 ? (c - 4) & 7 : (c - 36) % 7 + 1), j = c < 4 ? 4 + c : (c < 36 ? (c - 4) >> 3 : 4 + (c - 36) / 7);
      p.role[b] = (b & 1) | (perm[col] >> 1) << 1 | j << 3 | (perm[col] & 1) << 6;
    }
    for (int i = 0; i < 8; i++) h_key[i] = d_in[i];
    h_key[8] = d_out;
  }
  void* a0[] = {&h_p};
  cudaLaunchConfig_t cfg = launch_cfg(128, at);
  cudaLaunchKernelExC(&cfg, (const void*)mega_kernel, a0);
}
```
